```python
import torch

def _softmax(x, axis=-1):
    return torch.softmax(x, dim=axis)
def _gelu(x):
    return torch.nn.functional.gelu(x, approximate="tanh")
def _silu(x):
    return torch.nn.functional.silu(x)
def _sigmoid(x):
    return torch.sigmoid(x)
def _layernorm(x, axis=-1, eps=1e-5):
    m = x.mean(dim=axis, keepdim=True)
    v = x.var(dim=axis, keepdim=True, unbiased=False)
    return (x - m) / torch.sqrt(v + eps)
def _scatter_add(tgt, idx, src, axis=0):
    return tgt.clone().index_add_(axis, idx, src)
def _segment_sum(src, seg, n):
    out = torch.zeros((n,) + src.shape[1:], dtype=src.dtype)
    return out.index_add_(0, seg, src)
def _pad(x, pw):
    flat = tuple(v for pair in reversed(pw) for v in pair)
    return torch.nn.functional.pad(x, flat)

kernel_name = 'parallel_sum__ssm_conv_s5__glu_gated_glu__prompt'

def setup_inputs():

    _w = (lambda a: (lambda t: t.to(torch.bfloat16) if t.is_floating_point() else t)(torch.as_tensor(a)))
    def _A_setup():
        B, S, D = 1, 2048, 576
        P = D
        Lambda_re = -0.5 * (lambda _x: torch.exp(torch.as_tensor(_x)))((lambda *s: torch.randn(*s, dtype=torch.bfloat16) * 0.8)(P))
        Lambda_im = (lambda *s: torch.randn(*s, dtype=torch.bfloat16) * 0.8)(P) * 1.0
        B_re = (lambda *s: torch.randn(*s, dtype=torch.bfloat16) * 0.8)(P, D) * (D ** -0.5)
        B_im = (lambda *s: torch.randn(*s, dtype=torch.bfloat16) * 0.8)(P, D) * (D ** -0.5)
        C_re = (lambda *s: torch.randn(*s, dtype=torch.bfloat16) * 0.8)(D, P) * (P ** -0.5)
        C_im = (lambda *s: torch.randn(*s, dtype=torch.bfloat16) * 0.8)(D, P) * (P ** -0.5)
        log_dt = (lambda *s: torch.randn(*s, dtype=torch.bfloat16) * 0.8)(P) * 0.3 - 2.0
        Dskip = (lambda *s: torch.randn(*s, dtype=torch.bfloat16) * 0.8)(D)
        return {
            "x": _w((lambda *s: torch.randn(*s, dtype=torch.bfloat16) * 0.05)(B, S, D)),
            "Lambda_re": _w(Lambda_re),
            "Lambda_im": _w(Lambda_im),
            "B_re": _w(B_re),
            "B_im": _w(B_im),
            "C_re": _w(C_re),
            "C_im": _w(C_im),
            "log_dt": _w(log_dt),
            "Dskip": _w(Dskip),
        }
    _A_in = _A_setup()

    def _B_setup():
        B, S, D, F = 1, 2048, 576, 4608
        return {
            "x": _w((lambda *s: torch.randn(*s, dtype=torch.bfloat16) * 0.05)(B, S, D)),
            "w_gate": _w((lambda *s: torch.randn(*s, dtype=torch.bfloat16) * 0.05)(D, F)),
            "w_up": _w((lambda *s: torch.randn(*s, dtype=torch.bfloat16) * 0.05)(D, F)),
            "w_down": _w((lambda *s: torch.randn(*s, dtype=torch.bfloat16) * 0.05)(F, D)),
        }
    _B_in = _B_setup()

    return {
        "A_x": _A_in["x"],
        "A_Lambda_re": _A_in["Lambda_re"],
        "A_Lambda_im": _A_in["Lambda_im"],
        "A_B_re": _A_in["B_re"],
        "A_B_im": _A_in["B_im"],
        "A_C_re": _A_in["C_re"],
        "A_C_im": _A_in["C_im"],
        "A_log_dt": _A_in["log_dt"],
        "A_Dskip": _A_in["Dskip"],
        "B_x": _B_in["x"],
        "B_w_gate": _B_in["w_gate"],
        "B_w_up": _B_in["w_up"],
        "B_w_down": _B_in["w_down"],
    }

def reference(A_x, A_Lambda_re, A_Lambda_im, A_B_re, A_B_im, A_C_re, A_C_im, A_log_dt, A_Dskip, B_x, B_w_gate, B_w_up, B_w_down):
    def _A_ref(x, Lambda_re, Lambda_im, B_re, B_im, C_re, C_im, log_dt, Dskip):
        Bsz, L, H = x.shape
        Lam = Lambda_re + 1j * Lambda_im
        Bmat = B_re + 1j * B_im
        Cmat = C_re + 1j * C_im
        dt = torch.exp(log_dt)
        Lam_bar = torch.exp(dt * Lam)
        B_bar = ((Lam_bar - 1.0) / Lam)[:, None] * Bmat
        Bu = torch.einsum("bld,pd->blp", x + 0j, B_bar)
        h = torch.zeros_like(Bu[:, 0, :])
        hs = []
        for t in range(L):
            h = Lam_bar[None, :] * h + Bu[:, t, :]
            hs.append(h)
        hseq = torch.stack(hs, 1)
        y = 2.0 * torch.einsum("blp,dp->bld", hseq, Cmat).real + x * Dskip[None, None, :]
        return y

    def _B_ref(x, w_gate, w_up, w_down):
        g = torch.einsum("bsd,df->bsf", x, w_gate)
        u = torch.einsum("bsd,df->bsf", x, w_up)
        h = _sigmoid(g) * u
        return torch.einsum("bsf,fd->bsd", h, w_down)

    x = A_x
    xn = _layernorm(x, axis=-1)
    return x + _A_ref(xn, A_Lambda_re, A_Lambda_im, A_B_re, A_B_im, A_C_re, A_C_im, A_log_dt, A_Dskip) + _B_ref(xn, B_w_gate, B_w_up, B_w_down)
```

```cpp
#include <cuda_runtime.h>
#include <cuda.h>
#include <cuda_bf16.h>
#include <stdint.h>

namespace {

#define USE_MC 1
#define SKEW 3

constexpr int kS = 2048, kD = 576, kF = 4608;
constexpr int NST = 6;
constexpr uint32_t SLOT = 16384;
constexpr uint32_t OFF_H = NST * SLOT;
constexpr uint32_t OFF_MISC = OFF_H + 131072;
constexpr uint32_t OFF_BAR = OFF_MISC;
constexpr uint32_t OFF_STAT = OFF_MISC + 256;
constexpr uint32_t OFF_CONST = OFF_STAT + 1024;
constexpr uint32_t SMEM_BYTES = OFF_CONST + 6 * 72 * 4;
static_assert(SMEM_BYTES <= 232448, "smem");
constexpr uint32_t H_DUMP = 65536 - 64 * 576;
constexpr uint32_t H_STG = 0;
constexpr uint32_t H_HS = 32768;
constexpr uint32_t HS_BYTES = 18432;

enum { B_FULL = 0, B_EMPTY = NST, B_XFULL = 2 * NST, B_SCAN = B_XFULL + 2, B_INIT, B_HFREE, B_HSFULL = B_HFREE + 2 };
enum { NB_SKEW = 1, NB_WG = 2  , NB_SCAN = 4, NB_DUMP = 5 };

struct __align__(64) Params {
  CUtensorMap tx, tBre, tBim, tWg, tWu, tWd, tCre, tCim, tCre8, tCim8, tOut;
  const __nv_bfloat16 *x, *lre, *lim, *ldt, *dskip;
  float* out;
};

__device__ unsigned g_epoch[128];
__device__ unsigned g_initcnt[16];
__device__ uint2 g_S[2][16][576];
__device__ __align__(128) uint8_t g_hs[128][2 * HS_BYTES];
#define STAMP(role, i)

__device__ __forceinline__ void wgmma_n72_rs_tb0(float (&d)[36], uint32_t a0, uint32_t a1, uint32_t a2, uint32_t a3, uint64_t db, int scale_d) {
  asm volatile("{\n.reg .pred p;\nsetp.ne.b32 p, %41, 0;\n"
    "wgmma.mma_async.sync.aligned.m64n72k16.f32.bf16.bf16 {"
    "%0, %1, %2, %3, %4, %5, %6, %7, %8, %9, %10, %11, %12, %13, %14, %15, "
    "%16, %17, %18, %19, %20, %21, %22, %23, %24, %25, %26, %27, %28, %29, %30, %31, "
    "%32, %33, %34, %35"
    "}, {%36, %37, %38, %39}, %40, p, 1, 1, 0;\n}\n"
    : "+f"(d[0]), "+f"(d[1]), "+f"(d[2]), "+f"(d[3]), "+f"(d[4]), "+f"(d[5]), "+f"(d[6]), "+f"(d[7]),
      "+f"(d[8]), "+f"(d[9]), "+f"(d[10]), "+f"(d[11]), "+f"(d[12]), "+f"(d[13]), "+f"(d[14]), "+f"(d[15]),
      "+f"(d[16]), "+f"(d[17]), "+f"(d[18]), "+f"(d[19]), "+f"(d[20]), "+f"(d[21]), "+f"(d[22]), "+f"(d[23]),
      "+f"(d[24]), "+f"(d[25]), "+f"(d[26]), "+f"(d[27]), "+f"(d[28]), "+f"(d[29]), "+f"(d[30]), "+f"(d[31]),
      "+f"(d[32]), "+f"(d[33]), "+f"(d[34]), "+f"(d[35])
    : "r"(a0), "r"(a1), "r"(a2), "r"(a3), "l"(db), "r"(scale_d));
}
__device__ __forceinline__ void wgmma_n128_rs_tb1(float (&d)[64], uint32_t a0, uint32_t a1, uint32_t a2, uint32_t a3, uint64_t db, int scale_d) {
  asm volatile("{\n.reg .pred p;\nsetp.ne.b32 p, %69, 0;\n"
    "wgmma.mma_async.sync.aligned.m64n128k16.f32.bf16.bf16 {"
    "%0, %1, %2, %3, %4, %5, %6, %7, %8, %9, %10, %11, %12, %13, %14, %15, "
    "%16, %17, %18, %19, %20, %21, %22, %23, %24, %25, %26, %27, %28, %29, %30, %31, "
    "%32, %33, %34, %35, %36, %37, %38, %39, %40, %41, %42, %43, %44, %45, %46, %47, "
    "%48, %49, %50, %51, %52, %53, %54, %55, %56, %57, %58, %59, %60, %61, %62, %63"
    "}, {%64, %65, %66, %67}, %68, p, 1, 1, 1;\n}\n"
    : "+f"(d[0]), "+f"(d[1]), "+f"(d[2]), "+f"(d[3]), "+f"(d[4]), "+f"(d[5]), "+f"(d[6]), "+f"(d[7]),
      "+f"(d[8]), "+f"(d[9]), "+f"(d[10]), "+f"(d[11]), "+f"(d[12]), "+f"(d[13]), "+f"(d[14]), "+f"(d[15]),
      "+f"(d[16]), "+f"(d[17]), "+f"(d[18]), "+f"(d[19]), "+f"(d[20]), "+f"(d[21]), "+f"(d[22]), "+f"(d[23]),
      "+f"(d[24]), "+f"(d[25]), "+f"(d[26]), "+f"(d[27]), "+f"(d[28]), "+f"(d[29]), "+f"(d[30]), "+f"(d[31]),
      "+f"(d[32]), "+f"(d[33]), "+f"(d[34]), "+f"(d[35]), "+f"(d[36]), "+f"(d[37]), "+f"(d[38]), "+f"(d[39]),
      "+f"(d[40]), "+f"(d[41]), "+f"(d[42]), "+f"(d[43]), "+f"(d[44]), "+f"(d[45]), "+f"(d[46]), "+f"(d[47]),
      "+f"(d[48]), "+f"(d[49]), "+f"(d[50]), "+f"(d[51]), "+f"(d[52]), "+f"(d[53]), "+f"(d[54]), "+f"(d[55]),
      "+f"(d[56]), "+f"(d[57]), "+f"(d[58]), "+f"(d[59]), "+f"(d[60]), "+f"(d[61]), "+f"(d[62]), "+f"(d[63])
    : "r"(a0), "r"(a1), "r"(a2), "r"(a3), "l"(db), "r"(scale_d));
}
__device__ __forceinline__ void wgmma_n128_ss_tb0(float (&d)[64], uint64_t da, uint64_t db, int scale_d) {
  asm volatile("{\n.reg .pred p;\nsetp.ne.b32 p, %66, 0;\n"
    "wgmma.mma_async.sync.aligned.m64n128k16.f32.bf16.bf16 {"
    "%0, %1, %2, %3, %4, %5, %6, %7, %8, %9, %10, %11, %12, %13, %14, %15, "
    "%16, %17, %18, %19, %20, %21, %22, %23, %24, %25, %26, %27, %28, %29, %30, %31, "
    "%32, %33, %34, %35, %36, %37, %38, %39, %40, %41, %42, %43, %44, %45, %46, %47, "
    "%48, %49, %50, %51, %52, %53, %54, %55, %56, %57, %58, %59, %60, %61, %62, %63"
    "}, %64, %65, p, 1, 1, 0, 0;\n}\n"
    : "+f"(d[0]), "+f"(d[1]), "+f"(d[2]), "+f"(d[3]), "+f"(d[4]), "+f"(d[5]), "+f"(d[6]), "+f"(d[7]),
      "+f"(d[8]), "+f"(d[9]), "+f"(d[10]), "+f"(d[11]), "+f"(d[12]), "+f"(d[13]), "+f"(d[14]), "+f"(d[15]),
      "+f"(d[16]), "+f"(d[17]), "+f"(d[18]), "+f"(d[19]), "+f"(d[20]), "+f"(d[21]), "+f"(d[22]), "+f"(d[23]),
      "+f"(d[24]), "+f"(d[25]), "+f"(d[26]), "+f"(d[27]), "+f"(d[28]), "+f"(d[29]), "+f"(d[30]), "+f"(d[31]),
      "+f"(d[32]), "+f"(d[33]), "+f"(d[34]), "+f"(d[35]), "+f"(d[36]), "+f"(d[37]), "+f"(d[38]), "+f"(d[39]),
      "+f"(d[40]), "+f"(d[41]), "+f"(d[42]), "+f"(d[43]), "+f"(d[44]), "+f"(d[45]), "+f"(d[46]), "+f"(d[47]),
      "+f"(d[48]), "+f"(d[49]), "+f"(d[50]), "+f"(d[51]), "+f"(d[52]), "+f"(d[53]), "+f"(d[54]), "+f"(d[55]),
      "+f"(d[56]), "+f"(d[57]), "+f"(d[58]), "+f"(d[59]), "+f"(d[60]), "+f"(d[61]), "+f"(d[62]), "+f"(d[63])
    : "l"(da), "l"(db), "r"(scale_d));
}
__device__ __forceinline__ void wgmma_n64_rs_tb1(float (&d)[32], uint32_t a0, uint32_t a1, uint32_t a2, uint32_t a3, uint64_t db, int scale_d) {
  asm volatile("{\n.reg .pred p;\nsetp.ne.b32 p, %37, 0;\n"
    "wgmma.mma_async.sync.aligned.m64n64k16.f32.bf16.bf16 {"
    "%0, %1, %2, %3, %4, %5, %6, %7, %8, %9, %10, %11, %12, %13, %14, %15, "
    "%16, %17, %18, %19, %20, %21, %22, %23, %24, %25, %26, %27, %28, %29, %30, %31"
    "}, {%32, %33, %34, %35}, %36, p, 1, 1, 1;\n}\n"
    : "+f"(d[0]), "+f"(d[1]), "+f"(d[2]), "+f"(d[3]), "+f"(d[4]), "+f"(d[5]), "+f"(d[6]), "+f"(d[7]),
      "+f"(d[8]), "+f"(d[9]), "+f"(d[10]), "+f"(d[11]), "+f"(d[12]), "+f"(d[13]), "+f"(d[14]), "+f"(d[15]),
      "+f"(d[16]), "+f"(d[17]), "+f"(d[18]), "+f"(d[19]), "+f"(d[20]), "+f"(d[21]), "+f"(d[22]), "+f"(d[23]),
      "+f"(d[24]), "+f"(d[25]), "+f"(d[26]), "+f"(d[27]), "+f"(d[28]), "+f"(d[29]), "+f"(d[30]), "+f"(d[31])
    : "r"(a0), "r"(a1), "r"(a2), "r"(a3), "l"(db), "r"(scale_d));
}
__device__ __forceinline__ void wgmma_n64_ss_tb0(float (&d)[32], uint64_t da, uint64_t db, int scale_d) {
  asm volatile("{\n.reg .pred p;\nsetp.ne.b32 p, %34, 0;\n"
    "wgmma.mma_async.sync.aligned.m64n64k16.f32.bf16.bf16 {"
    "%0, %1, %2, %3, %4, %5, %6, %7, %8, %9, %10, %11, %12, %13, %14, %15, "
    "%16, %17, %18, %19, %20, %21, %22, %23, %24, %25, %26, %27, %28, %29, %30, %31"
    "}, %32, %33, p, 1, 1, 0, 0;\n}\n"
    : "+f"(d[0]), "+f"(d[1]), "+f"(d[2]), "+f"(d[3]), "+f"(d[4]), "+f"(d[5]), "+f"(d[6]), "+f"(d[7]),
      "+f"(d[8]), "+f"(d[9]), "+f"(d[10]), "+f"(d[11]), "+f"(d[12]), "+f"(d[13]), "+f"(d[14]), "+f"(d[15]),
      "+f"(d[16]), "+f"(d[17]), "+f"(d[18]), "+f"(d[19]), "+f"(d[20]), "+f"(d[21]), "+f"(d[22]), "+f"(d[23]),
      "+f"(d[24]), "+f"(d[25]), "+f"(d[26]), "+f"(d[27]), "+f"(d[28]), "+f"(d[29]), "+f"(d[30]), "+f"(d[31])
    : "l"(da), "l"(db), "r"(scale_d));
}

__device__ __forceinline__ bool elect() {
  uint32_t p;
  asm volatile("{.reg .pred q; elect.sync _|q, 0xffffffff; selp.u32 %0,1,0,q;}" : "=r"(p));
  return p;
}
__device__ __forceinline__ void mbar_init(uint32_t bar, uint32_t cnt) { asm volatile("mbarrier.init.shared::cta.b64 [%0], %1;" ::"r"(bar), "r"(cnt) : "memory"); }
__device__ __forceinline__ void mbar_expect(uint32_t bar, uint32_t bytes) { asm volatile("mbarrier.arrive.expect_tx.shared::cta.b64 _, [%0], %1;" ::"r"(bar), "r"(bytes) : "memory"); }
__device__ __forceinline__ void mbar_arrive(uint32_t bar) { asm volatile("mbarrier.arrive.shared::cta.b64 _, [%0];" ::"r"(bar) : "memory"); }
__device__ __forceinline__ void mbar_arrive_cta(uint32_t bar, uint32_t cta) {
  asm volatile("{.reg .b32 ra; mapa.shared::cluster.u32 ra, %0, %1; mbarrier.arrive.shared::cluster.b64 _, [ra];}" ::"r"(bar), "r"(cta) : "memory");
}
__device__ __forceinline__ void mbar_wait(uint32_t bar, uint32_t parity) {
  asm volatile(
      "{\n.reg .pred p;\n.reg .u32 c, t;\n"
      "mbarrier.try_wait.parity.shared::cta.b64 p, [%0], %1;\n@p bra DONE;\n"
      "mov.u32 c, %%clock;\n"
      "LAB_WAIT:\nmbarrier.try_wait.parity.shared::cta.b64 p, [%0], %1;\n@p bra DONE;\n"
      "mov.u32 t, %%clock;\nsub.u32 t, t, c;\nsetp.lt.u32 p, t, 0x40000000;\n@p bra LAB_WAIT;\ntrap;\nDONE:\n}" ::"r"(bar), "r"(parity) : "memory");
}
__device__ __forceinline__ void bar_sync(int id, int n) { asm volatile("bar.sync %0, %1;" ::"r"(id), "r"(n) : "memory"); }
__device__ __forceinline__ void bar_arrive(int id, int n) { asm volatile("bar.arrive %0, %1;" ::"r"(id), "r"(n) : "memory"); }
__device__ __forceinline__ void wg_fence() { asm volatile("wgmma.fence.sync.aligned;" ::: "memory"); }
__device__ __forceinline__ void wg_commit() { asm volatile("wgmma.commit_group.sync.aligned;" ::: "memory"); }
template <int N> __device__ __forceinline__ void wg_wait() { asm volatile("wgmma.wait_group.sync.aligned %0;" ::"n"(N) : "memory"); }
__device__ __forceinline__ void tma2d(uint32_t dst, const CUtensorMap* tm, uint32_t bar, int c0, int c1) {
  asm volatile("cp.async.bulk.tensor.2d.shared::cluster.global.mbarrier::complete_tx::bytes [%0], [%1,{%3,%4}], [%2];" ::"r"(dst), "l"(tm), "r"(bar), "r"(c0), "r"(c1) : "memory");
}
__device__ __forceinline__ void tma2d_mc(uint32_t dst, const CUtensorMap* tm, uint32_t bar, int c0, int c1) {
  asm volatile("cp.async.bulk.tensor.2d.shared::cluster.global.mbarrier::complete_tx::bytes.multicast::cluster [%0], [%1,{%3,%4}], [%2], %5;" ::"r"(dst), "l"(tm), "r"(bar), "r"(c0), "r"(c1), "h"((uint16_t)3) : "memory");
}
__device__ __forceinline__ void tma_prefetch2d(const CUtensorMap* tm, int c0, int c1) {
  asm volatile("cp.async.bulk.prefetch.tensor.2d.L2.global.tile [%0,{%1,%2}];" ::"l"(tm), "r"(c0), "r"(c1) : "memory");
}
__device__ __forceinline__ uint64_t desc(uint32_t lo, uint32_t hi) { return ((uint64_t)hi << 32) | lo; }
constexpr uint32_t DHI_SW128 = (1024 >> 4) | (1u << 30);
constexpr uint32_t DHI_NONE = (128 >> 4);
constexpr uint32_t DLO_MN = (8192 >> 4) << 16;
constexpr uint32_t DLO_K = 1u << 16;
__device__ __forceinline__ float tanh_fast(float x) { float y; asm("tanh.approx.f32 %0, %1;" : "=f"(y) : "f"(x)); return y; }
__device__ __forceinline__ uint32_t pack_bf16(float lo, float hi) { uint32_t r; asm("cvt.rn.bf16x2.f32 %0, %1, %2;" : "=r"(r) : "f"(hi), "f"(lo)); return r; }
__device__ __forceinline__ float rbf(float x) { return __bfloat162float(__float2bfloat16_rn(x)); }
__device__ __forceinline__ void mma16816(float (&c)[4], uint32_t a0, uint32_t a1, uint32_t a2, uint32_t a3, uint32_t b0, uint32_t b1) {
  asm volatile("mma.sync.aligned.m16n8k16.row.col.f32.bf16.bf16.f32 {%0,%1,%2,%3}, {%4,%5,%6,%7}, {%8,%9}, {%0,%1,%2,%3};"
               : "+f"(c[0]), "+f"(c[1]), "+f"(c[2]), "+f"(c[3]) : "r"(a0), "r"(a1), "r"(a2), "r"(a3), "r"(b0), "r"(b1));
}
__device__ __forceinline__ void sts128(uint32_t a, uint32_t x, uint32_t y, uint32_t z, uint32_t w) {
  asm volatile("st.shared.v4.b32 [%0], {%1,%2,%3,%4};" ::"r"(a), "r"(x), "r"(y), "r"(z), "r"(w) : "memory");
}
__device__ __forceinline__ void sts64f(uint32_t a, float x, float y) { asm volatile("st.shared.v2.f32 [%0], {%1,%2};" ::"r"(a), "f"(x), "f"(y) : "memory"); }
__device__ __forceinline__ float2 lds64f(uint32_t a) { float2 v; asm volatile("ld.shared.v2.f32 {%0,%1}, [%2];" : "=f"(v.x), "=f"(v.y) : "r"(a) : "memory"); return v; }
__device__ __forceinline__ float lds32f(uint32_t a) { float v; asm volatile("ld.shared.f32 %0, [%1];" : "=f"(v) : "r"(a) : "memory"); return v; }
template <int N> __device__ __forceinline__ void keep(float (&a)[N]) {
#pragma unroll
  for (int i = 0; i < N; i++) asm volatile("" : "+f"(a[i])::"memory");
}

template <bool MC>
__global__ void __launch_bounds__(384, 1) fused_kernel(const __grid_constant__ Params prm) {
  extern __shared__ __align__(1024) uint8_t smem[];
  const int warp = __shfl_sync(0xffffffffu, threadIdx.x >> 5, 0);
  const uint32_t sb = __shfl_sync(0xffffffffu, (uint32_t)__cvta_generic_to_shared(smem), 0);
  const int rank = MC ? (blockIdx.x & 1) : 0;
  const int j = MC ? ((blockIdx.x >> 1) & 7) : (blockIdx.x & 7);
  const int m = MC ? ((blockIdx.x >> 4) * 2 + rank) : (blockIdx.x >> 3);
  const uint32_t bars = sb + OFF_BAR;

  if (warp == 8) {
    if (elect()) {
      if (sb & 1023) __trap();
      for (int i = 0; i < NST; i++) { mbar_init(bars + 8 * (B_FULL + i), 1); mbar_init(bars + 8 * (B_EMPTY + i), MC ? 4 : 2); }
      mbar_init(bars + 8 * B_SCAN, 1); mbar_init(bars + 8 * B_INIT, 1);
      for (int w = 0; w < 2; w++) { mbar_init(bars + 8 * (B_XFULL + w), 1); mbar_init(bars + 8 * (B_HFREE + w), 4); mbar_init(bars + 8 * (B_HSFULL + w), 1); }
      asm volatile("fence.mbarrier_init.release.cluster;" ::: "memory");
      asm volatile("fence.proxy.async.shared::cta;" ::: "memory");
      mbar_expect(bars + 8 * B_XFULL, 65536);
      for (int kb = 0; kb < 8; kb++) tma2d(sb + OFF_H + kb * 8192, &prm.tx, bars + 8 * B_XFULL, kb * 64, m * 128);
      mbar_expect(bars + 8 * B_FULL, 16384);
      tma2d(sb, &prm.tx, bars + 8 * B_FULL, 512, m * 128);
      tma2d(sb + 8192, &prm.tx, bars + 8 * B_FULL, 512, m * 128 + 64);
      mbar_expect(bars + 8 * (B_XFULL + 1), 65536);
      for (int kb = 0; kb < 8; kb++) tma2d(sb + OFF_H + 65536 + kb * 8192, &prm.tx, bars + 8 * (B_XFULL + 1), kb * 64, m * 128 + 64);
    }
    __syncwarp();
  }
  if (MC) { asm volatile("barrier.cluster.arrive.release.aligned;\nbarrier.cluster.wait.acquire.aligned;" ::: "memory"); }
  else __syncthreads();

  if (warp >= 8) {
    asm volatile("setmaxnreg.dec.sync.aligned.u32 24;");
    if (warp == 8) {
      int s = 1; uint32_t ph = 1;
      uint32_t dst, fb; bool e;
      auto acquire = [&](uint32_t bytes) {
        mbar_wait(bars + 8 * (B_EMPTY + s), ph);
        fb = bars + 8 * (B_FULL + s); dst = sb + s * SLOT;
        e = elect();
        if (e) mbar_expect(fb, bytes);
        if (++s == NST) { s = 0; ph ^= 1; }
      };
      auto two = [&](const CUtensorMap* t0, uint32_t o0, int a0, int b0, const CUtensorMap* t1, uint32_t o1, int a1, int b1) {
        if (MC) { if (e) tma2d_mc(dst + (rank ? o1 : o0), rank ? t1 : t0, fb, rank ? a1 : a0, rank ? b1 : b0); }
        else if (e) { tma2d(dst + o0, t0, fb, a0, b0); tma2d(dst + o1, t1, fb, a1, b1); }
      };
      auto one = [&](const CUtensorMap* t, int a, int b, int who) {
        if (MC) { if (e && rank == who) tma2d_mc(dst, t, fb, a, b); }
        else if (e) tma2d(dst, t, fb, a, b);
      };
      for (int kb = 0; kb < 9; kb++) { acquire(9216); one(&prm.tBre, kb * 64, j * 72, kb & 1); }
      for (int kb = 0; kb < 9; kb++) { acquire(9216); one(&prm.tBim, kb * 64, j * 72, (kb & 1) ^ 1); }
      for (int c = 0; c < 9; c++) {
        const int col = j * 576 + c * 64;
        for (int kb = 0; kb < 9; kb++) { acquire(16384); two(&prm.tWg, 0, col, kb * 64, &prm.tWu, 8192, col, kb * 64); }
      }
      for (int t = 0; t < 4; t++) {
        const int n0 = ((t + j) & 3) * 128;
        for (int kb = 0; kb < 9; kb++) { acquire(16384); two(&prm.tWd, 0, n0, j * 576 + kb * 64, &prm.tWd, 8192, n0 + 64, j * 576 + kb * 64); }
        acquire(16384); two(&prm.tCre, 0, j * 72, n0, &prm.tCre, 8192, j * 72, n0 + 64);
        acquire(16384); two(&prm.tCim, 0, j * 72, n0, &prm.tCim, 8192, j * 72, n0 + 64);
        acquire(4096);
        two(&prm.tCre8, 0, j * 72 + 64, n0, &prm.tCim8, 2048, j * 72 + 64, n0);
        two(&prm.tCre8, 1024, j * 72 + 64, n0 + 64, &prm.tCim8, 3072, j * 72 + 64, n0 + 64);
      }
      for (int kp = 0; kp < 4; kp++) { acquire(16384); two(&prm.tWd, 0, 512, j * 576 + kp * 128, &prm.tWd, 8192, 512, j * 576 + kp * 128 + 64); }
      acquire(8192); one(&prm.tWd, 512, j * 576 + 512, 0);
      acquire(16384); two(&prm.tCre, 0, j * 72, 512, &prm.tCim, 8192, j * 72, 512);
      acquire(2048); two(&prm.tCre8, 0, j * 72 + 64, 512, &prm.tCim8, 2048, j * 72 + 64, 512);
    } else {
      const int p = threadIdx.x - 288;
      const unsigned epoch = *(volatile unsigned*)&g_epoch[blockIdx.x];
      if (warp == 9) {
        mbar_wait(bars + 8 * (B_XFULL + 1), 0);
        if (elect()) {
          for (int id = m; id < 162; id += 16) { const int c = id / 18, r = id - c * 18; tma_prefetch2d((r & 1) ? &prm.tWu : &prm.tWg, j * 576 + c * 64, (r >> 1) * 64); }
          for (int id = m; id < 81; id += 16) { const int c = id / 9, r = id - c * 9; tma_prefetch2d(&prm.tWd, c * 64, j * 576 + r * 64); }
          if (m < 9) { tma_prefetch2d(&prm.tCre, j * 72, m * 64); tma_prefetch2d(&prm.tCim, j * 72, m * 64); }
        }
        __syncwarp();
      }
      STAMP(2, 0);
      bar_sync(NB_DUMP, 352);
      STAMP(2, 1);
      if (p < 72) {
        const float ar = lds32f(sb + OFF_CONST + p * 4), ai = lds32f(sb + OFF_CONST + 288 + p * 4);
        float hr = 0.f, hi = 0.f;
        uint32_t a = sb + OFF_H + H_DUMP + p * 4;
        if (m < 15) {
          for (int w = 0; w < 2; w++) {
#pragma unroll 4
            for (int t = 0; t < 64; t++) {
              const float2 v = make_float2(lds32f(a + t * 288), lds32f(a + t * 288 + 18432));
              const float nr = fmaf(ar, hr, fmaf(-ai, hi, v.x)), ni = fmaf(ar, hi, fmaf(ai, hr, v.y));
              hr = nr; hi = ni;
            }
            a += 65536;
          }
          asm volatile("st.relaxed.gpu.global.v2.b32 [%0], {%1,%2};" ::"l"(&g_S[epoch & 1][m][j * 72 + p]), "r"(~__float_as_uint(hr)), "r"(~__float_as_uint(hi)) : "memory");
          g_S[(epoch & 1) ^ 1][m][j * 72 + p] = make_uint2(0u, 0u);
        }
        const float br = lds32f(sb + OFF_CONST + 576 + p * 4), bi = lds32f(sb + OFF_CONST + 864 + p * 4);
        hr = 0.f; hi = 0.f;
        const uint2* sp = &g_S[epoch & 1][0][j * 72 + p];
        for (int i0 = 0; i0 < m; i0 += 4) {
          uint32_t v[4][2];
          const uint32_t t0 = (uint32_t)clock();
          bool ok;
          do {
            ok = true;
#pragma unroll
            for (int k = 0; k < 4; k++) {
              v[k][0] = v[k][1] = 0xffffffffu;
              if (i0 + k < m) asm volatile("ld.relaxed.gpu.global.v2.b32 {%0,%1}, [%2];" : "=r"(v[k][0]), "=r"(v[k][1]) : "l"(sp + (i0 + k) * 576) : "memory");
            }
#pragma unroll
            for (int k = 0; k < 4; k++) ok = ok && v[k][0] != 0u && v[k][1] != 0u;
            if ((uint32_t)clock() - t0 > 0x40000000u) __trap();
          } while (!ok);
#pragma unroll
          for (int k = 0; k < 4; k++)
            if (i0 + k < m) {
              const float nr = fmaf(br, hr, fmaf(-bi, hi, __uint_as_float(~v[k][0]))), ni = fmaf(br, hi, fmaf(bi, hr, __uint_as_float(~v[k][1])));
              hr = nr; hi = ni;
            }
        }
        const float cr = lds32f(sb + OFF_CONST + 1152 + p * 4), ci = lds32f(sb + OFF_CONST + 1440 + p * 4);
        const bool mainp = p < 64;
        const uint32_t rstep = mainp ? 128 : 16, xm = mainp ? 0x70 : 0, imd = mainp ? 8192 : 1024;
        const uint32_t pc = mainp ? ((p >> 3) << 4) : 0;
        uint8_t* gp = &g_hs[blockIdx.x][(mainp ? 0 : 16384) + (p & 7) * 2];
        a = sb + OFF_H + H_DUMP + p * 4;
        for (int w = 0; w < 2; w++) {
#pragma unroll 2
          for (int t = 0; t < 64; t++) {
            const float2 v = make_float2(lds32f(a + t * 288), lds32f(a + t * 288 + 18432));
            const float nr = fmaf(ar, hr, fmaf(-ai, hi, v.x)), ni = fmaf(ar, hi, fmaf(ai, hr, v.y));
            hr = nr; hi = ni;
            const uint32_t pk = pack_bf16(fmaf(cr, hr, -ci * hi), fmaf(-cr, hi, -ci * hr));
            uint8_t* q = gp + t * rstep + (pc ^ ((t << 4) & xm));
            *(uint16_t*)q = (uint16_t)pk;
            *(uint16_t*)(q + imd) = (uint16_t)(pk >> 16);
          }
          a += 65536; gp += HS_BYTES;
        }
        __threadfence();
        asm volatile("fence.proxy.async.global;" ::: "memory");
      }
      __syncwarp();
      bar_sync(NB_SCAN, 96);
      if (p == 0) mbar_arrive(bars + 8 * B_SCAN);
      STAMP(2, 2);
      {
        int row = p / 18, cg = p - row * 18;
        for (int it = 0; it < 24; it++) {
          const int col = j * 72 + cg * 4;
          const size_t o = (size_t)(m * 128 + row) * kD + col;
          const uint2 xv = __ldg((const uint2*)(prm.x + o)), dv = __ldg((const uint2*)(prm.dskip + col));
          const float2 st = lds64f(sb + OFF_STAT + row * 8);
          float4 r;
          { const float x0 = __uint_as_float(xv.x << 16); r.x = x0 + rbf(rbf(rbf(x0 - st.x) * st.y) * __uint_as_float(dv.x << 16)); }
          { const float x0 = __uint_as_float(xv.x & 0xffff0000u); r.y = x0 + rbf(rbf(rbf(x0 - st.x) * st.y) * __uint_as_float(dv.x & 0xffff0000u)); }
          { const float x0 = __uint_as_float(xv.y << 16); r.z = x0 + rbf(rbf(rbf(x0 - st.x) * st.y) * __uint_as_float(dv.y << 16)); }
          { const float x0 = __uint_as_float(xv.y & 0xffff0000u); r.w = x0 + rbf(rbf(rbf(x0 - st.x) * st.y) * __uint_as_float(dv.y & 0xffff0000u)); }
          *(float4*)(prm.out + o) = r;
          row += 5; cg += 6;
          if (cg >= 18) { cg -= 18; row++; }
        }
        __threadfence();
      }
      bar_sync(NB_SCAN, 96);
      if (p == 0) {
        asm volatile("red.release.gpu.global.add.u32 [%0], 1;" ::"l"(&g_initcnt[m]) : "memory");
        const unsigned target = 8u * (epoch + 1u);
        const uint32_t t0 = (uint32_t)clock();
        unsigned v;
        do {
          asm volatile("ld.acquire.gpu.global.u32 %0, [%1];" : "=r"(v) : "l"(&g_initcnt[m]) : "memory");
          if ((uint32_t)clock() - t0 > 0x40000000u) __trap();
        } while ((int)(v - target) < 0);
        mbar_arrive(bars + 8 * B_INIT);
        g_epoch[blockIdx.x] = epoch + 1u;
      }
      __syncwarp();
      STAMP(2, 3);
      if (warp == 9) {
        for (int w = 0; w < 2; w++) {
          mbar_wait(bars + 8 * (B_HFREE + w), 0);
          if (elect()) {
            mbar_expect(bars + 8 * (B_HSFULL + w), HS_BYTES);
            asm volatile("cp.async.bulk.shared::cluster.global.mbarrier::complete_tx::bytes [%0], [%1], %2, [%3];" ::"r"(sb + OFF_H + w * 65536 + H_HS),
                         "l"(&g_hs[blockIdx.x][w * HS_BYTES]), "r"(HS_BYTES), "r"(bars + 8 * (B_HSFULL + w)) : "memory");
          }
          __syncwarp();
        }
      }
    }
    if (MC) asm volatile("barrier.cluster.arrive.relaxed.aligned;\nbarrier.cluster.wait.aligned;" ::: "memory");
  } else {
    asm volatile("setmaxnreg.inc.sync.aligned.u32 240;");
    const int wg = warp >> 2, w4 = warp & 3;
    const int lane = threadIdx.x & 31, g = lane >> 2, q = lane & 3;
    const uint32_t hw = sb + OFF_H + wg * 65536;
    STAMP(wg, 0);
    if (wg == 1 && threadIdx.x < 128 + 72) {
      const int p = threadIdx.x - 128, pg = j * 72 + p;
      const float lr = __bfloat162float(prm.lre[pg]), li = __bfloat162float(prm.lim[pg]);
      const float dt = rbf(expf(__bfloat162float(prm.ldt[pg])));
      const float ea = expf(dt * lr);
      float sn, cs;
      sincosf(dt * li, &sn, &cs);
      const float ar = ea * cs, ai = ea * sn;
      float br = ar, bi = ai;
#pragma unroll
      for (int k = 0; k < 7; k++) { const float t = br * br - bi * bi; bi = 2.f * br * bi; br = t; }
      const float nr = ar - 1.f, den = 2.f / (lr * lr + li * li);
      float* cp = (float*)(smem + OFF_CONST) + p;
      cp[0] = ar; cp[72] = ai; cp[144] = br; cp[216] = bi;
      cp[288] = (nr * lr + ai * li) * den; cp[360] = (ai * lr - nr * li) * den;
    }
    __syncwarp();

    int s = 0; uint32_t ph = 0;
    auto release = [&](int st) {
      if (MC) { if ((w4 & 2) == 0) { if (elect()) mbar_arrive_cta(bars + 8 * (B_EMPTY + st), w4 & 1); } }
      else if (w4 == 0) { if (elect()) mbar_arrive(bars + 8 * (B_EMPTY + st)); }
    };
    const uint32_t dring = (sb & 0x3FFFF) >> 4;
    uint32_t dlo; int prev = 0;
    auto stage_begin = [&]() { mbar_wait(bars + 8 * (B_FULL + s), ph); dlo = dring + s * (SLOT >> 4); wg_fence(); };
    auto stage_end = [&](bool rel) {
      wg_commit();
      if (rel) { wg_wait<1>(); release(prev); }
      prev = s;
      if (++s == NST) { s = 0; ph ^= 1; }
    };

    uint32_t xa[144];
    {
      const int r = w4 * 16 + (lane & 7) + ((lane >> 3) & 1) * 8;
      const uint32_t ro = r * 128, cx = ((lane >> 4) ^ (lane & 7)) << 4;
      float sm[2][4] = {};
      mbar_wait(bars + 8 * (B_XFULL + wg), 0);
      STAMP(wg, 1);
#pragma unroll
      for (int kb = 0; kb < 9; kb++) {
        uint32_t base = hw + kb * 8192 + ro;
        if (kb == 8) { mbar_wait(bars + 8 * B_FULL, 0); base = sb + wg * 8192 + ro; }
#pragma unroll
        for (int kk = 0; kk < 4; kk++) {
          const int i = (kb * 4 + kk) * 4;
          asm volatile("ldmatrix.sync.aligned.m8n8.x4.shared.b16 {%0,%1,%2,%3}, [%4];"
                       : "=r"(xa[i]), "=r"(xa[i + 1]), "=r"(xa[i + 2]), "=r"(xa[i + 3]) : "r"(base + (cx ^ (kk << 5))) : "memory");
        }
      }
#pragma unroll
      for (int ks = 0; ks < 36; ks++) mma16816(sm[ks & 1], xa[4 * ks], xa[4 * ks + 1], xa[4 * ks + 2], xa[4 * ks + 3], 0x3f803f80u, 0x3f803f80u);
      bar_sync(NB_WG + wg, 128);
      release(0); s = 1;
      const float mean0 = (sm[0][0] + sm[1][0]) * (1.f / kD), mean1 = (sm[0][2] + sm[1][2]) * (1.f / kD);
      const float mb0 = rbf(mean0), mb1 = rbf(mean1);
      const uint32_t m0 = pack_bf16(mb0, mb0), m1 = pack_bf16(mb1, mb1);
      float q0[2][4] = {}, q1[2][4] = {};
#pragma unroll
      for (int ks = 0; ks < 36; ks++) {
#pragma unroll
        for (int i = 0; i < 4; i++) asm("sub.rn.bf16x2 %0, %0, %1;" : "+r"(xa[4 * ks + i]) : "r"((i & 1) ? m1 : m0));
        mma16816(q0[ks & 1], xa[4 * ks], xa[4 * ks + 1], xa[4 * ks + 2], xa[4 * ks + 3], xa[4 * ks], xa[4 * ks + 2]);
        mma16816(q1[ks & 1], xa[4 * ks], xa[4 * ks + 1], xa[4 * ks + 2], xa[4 * ks + 3], xa[4 * ks + 1], xa[4 * ks + 3]);
      }
      const int src = (lane & ~3) | (g >> 1);
      const float ss0 = __shfl_sync(0xffffffffu, (g & 1) ? q0[0][1] + q0[1][1] : q0[0][0] + q0[1][0], src);
      const float ss1 = __shfl_sync(0xffffffffu, (g & 1) ? q1[0][3] + q1[1][3] : q1[0][2] + q1[1][2], src);
      const float d0 = mean0 - mb0, d1 = mean1 - mb1;
      const float v0 = fmaxf(fmaf(-d0, d0, ss0 * (1.f / kD)), 0.f), v1 = fmaxf(fmaf(-d1, d1, ss1 * (1.f / kD)), 0.f);
      const float r0 = 1.f / rbf(sqrtf(rbf(rbf(v0) + 1e-5f))), r1 = 1.f / rbf(sqrtf(rbf(rbf(v1) + 1e-5f)));
      if (q == 0) {
        sts64f(sb + OFF_STAT + (wg * 64 + w4 * 16 + g) * 8, mb0, r0);
        sts64f(sb + OFF_STAT + (wg * 64 + w4 * 16 + g + 8) * 8, mb1, r1);
      }
      const float h0 = rbf(r0), h1 = rbf(r1);
      const uint32_t rh0 = pack_bf16(h0, h0), rh1 = pack_bf16(h1, h1), rl0 = pack_bf16(r0 - h0, r0 - h0), rl1 = pack_bf16(r1 - h1, r1 - h1);
#pragma unroll
      for (int i = 0; i < 144; i++) {
        uint32_t t;
        asm("mul.rn.bf16x2 %0, %1, %2;" : "=r"(t) : "r"(xa[i]), "r"((i & 1) ? rl1 : rl0));
        asm("fma.rn.bf16x2 %0, %0, %1, %2;" : "+r"(xa[i]) : "r"((i & 1) ? rh1 : rh0), "r"(t));
      }
    }
    STAMP(wg, 2);

    {
      float ab[36];
      uint32_t da = hw + H_DUMP + (w4 * 16 + g) * 288 + q * 8;
      for (int ri = 0; ri < 2; ri++) {
#pragma unroll
        for (int kb = 0; kb < 9; kb++) {
          stage_begin();
#pragma unroll
          for (int kk = 0; kk < 4; kk++) { const int i = (kb * 4 + kk) * 4; wgmma_n72_rs_tb0(ab, xa[i], xa[i + 1], xa[i + 2], xa[i + 3], desc((dlo + kk * 2) | DLO_K, DHI_SW128), (kb | kk) != 0); }
          stage_end(kb > 0);
        }
        wg_wait<0>();
        release(prev);
        keep(ab);
#pragma unroll
        for (int i = 0; i < 9; i++) {
          sts64f(da + i * 32, ab[4 * i], ab[4 * i + 1]);
          sts64f(da + i * 32 + 8 * 288, ab[4 * i + 2], ab[4 * i + 3]);
        }
        da += 18432;
      }
      bar_arrive(NB_DUMP, 352);
    }
    STAMP(wg, 3);

    float acc[64];
    {
      const uint32_t ha = hw + (threadIdx.x & 127) * 16;
      auto glu = [&](int i) {
        const float t0 = tanh_fast(0.5f * acc[2 * i]), t1 = tanh_fast(0.5f * acc[2 * i + 1]);
        const float u0 = 0.5f * acc[32 + 2 * i], u1 = 0.5f * acc[33 + 2 * i];
        return pack_bf16(fmaf(u0, t0, u0), fmaf(u1, t1, u1));
      };
      for (int c = 0;; c++) {
        if (SKEW > 0 && wg == 1) bar_sync(NB_SKEW, 256);
#pragma unroll
        for (int kb = 0; kb < 9; kb++) {
          stage_begin();
#pragma unroll
          for (int kk = 0; kk < 4; kk++) { const int i = (kb * 4 + kk) * 4; wgmma_n128_rs_tb1(acc, xa[i], xa[i + 1], xa[i + 2], xa[i + 3], desc((dlo + kk * 128) | DLO_MN, DHI_SW128), (kb | kk) != 0); }
          if (SKEW > 0 && kb == SKEW - 1 && wg == 0) bar_arrive(NB_SKEW, 256);
          if (kb == 8 && c == 3) mbar_wait(bars + 8 * B_SCAN, 0);
          stage_end(kb > 0);
        }
        wg_wait<0>();
        release(prev);
        keep(acc);
        if (c == 8) break;
#pragma unroll
        for (int i = 0; i < 4; i++) sts128(ha + c * 8192 + i * 2048, glu(4 * i), glu(4 * i + 1), glu(4 * i + 2), glu(4 * i + 3));
        STAMP(wg, 4 + c);
      }
#pragma unroll
      for (int i = 0; i < 32; i++)
        asm volatile("ld.shared.v4.b32 {%0,%1,%2,%3}, [%4];" : "=r"(xa[4 * i]), "=r"(xa[4 * i + 1]), "=r"(xa[4 * i + 2]), "=r"(xa[4 * i + 3]) : "r"(ha + i * 2048) : "memory");
#pragma unroll
      for (int i = 0; i < 16; i++) xa[128 + i] = glu(i);
      __syncwarp();
      if (elect()) mbar_arrive(bars + 8 * (B_HFREE + wg));
    }
    STAMP(wg, 13);

    const uint32_t dhs = ((hw + H_HS) & 0x3FFFF) >> 4;
    const int rp = (g >> 2) + 2 * (g & 3);
    const uint32_t stg = hw + H_STG + w4 * 2048 + rp * 128 + (q & 1) * 8, sx = ((q >> 1) ^ rp) << 4;
    auto reduce_out = [&](int nbox, int n0) {
      asm volatile("fence.proxy.async.shared::cta;" ::: "memory");
      bar_sync(NB_WG + wg, 128);
      if (w4 == 0) {
        if (elect()) {
          for (int b = 0; b < nbox; b++)
            asm volatile("cp.reduce.async.bulk.tensor.4d.global.shared::cta.add.tile.bulk_group [%0, {%1,%2,%2,%3}], [%4];" ::"l"(&prm.tOut), "r"(n0 + b * 32), "r"(0),
                         "r"(m * 16 + wg * 8), "r"(hw + H_STG + b * 8192) : "memory");
          asm volatile("cp.async.bulk.commit_group;" ::: "memory");
        }
        __syncwarp();
      }
    };
    auto staging_free = [&](bool first) {
      if (w4 == 0) {
        if (first) { mbar_wait(bars + 8 * B_INIT, 0); asm volatile("fence.proxy.async.global;" ::: "memory"); }
        asm volatile("cp.async.bulk.wait_group.read 0;" ::: "memory");
      }
      bar_sync(NB_WG + wg, 128);
    };
    for (int t = 0; t < 4; t++) {
      if (SKEW > 0 && wg == 1) bar_sync(NB_SKEW, 256);
#pragma unroll
      for (int kb = 0; kb < 9; kb++) {
        stage_begin();
#pragma unroll
        for (int kk = 0; kk < 4; kk++) { const int i = (kb * 4 + kk) * 4; wgmma_n128_rs_tb1(acc, xa[i], xa[i + 1], xa[i + 2], xa[i + 3], desc((dlo + kk * 128) | DLO_MN, DHI_SW128), (kb | kk) != 0); }
        if (SKEW > 0 && kb == SKEW - 1 && wg == 0) bar_arrive(NB_SKEW, 256);
        stage_end(kb > 0);
      }
      if (t == 0) mbar_wait(bars + 8 * (B_HSFULL + wg), 0);
#pragma unroll
      for (int ri = 0; ri < 2; ri++) {
        stage_begin();
#pragma unroll
        for (int kk = 0; kk < 4; kk++) wgmma_n128_ss_tb0(acc, desc((dhs + ri * 512 + kk * 2) | DLO_K, DHI_SW128), desc((dlo + kk * 2) | DLO_K, DHI_SW128), 1);
        stage_end(true);
      }
      stage_begin();
      wgmma_n128_ss_tb0(acc, desc((dhs + 1024) | ((1024 >> 4) << 16), DHI_NONE), desc(dlo | ((2048 >> 4) << 16), DHI_NONE), 1);
      stage_end(true);
      staging_free(t == 0);
      wg_wait<0>();
      release(prev);
      keep(acc);
#pragma unroll
      for (int i = 0; i < 16; i++) {
        const uint32_t a = stg + (i >> 2) * 8192 + (sx ^ ((i & 3) << 5));
        sts64f(a, acc[4 * i], acc[4 * i + 1]);
        sts64f(a + 1024, acc[4 * i + 2], acc[4 * i + 3]);
      }
      reduce_out(4, ((t + j) & 3) * 128);
      STAMP(wg, 14 + t);
    }
    {
      float a2[32];
      if (SKEW > 0 && wg == 1) bar_sync(NB_SKEW, 256);
#pragma unroll
      for (int kp = 0; kp < 5; kp++) {
        stage_begin();
#pragma unroll
        for (int kk = 0; kk < (kp < 4 ? 8 : 4); kk++) { const int i = (kp * 8 + kk) * 4; wgmma_n64_rs_tb1(a2, xa[i], xa[i + 1], xa[i + 2], xa[i + 3], desc((dlo + kk * 128) | DLO_MN, DHI_SW128), (kp | kk) != 0); }
        if (SKEW > 0 && kp == 1 && wg == 0) bar_arrive(NB_SKEW, 256);
        stage_end(kp > 0);
      }
      stage_begin();
#pragma unroll
      for (int kk = 0; kk < 8; kk++) wgmma_n64_ss_tb0(a2, desc((dhs + (kk >> 2) * 512 + (kk & 3) * 2) | DLO_K, DHI_SW128), desc((dlo + (kk >> 2) * 512 + (kk & 3) * 2) | DLO_K, DHI_SW128), 1);
      stage_end(true);
      stage_begin();
      wgmma_n64_ss_tb0(a2, desc((dhs + 1024) | ((1024 >> 4) << 16), DHI_NONE), desc(dlo | ((2048 >> 4) << 16), DHI_NONE), 1);
      stage_end(true);
      staging_free(false);
      wg_wait<0>();
      keep(a2);
#pragma unroll
      for (int i = 0; i < 8; i++) {
        const uint32_t a = stg + (i >> 2) * 8192 + (sx ^ ((i & 3) << 5));
        sts64f(a, a2[4 * i], a2[4 * i + 1]);
        sts64f(a + 1024, a2[4 * i + 2], a2[4 * i + 3]);
      }
      reduce_out(2, 512);
      STAMP(wg, 18);
      if (w4 == 0) asm volatile("cp.async.bulk.wait_group.read 0;" ::: "memory");
      STAMP(wg, 19);
    }
    if (MC) asm volatile("barrier.cluster.arrive.relaxed.aligned;\nbarrier.cluster.wait.aligned;" ::: "memory");
  }
}

typedef CUresult (*EncodeFn)(CUtensorMap*, CUtensorMapDataType, cuuint32_t, void*, const cuuint64_t*, const cuuint64_t*, const cuuint32_t*,
                             const cuuint32_t*, CUtensorMapInterleave, CUtensorMapSwizzle, CUtensorMapL2promotion, CUtensorMapFloatOOBfill);

void map2d(EncodeFn enc, CUtensorMap* tm, const void* p, uint64_t cols, uint64_t rows, uint32_t bc, uint32_t br, CUtensorMapSwizzle sw) {
  cuuint64_t gd[2] = {cols, rows}, gs[1] = {cols * 2};
  cuuint32_t bd[2] = {bc, br}, es[2] = {1, 1};
  enc(tm, CU_TENSOR_MAP_DATA_TYPE_BFLOAT16, 2, (void*)p, gd, gs, bd, es, CU_TENSOR_MAP_INTERLEAVE_NONE, sw,
      sw == CU_TENSOR_MAP_SWIZZLE_NONE ? CU_TENSOR_MAP_L2_PROMOTION_NONE : CU_TENSOR_MAP_L2_PROMOTION_L2_128B, CU_TENSOR_MAP_FLOAT_OOB_FILL_NONE);
}

}

extern "C" void kernel_launch(void* const* d_in, const int* in_sizes, int n_in, void* d_out, int out_size) {
  (void)in_sizes; (void)n_in; (void)out_size;
  static EncodeFn enc = nullptr;
  if (!enc) {
    cudaDriverEntryPointQueryResult qr;
    cudaGetDriverEntryPoint("cuTensorMapEncodeTiled", (void**)&enc, cudaEnableDefault, &qr);
    cudaFuncSetAttribute(fused_kernel<USE_MC != 0>, cudaFuncAttributeMaxDynamicSharedMemorySize, SMEM_BYTES);
  }
  Params prm;
  const CUtensorMapSwizzle S128 = CU_TENSOR_MAP_SWIZZLE_128B, S0 = CU_TENSOR_MAP_SWIZZLE_NONE;
  map2d(enc, &prm.tx, d_in[0], kD, kS, 64, 64, S128);
  map2d(enc, &prm.tBre, d_in[3], kD, 576, 64, 72, S128);
  map2d(enc, &prm.tBim, d_in[4], kD, 576, 64, 72, S128);
  map2d(enc, &prm.tCre, d_in[5], 576, kD, 64, 64, S128);
  map2d(enc, &prm.tCim, d_in[6], 576, kD, 64, 64, S128);
  map2d(enc, &prm.tCre8, d_in[5], 576, kD, 8, 64, S0);
  map2d(enc, &prm.tCim8, d_in[6], 576, kD, 8, 64, S0);
  map2d(enc, &prm.tWg, d_in[10], kF, kD, 64, 64, S128);
  map2d(enc, &prm.tWu, d_in[11], kF, kD, 64, 64, S128);
  map2d(enc, &prm.tWd, d_in[12], kD, kF, 64, 64, S128);
  {
    cuuint64_t gd[4] = {kD, 2, 4, kS / 8}, gs[3] = {4 * kD * 4, kD * 4, 8 * kD * 4};
    cuuint32_t bd[4] = {32, 2, 4, 8}, es[4] = {1, 1, 1, 1};
    enc(&prm.tOut, CU_TENSOR_MAP_DATA_TYPE_FLOAT32, 4, d_out, gd, gs, bd, es, CU_TENSOR_MAP_INTERLEAVE_NONE, S128, CU_TENSOR_MAP_L2_PROMOTION_NONE,
        CU_TENSOR_MAP_FLOAT_OOB_FILL_NONE);
  }
  prm.x = (const __nv_bfloat16*)d_in[0];
  prm.lre = (const __nv_bfloat16*)d_in[1];
  prm.lim = (const __nv_bfloat16*)d_in[2];
  prm.ldt = (const __nv_bfloat16*)d_in[7];
  prm.dskip = (const __nv_bfloat16*)d_in[8];
  prm.out = (float*)d_out;

  cudaLaunchConfig_t cfg = {};
  cfg.gridDim = dim3(128); cfg.blockDim = dim3(384); cfg.dynamicSmemBytes = SMEM_BYTES; cfg.stream = cudaStreamPerThread;
  cudaLaunchAttribute at[1];
  at[0].id = cudaLaunchAttributeClusterDimension;
  at[0].val.clusterDim.x = USE_MC ? 2 : 1; at[0].val.clusterDim.y = 1; at[0].val.clusterDim.z = 1;
  cfg.attrs = at; cfg.numAttrs = 1;
  cudaLaunchKernelEx(&cfg, fused_kernel<USE_MC != 0>, prm);
}
```

```cpp
#include <cuda_runtime.h>
#include <cuda.h>
#include <cuda_bf16.h>
#include <stdint.h>

namespace {

#define PACE 1
#define SKEW 3

constexpr int kS = 2048, kD = 576, kF = 4608;
constexpr int NST = 6;
constexpr uint32_t SLOT = 16384;
constexpr uint32_t OFF_H = NST * SLOT;
constexpr uint32_t OFF_DUMP = OFF_H + 65536 - 64 * 288;
constexpr uint32_t OFF_BAR = OFF_H + 131072;
constexpr uint32_t OFF_CONST = OFF_BAR + 384;
constexpr uint32_t SMEM_BYTES = OFF_CONST + 6 * 72 * 4;
static_assert(SMEM_BYTES <= 232448, "smem");
constexpr uint32_t H_STG = 0;
constexpr uint32_t H_RCV = 24576;
constexpr uint32_t H_HS = 40960;
constexpr uint32_t HS_BYTES = 18432;

enum { B_FULL = 0, B_EMPTY = NST, B_X = 2 * NST, B_SCAN = B_X + 8, B_HFREE, B_HSFULL = B_HFREE + 2, B_SFULL = B_HSFULL + 2,
       B_SFREE = B_SFULL + 2, B_RFULL = B_SFREE + 2, B_RFREE = B_RFULL + 2, B_COUNT = B_RFREE + 2 };
static_assert(B_COUNT * 8 <= 384, "barriers");
enum { NB_SKEW = 1, NB_WG = 2  , NB_SCAN = 4, NB_DUMP = 5 };

struct __align__(64) Params {
  CUtensorMap tx, tBre, tBim, tWg, tWu, tWd, tCre, tCim, tCre8, tCim8, tOut;
  const __nv_bfloat16 *x, *lre, *lim, *bre, *bim, *cre, *cim, *ldt, *dskip, *wg, *wu, *wd;
  float* out;
};

__device__ unsigned g_epoch[128];
__device__ unsigned g_initcnt[16];
__device__ uint2 g_S[2][16][576];
__device__ __align__(128) uint8_t g_hs[128][2 * HS_BYTES];
#define STAMP(role, i)

__device__ __forceinline__ void wgmma_n72_rs_tb0(float (&d)[36], uint32_t a0, uint32_t a1, uint32_t a2, uint32_t a3, uint64_t db, int scale_d) {
  asm volatile("{\n.reg .pred p;\nsetp.ne.b32 p, %41, 0;\n"
    "wgmma.mma_async.sync.aligned.m64n72k16.f32.bf16.bf16 {"
    "%0, %1, %2, %3, %4, %5, %6, %7, %8, %9, %10, %11, %12, %13, %14, %15, "
    "%16, %17, %18, %19, %20, %21, %22, %23, %24, %25, %26, %27, %28, %29, %30, %31, "
    "%32, %33, %34, %35"
    "}, {%36, %37, %38, %39}, %40, p, 1, 1, 0;\n}\n"
    : "+f"(d[0]), "+f"(d[1]), "+f"(d[2]), "+f"(d[3]), "+f"(d[4]), "+f"(d[5]), "+f"(d[6]), "+f"(d[7]),
      "+f"(d[8]), "+f"(d[9]), "+f"(d[10]), "+f"(d[11]), "+f"(d[12]), "+f"(d[13]), "+f"(d[14]), "+f"(d[15]),
      "+f"(d[16]), "+f"(d[17]), "+f"(d[18]), "+f"(d[19]), "+f"(d[20]), "+f"(d[21]), "+f"(d[22]), "+f"(d[23]),
      "+f"(d[24]), "+f"(d[25]), "+f"(d[26]), "+f"(d[27]), "+f"(d[28]), "+f"(d[29]), "+f"(d[30]), "+f"(d[31]),
      "+f"(d[32]), "+f"(d[33]), "+f"(d[34]), "+f"(d[35])
    : "r"(a0), "r"(a1), "r"(a2), "r"(a3), "l"(db), "r"(scale_d));
}
__device__ __forceinline__ void wgmma_n128_rs_tb1(float (&d)[64], uint32_t a0, uint32_t a1, uint32_t a2, uint32_t a3, uint64_t db, int scale_d) {
  asm volatile("{\n.reg .pred p;\nsetp.ne.b32 p, %69, 0;\n"
    "wgmma.mma_async.sync.aligned.m64n128k16.f32.bf16.bf16 {"
    "%0, %1, %2, %3, %4, %5, %6, %7, %8, %9, %10, %11, %12, %13, %14, %15, "
    "%16, %17, %18, %19, %20, %21, %22, %23, %24, %25, %26, %27, %28, %29, %30, %31, "
    "%32, %33, %34, %35, %36, %37, %38, %39, %40, %41, %42, %43, %44, %45, %46, %47, "
    "%48, %49, %50, %51, %52, %53, %54, %55, %56, %57, %58, %59, %60, %61, %62, %63"
    "}, {%64, %65, %66, %67}, %68, p, 1, 1, 1;\n}\n"
    : "+f"(d[0]), "+f"(d[1]), "+f"(d[2]), "+f"(d[3]), "+f"(d[4]), "+f"(d[5]), "+f"(d[6]), "+f"(d[7]),
      "+f"(d[8]), "+f"(d[9]), "+f"(d[10]), "+f"(d[11]), "+f"(d[12]), "+f"(d[13]), "+f"(d[14]), "+f"(d[15]),
      "+f"(d[16]), "+f"(d[17]), "+f"(d[18]), "+f"(d[19]), "+f"(d[20]), "+f"(d[21]), "+f"(d[22]), "+f"(d[23]),
      "+f"(d[24]), "+f"(d[25]), "+f"(d[26]), "+f"(d[27]), "+f"(d[28]), "+f"(d[29]), "+f"(d[30]), "+f"(d[31]),
      "+f"(d[32]), "+f"(d[33]), "+f"(d[34]), "+f"(d[35]), "+f"(d[36]), "+f"(d[37]), "+f"(d[38]), "+f"(d[39]),
      "+f"(d[40]), "+f"(d[41]), "+f"(d[42]), "+f"(d[43]), "+f"(d[44]), "+f"(d[45]), "+f"(d[46]), "+f"(d[47]),
      "+f"(d[48]), "+f"(d[49]), "+f"(d[50]), "+f"(d[51]), "+f"(d[52]), "+f"(d[53]), "+f"(d[54]), "+f"(d[55]),
      "+f"(d[56]), "+f"(d[57]), "+f"(d[58]), "+f"(d[59]), "+f"(d[60]), "+f"(d[61]), "+f"(d[62]), "+f"(d[63])
    : "r"(a0), "r"(a1), "r"(a2), "r"(a3), "l"(db), "r"(scale_d));
}
__device__ __forceinline__ void wgmma_n128_ss_tb0(float (&d)[64], uint64_t da, uint64_t db, int scale_d) {
  asm volatile("{\n.reg .pred p;\nsetp.ne.b32 p, %66, 0;\n"
    "wgmma.mma_async.sync.aligned.m64n128k16.f32.bf16.bf16 {"
    "%0, %1, %2, %3, %4, %5, %6, %7, %8, %9, %10, %11, %12, %13, %14, %15, "
    "%16, %17, %18, %19, %20, %21, %22, %23, %24, %25, %26, %27, %28, %29, %30, %31, "
    "%32, %33, %34, %35, %36, %37, %38, %39, %40, %41, %42, %43, %44, %45, %46, %47, "
    "%48, %49, %50, %51, %52, %53, %54, %55, %56, %57, %58, %59, %60, %61, %62, %63"
    "}, %64, %65, p, 1, 1, 0, 0;\n}\n"
    : "+f"(d[0]), "+f"(d[1]), "+f"(d[2]), "+f"(d[3]), "+f"(d[4]), "+f"(d[5]), "+f"(d[6]), "+f"(d[7]),
      "+f"(d[8]), "+f"(d[9]), "+f"(d[10]), "+f"(d[11]), "+f"(d[12]), "+f"(d[13]), "+f"(d[14]), "+f"(d[15]),
      "+f"(d[16]), "+f"(d[17]), "+f"(d[18]), "+f"(d[19]), "+f"(d[20]), "+f"(d[21]), "+f"(d[22]), "+f"(d[23]),
      "+f"(d[24]), "+f"(d[25]), "+f"(d[26]), "+f"(d[27]), "+f"(d[28]), "+f"(d[29]), "+f"(d[30]), "+f"(d[31]),
      "+f"(d[32]), "+f"(d[33]), "+f"(d[34]), "+f"(d[35]), "+f"(d[36]), "+f"(d[37]), "+f"(d[38]), "+f"(d[39]),
      "+f"(d[40]), "+f"(d[41]), "+f"(d[42]), "+f"(d[43]), "+f"(d[44]), "+f"(d[45]), "+f"(d[46]), "+f"(d[47]),
      "+f"(d[48]), "+f"(d[49]), "+f"(d[50]), "+f"(d[51]), "+f"(d[52]), "+f"(d[53]), "+f"(d[54]), "+f"(d[55]),
      "+f"(d[56]), "+f"(d[57]), "+f"(d[58]), "+f"(d[59]), "+f"(d[60]), "+f"(d[61]), "+f"(d[62]), "+f"(d[63])
    : "l"(da), "l"(db), "r"(scale_d));
}
__device__ __forceinline__ void wgmma_n64_rs_tb1(float (&d)[32], uint32_t a0, uint32_t a1, uint32_t a2, uint32_t a3, uint64_t db, int scale_d) {
  asm volatile("{\n.reg .pred p;\nsetp.ne.b32 p, %37, 0;\n"
    "wgmma.mma_async.sync.aligned.m64n64k16.f32.bf16.bf16 {"
    "%0, %1, %2, %3, %4, %5, %6, %7, %8, %9, %10, %11, %12, %13, %14, %15, "
    "%16, %17, %18, %19, %20, %21, %22, %23, %24, %25, %26, %27, %28, %29, %30, %31"
    "}, {%32, %33, %34, %35}, %36, p, 1, 1, 1;\n}\n"
    : "+f"(d[0]), "+f"(d[1]), "+f"(d[2]), "+f"(d[3]), "+f"(d[4]), "+f"(d[5]), "+f"(d[6]), "+f"(d[7]),
      "+f"(d[8]), "+f"(d[9]), "+f"(d[10]), "+f"(d[11]), "+f"(d[12]), "+f"(d[13]), "+f"(d[14]), "+f"(d[15]),
      "+f"(d[16]), "+f"(d[17]), "+f"(d[18]), "+f"(d[19]), "+f"(d[20]), "+f"(d[21]), "+f"(d[22]), "+f"(d[23]),
      "+f"(d[24]), "+f"(d[25]), "+f"(d[26]), "+f"(d[27]), "+f"(d[28]), "+f"(d[29]), "+f"(d[30]), "+f"(d[31])
    : "r"(a0), "r"(a1), "r"(a2), "r"(a3), "l"(db), "r"(scale_d));
}
__device__ __forceinline__ void wgmma_n64_ss_tb0(float (&d)[32], uint64_t da, uint64_t db, int scale_d) {
  asm volatile("{\n.reg .pred p;\nsetp.ne.b32 p, %34, 0;\n"
    "wgmma.mma_async.sync.aligned.m64n64k16.f32.bf16.bf16 {"
    "%0, %1, %2, %3, %4, %5, %6, %7, %8, %9, %10, %11, %12, %13, %14, %15, "
    "%16, %17, %18, %19, %20, %21, %22, %23, %24, %25, %26, %27, %28, %29, %30, %31"
    "}, %32, %33, p, 1, 1, 0, 0;\n}\n"
    : "+f"(d[0]), "+f"(d[1]), "+f"(d[2]), "+f"(d[3]), "+f"(d[4]), "+f"(d[5]), "+f"(d[6]), "+f"(d[7]),
      "+f"(d[8]), "+f"(d[9]), "+f"(d[10]), "+f"(d[11]), "+f"(d[12]), "+f"(d[13]), "+f"(d[14]), "+f"(d[15]),
      "+f"(d[16]), "+f"(d[17]), "+f"(d[18]), "+f"(d[19]), "+f"(d[20]), "+f"(d[21]), "+f"(d[22]), "+f"(d[23]),
      "+f"(d[24]), "+f"(d[25]), "+f"(d[26]), "+f"(d[27]), "+f"(d[28]), "+f"(d[29]), "+f"(d[30]), "+f"(d[31])
    : "l"(da), "l"(db), "r"(scale_d));
}

__device__ __forceinline__ bool elect() {
  uint32_t p;
  asm volatile("{.reg .pred q; elect.sync _|q, 0xffffffff; selp.u32 %0,1,0,q;}" : "=r"(p));
  return p;
}
__device__ __forceinline__ void mbar_init(uint32_t bar, uint32_t cnt) { asm volatile("mbarrier.init.shared::cta.b64 [%0], %1;" ::"r"(bar), "r"(cnt) : "memory"); }
__device__ __forceinline__ void mbar_expect(uint32_t bar, uint32_t bytes) { asm volatile("mbarrier.arrive.expect_tx.shared::cta.b64 _, [%0], %1;" ::"r"(bar), "r"(bytes) : "memory"); }
__device__ __forceinline__ void mbar_arrive(uint32_t bar) { asm volatile("mbarrier.arrive.shared::cta.b64 _, [%0];" ::"r"(bar) : "memory"); }
__device__ __forceinline__ void mbar_arrive_cta(uint32_t bar, uint32_t cta) {
  asm volatile("{.reg .b32 ra; mapa.shared::cluster.u32 ra, %0, %1; mbarrier.arrive.shared::cluster.b64 _, [ra];}" ::"r"(bar), "r"(cta) : "memory");
}
__device__ __forceinline__ void mbar_wait(uint32_t bar, uint32_t parity) {
  asm volatile(
      "{\n.reg .pred p;\n.reg .u32 c, t;\n"
      "mbarrier.try_wait.parity.shared::cta.b64 p, [%0], %1;\n@p bra DONE;\n"
      "mov.u32 c, %%clock;\n"
      "LAB_WAIT:\nmbarrier.try_wait.parity.shared::cta.b64 p, [%0], %1;\n@p bra DONE;\n"
      "mov.u32 t, %%clock;\nsub.u32 t, t, c;\nsetp.lt.u32 p, t, 0x40000000;\n@p bra LAB_WAIT;\ntrap;\nDONE:\n}" ::"r"(bar), "r"(parity) : "memory");
}
__device__ __forceinline__ void bar_sync(int id, int n) { asm volatile("bar.sync %0, %1;" ::"r"(id), "r"(n) : "memory"); }
__device__ __forceinline__ void bar_arrive(int id, int n) { asm volatile("bar.arrive %0, %1;" ::"r"(id), "r"(n) : "memory"); }
__device__ __forceinline__ void wg_fence() { asm volatile("wgmma.fence.sync.aligned;" ::: "memory"); }
__device__ __forceinline__ void wg_commit() { asm volatile("wgmma.commit_group.sync.aligned;" ::: "memory"); }
template <int N> __device__ __forceinline__ void wg_wait() { asm volatile("wgmma.wait_group.sync.aligned %0;" ::"n"(N) : "memory"); }
__device__ __forceinline__ void tma2d(uint32_t dst, const CUtensorMap* tm, uint32_t bar, int c0, int c1) {
  asm volatile("cp.async.bulk.tensor.2d.shared::cluster.global.mbarrier::complete_tx::bytes [%0], [%1,{%3,%4}], [%2];" ::"r"(dst), "l"(tm), "r"(bar), "r"(c0), "r"(c1) : "memory");
}
__device__ __forceinline__ void tma2d_mc(uint32_t dst, const CUtensorMap* tm, uint32_t bar, int c0, int c1) {
  asm volatile("cp.async.bulk.tensor.2d.shared::cluster.global.mbarrier::complete_tx::bytes.multicast::cluster [%0], [%1,{%3,%4}], [%2], %5;" ::"r"(dst), "l"(tm), "r"(bar), "r"(c0), "r"(c1), "h"((uint16_t)3) : "memory");
}
__device__ __forceinline__ void l2_prefetch(const void* p, uint32_t bytes) {
  asm volatile("cp.async.bulk.prefetch.L2.global [%0], %1;" ::"l"(p), "r"(bytes) : "memory");
}
__device__ __forceinline__ void tma_prefetch2d(const CUtensorMap* tm, int c0, int c1) {
  asm volatile("cp.async.bulk.prefetch.tensor.2d.L2.global.tile [%0,{%1,%2}];" ::"l"(tm), "r"(c0), "r"(c1) : "memory");
}
__device__ __forceinline__ uint64_t desc(uint32_t lo, uint32_t hi) { return ((uint64_t)hi << 32) | lo; }
constexpr uint32_t DHI_SW128 = (1024 >> 4) | (1u << 30);
constexpr uint32_t DHI_NONE = (128 >> 4);
constexpr uint32_t DLO_MN = (8192 >> 4) << 16;
constexpr uint32_t DLO_K = 1u << 16;
__device__ __forceinline__ float tanh_fast(float x) { float y; asm("tanh.approx.f32 %0, %1;" : "=f"(y) : "f"(x)); return y; }
__device__ __forceinline__ uint32_t pack_bf16(float lo, float hi) { uint32_t r; asm("cvt.rn.bf16x2.f32 %0, %1, %2;" : "=r"(r) : "f"(hi), "f"(lo)); return r; }
__device__ __forceinline__ float rbf(float x) { return __bfloat162float(__float2bfloat16_rn(x)); }
__device__ __forceinline__ void mma16816(float (&c)[4], uint32_t a0, uint32_t a1, uint32_t a2, uint32_t a3, uint32_t b0, uint32_t b1) {
  asm volatile("mma.sync.aligned.m16n8k16.row.col.f32.bf16.bf16.f32 {%0,%1,%2,%3}, {%4,%5,%6,%7}, {%8,%9}, {%0,%1,%2,%3};"
               : "+f"(c[0]), "+f"(c[1]), "+f"(c[2]), "+f"(c[3]) : "r"(a0), "r"(a1), "r"(a2), "r"(a3), "r"(b0), "r"(b1));
}
__device__ __forceinline__ void sts128(uint32_t a, uint32_t x, uint32_t y, uint32_t z, uint32_t w) {
  asm volatile("st.shared.v4.b32 [%0], {%1,%2,%3,%4};" ::"r"(a), "r"(x), "r"(y), "r"(z), "r"(w) : "memory");
}
__device__ __forceinline__ void sts64f(uint32_t a, float x, float y) { asm volatile("st.shared.v2.f32 [%0], {%1,%2};" ::"r"(a), "f"(x), "f"(y) : "memory"); }
__device__ __forceinline__ float2 lds64f(uint32_t a) { float2 v; asm volatile("ld.shared.v2.f32 {%0,%1}, [%2];" : "=f"(v.x), "=f"(v.y) : "r"(a) : "memory"); return v; }
__device__ __forceinline__ uint32_t lds32(uint32_t a) { uint32_t v; asm volatile("ld.shared.b32 %0, [%1];" : "=r"(v) : "r"(a) : "memory"); return v; }
__device__ __forceinline__ void lds128(uint32_t a, uint32_t& x, uint32_t& y, uint32_t& z, uint32_t& w) {
  asm volatile("ld.shared.v4.b32 {%0,%1,%2,%3}, [%4];" : "=r"(x), "=r"(y), "=r"(z), "=r"(w) : "r"(a) : "memory");
}
__device__ __forceinline__ float bflo(uint32_t v) { return __uint_as_float(v << 16); }
__device__ __forceinline__ float bfhi(uint32_t v) { return __uint_as_float(v & 0xffff0000u); }
__device__ __forceinline__ float lds32f(uint32_t a) { float v; asm volatile("ld.shared.f32 %0, [%1];" : "=f"(v) : "r"(a) : "memory"); return v; }
template <int N> __device__ __forceinline__ void keep(float (&a)[N]) {
#pragma unroll
  for (int i = 0; i < N; i++) asm volatile("" : "+f"(a[i])::"memory");
}

__global__ void __cluster_dims__(2, 1, 1) __launch_bounds__(384, 1) fused_kernel(const __grid_constant__ Params prm) {
  extern __shared__ __align__(1024) uint8_t smem[];
  const int warp = __shfl_sync(0xffffffffu, threadIdx.x >> 5, 0);
  const uint32_t sb = __shfl_sync(0xffffffffu, (uint32_t)__cvta_generic_to_shared(smem), 0);
  const int j = blockIdx.x & 7, m = blockIdx.x >> 3, rank = j & 1;
  const uint32_t bars = sb + OFF_BAR;
  STAMP(warp >> 2, 31);

  if (warp == 8) {
    if (elect()) {
      l2_prefetch(prm.x + (size_t)(m * 128 + j * 16) * kD, 16 * kD * 2);
      l2_prefetch(prm.bre + (size_t)blockIdx.x * 2592, 5184);
      l2_prefetch(prm.bim + (size_t)blockIdx.x * 2592, 5184);
      if (sb & 1023) __trap();
      for (int i = 0; i < B_COUNT; i++) {
        const bool four = (i >= B_HFREE && i < B_HFREE + 2) || (i >= B_SFULL && i < B_SFULL + 2);
        mbar_init(bars + 8 * i, four ? 4 : (i >= B_EMPTY && i < B_X) ? 2 : i == B_SCAN ? 3 : 1);
      }
      asm volatile("fence.mbarrier_init.release.cluster;" ::: "memory");
    }
    __syncwarp();
  } else if (warp == 9) {
    if (threadIdx.x < 288 + 11) asm volatile("prefetch.tensormap [%0];" ::"l"(&prm.tx + (threadIdx.x - 288)) : "memory");
    __syncwarp();
  }
  asm volatile("barrier.cluster.arrive.relaxed.aligned;\nbarrier.cluster.wait.aligned;" ::: "memory");

  if (warp >= 8) {
    if (warp == 8) {
      if (elect()) {
        mbar_expect(bars + 8 * B_FULL, 16384);
        tma2d_mc(sb + rank * 8192, &prm.tx, bars + 8 * B_FULL, 512, m * 128 + rank * 64);
        for (int i = 0; i < 8; i++) {
          const int w = i >> 2, kb = (i & 3) * 2 + rank;
          mbar_expect(bars + 8 * (B_X + i), 16384);
          tma2d_mc(sb + OFF_H + w * 65536 + kb * 8192, &prm.tx, bars + 8 * (B_X + i), kb * 64, m * 128 + w * 64);
        }
      }
      __syncwarp();
    }
    asm volatile("setmaxnreg.dec.sync.aligned.u32 24;");
    if (warp == 8) {
      int s = 1; uint32_t ph = 1;
      uint32_t dst, fb; bool e;
      auto acquire = [&](uint32_t bytes) {
        mbar_wait(bars + 8 * (B_EMPTY + s), ph);
        fb = bars + 8 * (B_FULL + s); dst = sb + s * SLOT;
        e = elect();
        if (e) mbar_expect(fb, bytes);
        if (++s == NST) { s = 0; ph ^= 1; }
      };
      auto box = [&](const CUtensorMap* t, uint32_t o, int a, int b) { if (e) tma2d(dst + o, t, fb, a, b); };
      for (int kb = 0; kb < 9; kb++) { acquire(9216); box(&prm.tBre, 0, kb * 64, j * 72); }
      for (int kb = 0; kb < 9; kb++) { acquire(9216); box(&prm.tBim, 0, kb * 64, j * 72); }
      for (int c = 0; c < 9; c++) {
        const int col = j * 576 + c * 64;
        for (int kb = 0; kb < 9; kb++) { acquire(16384); box(&prm.tWg, 0, col, kb * 64); box(&prm.tWu, 8192, col, kb * 64); }
      }
      for (int t = 0; t < 4; t++) {
        const int n0 = ((rank ^ t ^ 1) & 1) * 256 + (((t >> 1) ^ (j >> 1)) & 1) * 128;
        for (int kb = 0; kb < 9; kb++) { acquire(16384); box(&prm.tWd, 0, n0, j * 576 + kb * 64); box(&prm.tWd, 8192, n0 + 64, j * 576 + kb * 64); }
        acquire(16384); box(&prm.tCre, 0, j * 72, n0); box(&prm.tCre, 8192, j * 72, n0 + 64);
        acquire(16384); box(&prm.tCim, 0, j * 72, n0); box(&prm.tCim, 8192, j * 72, n0 + 64);
        acquire(4096);
        box(&prm.tCre8, 0, j * 72 + 64, n0); box(&prm.tCre8, 1024, j * 72 + 64, n0 + 64);
        box(&prm.tCim8, 2048, j * 72 + 64, n0); box(&prm.tCim8, 3072, j * 72 + 64, n0 + 64);
      }
      for (int kp = 0; kp < 4; kp++) { acquire(16384); box(&prm.tWd, 0, 512, j * 576 + kp * 128); box(&prm.tWd, 8192, 512, j * 576 + kp * 128 + 64); }
      acquire(8192 + 2048); box(&prm.tWd, 0, 512, j * 576 + 512); box(&prm.tCre8, 8192, j * 72 + 64, 512); box(&prm.tCim8, 8192 + 1024, j * 72 + 64, 512);
      acquire(16384); box(&prm.tCre, 0, j * 72, 512); box(&prm.tCim, 8192, j * 72, 512);
    } else {
      const int p = threadIdx.x - 288;
      const unsigned epoch = *(volatile unsigned*)&g_epoch[blockIdx.x];
      if (warp == 9) {
        mbar_wait(bars + 8 * (B_X + 7), 0);
        if (elect()) {
          const size_t o = (size_t)blockIdx.x * 20736;
          for (int i = 0; i < 3; i++) { l2_prefetch(prm.wg + o + i * 6912, 13824); l2_prefetch(prm.wu + o + i * 6912, 13824); }
          for (int i = 0; i < 3; i++) l2_prefetch(prm.wd + o + i * 6912, 13824);
          l2_prefetch(prm.cre + (size_t)blockIdx.x * 2592, 5184);
          l2_prefetch(prm.cim + (size_t)blockIdx.x * 2592, 5184);
        }
        __syncwarp();
      }
      bar_sync(NB_DUMP, 352);
      if (p == 95) {
        __threadfence();
        asm volatile("red.release.gpu.global.add.u32 [%0], 1;" ::"l"(&g_initcnt[m]) : "memory");
        g_epoch[blockIdx.x] = epoch + 1u;
      }
      if (p < 72) {
        const float ar = lds32f(sb + OFF_CONST + p * 4), ai = lds32f(sb + OFF_CONST + 288 + p * 4);
        float hr = 0.f, hi = 0.f;
        uint32_t a0 = sb + OFF_DUMP + p * 4;
        asm volatile("" : "+r"(a0));
        auto step = [&](uint32_t v) {
          const float nr = fmaf(ar, hr, fmaf(-ai, hi, bflo(v)));
          hi = fmaf(ar, hi, fmaf(ai, hr, bfhi(v))); hr = nr;
        };
        if (m < 15) {
          uint32_t u[4], v[4], a = a0;
#pragma unroll
          for (int k = 0; k < 4; k++) u[k] = lds32(a + k * 288);
#pragma unroll 1
          for (; a != a0 + 128 * 288; a += 8 * 288) {
#pragma unroll
            for (int k = 0; k < 4; k++) v[k] = lds32(a + (4 + k) * 288);
#pragma unroll
            for (int k = 0; k < 4; k++) step(u[k]);
#pragma unroll
            for (int k = 0; k < 4; k++) u[k] = lds32(a + (8 + k) * 288);
#pragma unroll
            for (int k = 0; k < 4; k++) step(v[k]);
          }
          asm volatile("st.relaxed.gpu.global.v2.b32 [%0], {%1,%2};" ::"l"(&g_S[epoch & 1][m][j * 72 + p]), "r"(~__float_as_uint(hr)), "r"(~__float_as_uint(hi)) : "memory");
          g_S[(epoch & 1) ^ 1][m][j * 72 + p] = make_uint2(0u, 0u);
        }
        STAMP(2, 4);
        {
          const float br = lds32f(sb + OFF_CONST + 576 + p * 4), bi = lds32f(sb + OFF_CONST + 864 + p * 4);
          hr = 0.f; hi = 0.f;
          const uint2* sp = &g_S[epoch & 1][0][j * 72 + p];
#pragma unroll 1
          for (int left = m; left > 0; left -= 4, sp += 4 * 576) {
            uint32_t v[4][2];
            int spins = 0;
            uint32_t ok;
            do {
#pragma unroll
              for (int k = 0; k < 4; k++) {
                v[k][0] = v[k][1] = 0xffffffffu;
                if (k < left) asm volatile("ld.relaxed.gpu.global.v2.b32 {%0,%1}, [%2];" : "=r"(v[k][0]), "=r"(v[k][1]) : "l"(sp + k * 576) : "memory");
              }
              ok = min(min(min(v[0][0], v[0][1]), min(v[1][0], v[1][1])), min(min(v[2][0], v[2][1]), min(v[3][0], v[3][1])));
              if (++spins > (1 << 22)) __trap();
            } while (ok == 0u);
#pragma unroll
            for (int k = 0; k < 4; k++)
              if (k < left) { const float nr = fmaf(br, hr, fmaf(-bi, hi, __uint_as_float(~v[k][0]))); hi = fmaf(br, hi, fmaf(bi, hr, __uint_as_float(~v[k][1]))); hr = nr; }
          }
        }
        STAMP(2, 5);
        const float cr = lds32f(sb + OFF_CONST + 1152 + p * 4), ci = lds32f(sb + OFF_CONST + 1440 + p * 4);
        auto emit = [&](uint32_t v, uint32_t a) {
          step(v);
          asm volatile("st.shared.b32 [%0], %1;" ::"r"(a), "r"(pack_bf16(fmaf(cr, hr, -ci * hi), fmaf(-cr, hi, -ci * hr))) : "memory");
        };
        uint32_t u[3], v[3], a = a0;
#pragma unroll
        for (int k = 0; k < 3; k++) u[k] = lds32(a + k * 288);
#pragma unroll 1
        for (; a != a0 + 126 * 288; a += 6 * 288) {
#pragma unroll
          for (int k = 0; k < 3; k++) v[k] = lds32(a + (3 + k) * 288);
#pragma unroll
          for (int k = 0; k < 3; k++) emit(u[k], a + k * 288);
#pragma unroll
          for (int k = 0; k < 3; k++) u[k] = lds32(a + (6 + k) * 288);
#pragma unroll
          for (int k = 0; k < 3; k++) emit(v[k], a + (3 + k) * 288);
        }
        emit(u[0], a); emit(u[1], a + 288);
      }
      __syncwarp();
      STAMP(2, 6);
      bar_sync(NB_SCAN, 96);
      {
        int t = p / 9, c = p - t * 9;
        uint8_t* const gp = &g_hs[blockIdx.x][0];
#pragma unroll 1
        for (int it = 0; it < 12; it++) {
          const uint32_t tt = t & 63, a = sb + OFF_DUMP + t * 288 + c * 32;
          uint32_t w[8];
          lds128(a, w[0], w[1], w[2], w[3]);
          lds128(a + 16, w[4], w[5], w[6], w[7]);
          uint8_t* o = gp + ((t >> 6) * HS_BYTES + (c < 8 ? tt * 128 + ((c ^ (tt & 7)) << 4) : 16384 + tt * 16));
          *(uint4*)o = make_uint4(__byte_perm(w[0], w[1], 0x5410), __byte_perm(w[2], w[3], 0x5410), __byte_perm(w[4], w[5], 0x5410), __byte_perm(w[6], w[7], 0x5410));
          *(uint4*)(o + (c < 8 ? 8192 : 1024)) = make_uint4(__byte_perm(w[0], w[1], 0x7632), __byte_perm(w[2], w[3], 0x7632), __byte_perm(w[4], w[5], 0x7632), __byte_perm(w[6], w[7], 0x7632));
          t += 10; c += 6;
          if (c >= 9) { c -= 9; t++; }
        }
      }
      __syncwarp();
      if (elect()) mbar_arrive(bars + 8 * B_SCAN);
      STAMP(2, 2);
      __threadfence();
      asm volatile("fence.proxy.async.global;" ::: "memory");
      bar_sync(NB_SCAN, 96);
      STAMP(2, 3);
      if (warp == 9) {
        for (int w = 0; w < 2; w++) {
          mbar_wait(bars + 8 * (B_HFREE + w), 0);
          if (elect()) {
            mbar_arrive_cta(bars + 8 * (B_RFREE + w), rank ^ 1);
            mbar_expect(bars + 8 * (B_HSFULL + w), HS_BYTES);
            asm volatile("cp.async.bulk.shared::cluster.global.mbarrier::complete_tx::bytes [%0], [%1], %2, [%3];" ::"r"(sb + OFF_H + w * 65536 + H_HS),
                         "l"(&g_hs[blockIdx.x][w * HS_BYTES]), "r"(HS_BYTES), "r"(bars + 8 * (B_HSFULL + w)) : "memory");
          }
          __syncwarp();
        }
      } else {
        const int w = warp - 10;
        const uint32_t hw = sb + OFF_H + w * 65536;
        {
          const unsigned target = 8u * (epoch + 1u);
          int spins = 0;
          unsigned v;
          do {
            asm volatile("ld.acquire.gpu.global.u32 %0, [%1];" : "=r"(v) : "l"(&g_initcnt[m]) : "memory");
            if (++spins > (1 << 22)) __trap();
          } while ((int)(v - target) < 0);
          asm volatile("fence.proxy.async.global;" ::: "memory");
        }
#pragma unroll 1
        for (int t = 0; t < 5; t++) {
          if (t == 0 || t == 2) {
            if (elect()) mbar_expect(bars + 8 * (B_RFULL + w), 16384);
            mbar_wait(bars + 8 * (B_SFULL + w), 0);
            mbar_wait(bars + 8 * (B_RFREE + w), t >> 1);
            if (elect())
              asm volatile("{.reg .b32 ra, rb; mapa.shared::cluster.u32 ra, %0, %3; mapa.shared::cluster.u32 rb, %2, %3;\n"
                           "cp.async.bulk.shared::cluster.shared::cta.mbarrier::complete_tx::bytes [ra], [%1], 16384, [rb];}" ::"r"(hw + H_RCV),
                           "r"(hw + H_STG), "r"(bars + 8 * (B_RFULL + w)), "r"(rank ^ 1) : "memory");
            mbar_wait(bars + 8 * (B_RFULL + w), t >> 1);
            if (elect()) mbar_arrive_cta(bars + 8 * (B_SFREE + w), rank ^ 1);
          } else {
            mbar_wait(bars + 8 * (B_SFULL + w), t & 1);
            const int n0 = t < 4 ? rank * 256 + (((t >> 1) ^ (j >> 1)) & 1) * 128 : 512;
            if (elect()) {
#pragma unroll 1
              for (int b = 0; b < (t < 4 ? 4 : 2); b++) {
                asm volatile("cp.reduce.async.bulk.tensor.4d.global.shared::cta.add.tile.bulk_group [%0, {%1,%2,%2,%3}], [%4];" ::"l"(&prm.tOut), "r"(n0 + b * 32), "r"(0),
                             "r"(m * 16 + w * 8), "r"(hw + H_STG + b * 8192) : "memory");
                asm volatile("cp.async.bulk.commit_group;" ::: "memory");
                if (PACE && t < 4) { asm volatile("cp.async.bulk.wait_group.read 0;" ::: "memory"); if (PACE > 1) __nanosleep(PACE); }
              }
              asm volatile("cp.async.bulk.wait_group.read 0;" ::: "memory");
              mbar_arrive(bars + 8 * (B_SFREE + w));
              if (t == 1) mbar_arrive_cta(bars + 8 * (B_RFREE + w), rank ^ 1);
            }
          }
          __syncwarp();
        }
      }
    }
  } else {
    asm volatile("setmaxnreg.inc.sync.aligned.u32 240;");
    const int wg = warp >> 2, w4 = warp & 3;
    const int lane = threadIdx.x & 31, g = lane >> 2, q = lane & 3;
    const uint32_t hw = sb + OFF_H + wg * 65536;
    STAMP(wg, 0);
    if (wg == 1 && threadIdx.x < 128 + 72) {
      const int p = threadIdx.x - 128, pg = j * 72 + p;
      const float lr = __bfloat162float(prm.lre[pg]), li = __bfloat162float(prm.lim[pg]);
      const float dt = rbf(expf(__bfloat162float(prm.ldt[pg])));
      const float ea = expf(dt * lr);
      float sn, cs;
      sincosf(dt * li, &sn, &cs);
      const float ar = ea * cs, ai = ea * sn;
      float br = ar, bi = ai;
#pragma unroll
      for (int k = 0; k < 7; k++) { const float t = br * br - bi * bi; bi = 2.f * br * bi; br = t; }
      const float nr = ar - 1.f, den = 2.f / (lr * lr + li * li);
      float* cp = (float*)(smem + OFF_CONST) + p;
      cp[0] = ar; cp[72] = ai; cp[144] = br; cp[216] = bi;
      cp[288] = (nr * lr + ai * li) * den; cp[360] = (ai * lr - nr * li) * den;
    }
    __syncwarp();

    int s = 0; uint32_t ph = 0;
    auto release = [&](int st) { if (w4 == 0) { if (elect()) mbar_arrive(bars + 8 * (B_EMPTY + st)); } };
    const uint32_t dring = (sb & 0x3FFFF) >> 4;
    uint32_t dlo; int prev = 0;
    auto stage_begin = [&]() { mbar_wait(bars + 8 * (B_FULL + s), ph); dlo = dring + s * (SLOT >> 4); wg_fence(); };
    auto advance = [&]() { if (++s == NST) { s = 0; ph ^= 1; } };
    auto stage_end = [&](bool rel) {
      wg_commit();
      if (rel) { wg_wait<1>(); release(prev); }
      prev = s;
      advance();
    };

    uint32_t xa[144];
    uint32_t xr[18], dk[9];
    float mean[2], rstd[2];
#pragma unroll
    for (int i = 0; i < 9; i++) dk[i] = __ldg((const uint32_t*)(prm.dskip + j * 72 + i * 8 + q * 2));
    {
      const int r = w4 * 16 + (lane & 7) + ((lane >> 3) & 1) * 8;
      const uint32_t ro = r * 128, cx = ((lane >> 4) ^ (lane & 7)) << 4;
      float s1[2][4] = {}, s2[2][4] = {};
      auto box = [&](int kb, uint32_t base) {
#pragma unroll
        for (int kk = 0; kk < 4; kk++) {
          const int i = (kb * 4 + kk) * 4;
          asm volatile("ldmatrix.sync.aligned.m8n8.x4.shared.b16 {%0,%1,%2,%3}, [%4];"
                       : "=r"(xa[i]), "=r"(xa[i + 1]), "=r"(xa[i + 2]), "=r"(xa[i + 3]) : "r"(base + ro + (cx ^ (kk << 5))) : "memory");
        }
#pragma unroll
        for (int kk = 0; kk < 4; kk++) {
          const int i = (kb * 4 + kk) * 4;
          uint32_t sq[4];
#pragma unroll
          for (int e = 0; e < 4; e++) asm("mul.rn.bf16x2 %0, %1, %1;" : "=r"(sq[e]) : "r"(xa[i + e]));
          mma16816(s1[kk & 1], xa[i], xa[i + 1], xa[i + 2], xa[i + 3], 0x3f803f80u, 0x3f803f80u);
          mma16816(s2[kk & 1], sq[0], sq[1], sq[2], sq[3], 0x3f803f80u, 0x3f803f80u);
        }
      };
      mbar_wait(bars + 8 * B_FULL, 0);
      box(8, sb + wg * 8192);
#pragma unroll
      for (int kp = 0; kp < 4; kp++) {
        mbar_wait(bars + 8 * (B_X + wg * 4 + kp), 0);
        box(2 * kp, hw + 2 * kp * 8192);
        box(2 * kp + 1, hw + (2 * kp + 1) * 8192);
      }
      STAMP(wg, 1);
#pragma unroll
      for (int i = 0; i < 9; i++) {
        const int c8 = j * 9 + i, kb = c8 >> 3;
        const uint32_t a = (kb < 8 ? hw + kb * 8192 : sb + wg * 8192) + (w4 * 16 + g) * 128 + (((c8 & 7) ^ g) << 4) + q * 4;
        xr[2 * i] = lds32(a); xr[2 * i + 1] = lds32(a + 1024);
      }
      uint32_t rh[2], rl[2], cc[2];
#pragma unroll
      for (int e = 0; e < 2; e++) {
        const float mu = (s1[0][2 * e] + s1[1][2 * e]) * (1.f / kD);
        const float var = fmaxf(fmaf(-mu, mu, (s2[0][2 * e] + s2[1][2 * e]) * (1.f / kD)), 0.f);
        float sd, r;
        asm("sqrt.approx.f32 %0, %1;" : "=f"(sd) : "f"(rbf(rbf(var) + 1e-5f)));
        asm("rcp.approx.ftz.f32 %0, %1;" : "=f"(r) : "f"(rbf(sd)));
        mean[e] = mu; rstd[e] = r;
        const float h = rbf(r);
        rh[e] = pack_bf16(h, h); rl[e] = pack_bf16(r - h, r - h); cc[e] = pack_bf16(-mu * r, -mu * r);
      }
#pragma unroll
      for (int i = 0; i < 144; i++) {
        uint32_t t;
        asm("fma.rn.bf16x2 %0, %1, %2, %3;" : "=r"(t) : "r"(xa[i]), "r"(rl[i & 1]), "r"(cc[i & 1]));
        asm("fma.rn.bf16x2 %0, %0, %1, %2;" : "+r"(xa[i]) : "r"(rh[i & 1]), "r"(t));
      }
      bar_sync(NB_WG + wg, 128);
      release(0); s = 1;
    }
    STAMP(wg, 2);

    {
      float ab[36];
      uint32_t rp[18];
      float* op = prm.out + (size_t)(m * 128 + wg * 64 + w4 * 16 + g) * kD + j * 72 + q * 2;
#pragma unroll
      for (int kb = 0; kb < 9; kb++) {
        stage_begin();
#pragma unroll
        for (int kk = 0; kk < 4; kk++) { const int i = (kb * 4 + kk) * 4; wgmma_n72_rs_tb0(ab, xa[i], xa[i + 1], xa[i + 2], xa[i + 3], desc((dlo + kk * 2) | DLO_K, DHI_SW128), (kb | kk) != 0); }
        stage_end(kb > 0);
#pragma unroll
        for (int e = 0; e < 2; e++) {
          const float x0 = bflo(xr[2 * kb + e]), x1 = bfhi(xr[2 * kb + e]);
          const uint32_t xn = pack_bf16((x0 - mean[e]) * rstd[e], (x1 - mean[e]) * rstd[e]);
          uint32_t t;
          asm("mul.rn.bf16x2 %0, %1, %2;" : "=r"(t) : "r"(xn), "r"(dk[kb]));
          *(float2*)(op + e * 8 * kD + kb * 8) = make_float2(x0 + bflo(t), x1 + bfhi(t));
        }
      }
      wg_wait<0>();
      release(prev);
      keep(ab);
#pragma unroll
      for (int i = 0; i < 18; i++) rp[i] = pack_bf16(ab[2 * i], ab[2 * i + 1]);
#pragma unroll
      for (int kb = 0; kb < 9; kb++) {
        stage_begin();
#pragma unroll
        for (int kk = 0; kk < 4; kk++) { const int i = (kb * 4 + kk) * 4; wgmma_n72_rs_tb0(ab, xa[i], xa[i + 1], xa[i + 2], xa[i + 3], desc((dlo + kk * 2) | DLO_K, DHI_SW128), (kb | kk) != 0); }
        stage_end(kb > 0);
      }
      wg_wait<0>();
      release(prev);
      keep(ab);
      const uint32_t da = sb + OFF_DUMP + (wg * 64 + w4 * 16 + g) * 288 + q * 8;
#pragma unroll
      for (int i = 0; i < 18; i++) {
        const uint32_t ip = pack_bf16(ab[2 * i], ab[2 * i + 1]);
        asm volatile("st.shared.v2.b32 [%0], {%1,%2};" ::"r"(da + (i >> 1) * 32 + (i & 1) * 8 * 288), "r"(__byte_perm(rp[i], ip, 0x5410)), "r"(__byte_perm(rp[i], ip, 0x7632)) : "memory");
      }
      bar_arrive(NB_DUMP, 352);
    }
    STAMP(wg, 3);

    float acc[64];
    {
      const uint32_t ha = hw + (threadIdx.x & 127) * 16 + wg * 7 * 8192;
      const int hstep = wg ? -8192 : 8192;
      auto glu = [&](int i) {
        const float t0 = tanh_fast(0.5f * acc[2 * i]), t1 = tanh_fast(0.5f * acc[2 * i + 1]);
        const float u0 = 0.5f * acc[32 + 2 * i], u1 = 0.5f * acc[33 + 2 * i];
        return pack_bf16(fmaf(u0, t0, u0), fmaf(u1, t1, u1));
      };
      for (int c = 0;; c++) {
        if (SKEW > 0 && wg == 1) bar_sync(NB_SKEW, 256);
#pragma unroll
        for (int kb = 0; kb < 9; kb++) {
          stage_begin();
#pragma unroll
          for (int kk = 0; kk < 4; kk++) { const int i = (kb * 4 + kk) * 4; wgmma_n128_rs_tb1(acc, xa[i], xa[i + 1], xa[i + 2], xa[i + 3], desc((dlo + kk * 128) | DLO_MN, DHI_SW128), (kb | kk) != 0); }
          if (SKEW > 0 && kb == SKEW - 1 && wg == 0) bar_arrive(NB_SKEW, 256);
          if (kb == 8 && c == 5) mbar_wait(bars + 8 * B_SCAN, 0);
          stage_end(kb > 0);
        }
        wg_wait<0>();
        release(prev);
        keep(acc);
        if (c == 8) break;
#pragma unroll
        for (int i = 0; i < 4; i++) sts128(ha + c * hstep + i * 2048, glu(4 * i), glu(4 * i + 1), glu(4 * i + 2), glu(4 * i + 3));
        STAMP(wg, 4 + c);
      }
#pragma unroll
      for (int i = 0; i < 32; i++) lds128(ha + (i >> 2) * hstep + (i & 3) * 2048, xa[4 * i], xa[4 * i + 1], xa[4 * i + 2], xa[4 * i + 3]);
#pragma unroll
      for (int i = 0; i < 16; i++) xa[128 + i] = glu(i);
      __syncwarp();
      if (elect()) mbar_arrive(bars + 8 * (B_HFREE + wg));
    }
    STAMP(wg, 13);

    const uint32_t dhs = ((hw + H_HS) & 0x3FFFF) >> 4;
    const int rp = (g >> 2) + 2 * (g & 3);
    const uint32_t stg = hw + H_STG + w4 * 2048 + rp * 128 + (q & 1) * 8, sx = ((q >> 1) ^ rp) << 4;
    const uint32_t lin = hw + w4 * 2048 + lane * 16;
    auto staged = [&]() {
      asm volatile("fence.proxy.async.shared::cta;" ::: "memory");
      __syncwarp();
      if (elect()) mbar_arrive(bars + 8 * (B_SFULL + wg));
    };
    for (int t = 0; t < 4; t++) {
      if (SKEW > 0 && wg == 1) bar_sync(NB_SKEW, 256);
#pragma unroll
      for (int kb = 0; kb < 9; kb++) {
        stage_begin();
#pragma unroll
        for (int kk = 0; kk < 4; kk++) { const int i = (kb * 4 + kk) * 4; wgmma_n128_rs_tb1(acc, xa[i], xa[i + 1], xa[i + 2], xa[i + 3], desc((dlo + kk * 128) | DLO_MN, DHI_SW128), (kb | kk) != 0); }
        if (SKEW > 0 && kb == SKEW - 1 && wg == 0) bar_arrive(NB_SKEW, 256);
        stage_end(kb > 0);
        if (kb == 0 && t > 0) staged();
      }
      if (t == 0) mbar_wait(bars + 8 * (B_HSFULL + wg), 0);
      stage_begin();
#pragma unroll
      for (int kk = 0; kk < 4; kk++) wgmma_n128_ss_tb0(acc, desc((dhs + kk * 2) | DLO_K, DHI_SW128), desc((dlo + kk * 2) | DLO_K, DHI_SW128), 1);
      stage_end(true);
      stage_begin();
#pragma unroll
      for (int kk = 0; kk < 4; kk++) wgmma_n128_ss_tb0(acc, desc((dhs + 512 + kk * 2) | DLO_K, DHI_SW128), desc((dlo + kk * 2) | DLO_K, DHI_SW128), 1);
      const int s_im = s;
      advance();
      stage_begin();
      wgmma_n128_ss_tb0(acc, desc((dhs + 1024) | ((1024 >> 4) << 16), DHI_NONE), desc(dlo | ((2048 >> 4) << 16), DHI_NONE), 1);
      stage_end(true);
      if (t > 0) mbar_wait(bars + 8 * (B_SFREE + wg), (t - 1) & 1);
      if (t & 1) mbar_wait(bars + 8 * (B_RFULL + wg), t >> 1);
      wg_wait<0>();
      release(s_im); release(prev);
      keep(acc);
      if (t & 1) {
#pragma unroll
        for (int i = 0; i < 8; i++) {
          uint32_t v[4];
          lds128(lin + H_RCV + (i >> 2) * 8192 + (i & 3) * 512, v[0], v[1], v[2], v[3]);
#pragma unroll
          for (int e = 0; e < 4; e++) { acc[8 * i + 2 * e] += bflo(v[e]); acc[8 * i + 2 * e + 1] += bfhi(v[e]); }
        }
        __syncwarp();
#pragma unroll
        for (int i = 0; i < 16; i++) {
          const uint32_t a = stg + (i >> 2) * 8192 + (sx ^ ((i & 3) << 5));
          sts64f(a, acc[4 * i], acc[4 * i + 1]);
          sts64f(a + 1024, acc[4 * i + 2], acc[4 * i + 3]);
        }
      } else {
#pragma unroll
        for (int i = 0; i < 8; i++)
          sts128(lin + H_STG + (i >> 2) * 8192 + (i & 3) * 512, pack_bf16(acc[8 * i], acc[8 * i + 1]), pack_bf16(acc[8 * i + 2], acc[8 * i + 3]),
                 pack_bf16(acc[8 * i + 4], acc[8 * i + 5]), pack_bf16(acc[8 * i + 6], acc[8 * i + 7]));
      }
      STAMP(wg, 14 + t);
    }
    {
      float a2[32];
      if (SKEW > 0 && wg == 1) bar_sync(NB_SKEW, 256);
#pragma unroll
      for (int kp = 0; kp < 5; kp++) {
        stage_begin();
#pragma unroll
        for (int kk = 0; kk < (kp < 4 ? 8 : 4); kk++) { const int i = (kp * 8 + kk) * 4; wgmma_n64_rs_tb1(a2, xa[i], xa[i + 1], xa[i + 2], xa[i + 3], desc((dlo + kk * 128) | DLO_MN, DHI_SW128), (kp | kk) != 0); }
        if (kp == 4) wgmma_n64_ss_tb0(a2, desc((dhs + 1024) | ((1024 >> 4) << 16), DHI_NONE), desc((dlo + 512) | ((1024 >> 4) << 16), DHI_NONE), 1);
        if (SKEW > 0 && kp == 1 && wg == 0) bar_arrive(NB_SKEW, 256);
        stage_end(kp > 0);
        if (kp == 0) staged();
      }
      stage_begin();
#pragma unroll
      for (int kk = 0; kk < 8; kk++) wgmma_n64_ss_tb0(a2, desc((dhs + (kk >> 2) * 512 + (kk & 3) * 2) | DLO_K, DHI_SW128), desc((dlo + (kk >> 2) * 512 + (kk & 3) * 2) | DLO_K, DHI_SW128), 1);
      wg_commit();
      mbar_wait(bars + 8 * (B_SFREE + wg), 1);
      wg_wait<0>();
      keep(a2);
#pragma unroll
      for (int i = 0; i < 8; i++) {
        const uint32_t a = stg + (i >> 2) * 8192 + (sx ^ ((i & 3) << 5));
        sts64f(a, a2[4 * i], a2[4 * i + 1]);
        sts64f(a + 1024, a2[4 * i + 2], a2[4 * i + 3]);
      }
      staged();
      STAMP(wg, 18);
    }
  }
}

typedef CUresult (*EncodeFn)(CUtensorMap*, CUtensorMapDataType, cuuint32_t, void*, const cuuint64_t*, const cuuint64_t*, const cuuint32_t*,
                             const cuuint32_t*, CUtensorMapInterleave, CUtensorMapSwizzle, CUtensorMapL2promotion, CUtensorMapFloatOOBfill);

void map2d(EncodeFn enc, CUtensorMap* tm, const void* p, uint64_t cols, uint64_t rows, uint32_t bc, uint32_t br, CUtensorMapSwizzle sw) {
  cuuint64_t gd[2] = {cols, rows}, gs[1] = {cols * 2};
  cuuint32_t bd[2] = {bc, br}, es[2] = {1, 1};
  enc(tm, CU_TENSOR_MAP_DATA_TYPE_BFLOAT16, 2, (void*)p, gd, gs, bd, es, CU_TENSOR_MAP_INTERLEAVE_NONE, sw,
      sw == CU_TENSOR_MAP_SWIZZLE_NONE ? CU_TENSOR_MAP_L2_PROMOTION_NONE : CU_TENSOR_MAP_L2_PROMOTION_L2_128B, CU_TENSOR_MAP_FLOAT_OOB_FILL_NONE);
}

}

extern "C" void kernel_launch(void* const* d_in, const int* in_sizes, int n_in, void* d_out, int out_size) {
  (void)in_sizes; (void)n_in; (void)out_size;
  static EncodeFn enc = nullptr;
  if (!enc) {
    cudaDriverEntryPointQueryResult qr;
    cudaGetDriverEntryPoint("cuTensorMapEncodeTiled", (void**)&enc, cudaEnableDefault, &qr);
    cudaFuncSetAttribute(fused_kernel, cudaFuncAttributeMaxDynamicSharedMemorySize, SMEM_BYTES);
  }
  Params prm;
  const CUtensorMapSwizzle S128 = CU_TENSOR_MAP_SWIZZLE_128B, S0 = CU_TENSOR_MAP_SWIZZLE_NONE;
  map2d(enc, &prm.tx, d_in[0], kD, kS, 64, 64, S128);
  map2d(enc, &prm.tBre, d_in[3], kD, 576, 64, 72, S128);
  map2d(enc, &prm.tBim, d_in[4], kD, 576, 64, 72, S128);
  map2d(enc, &prm.tCre, d_in[5], 576, kD, 64, 64, S128);
  map2d(enc, &prm.tCim, d_in[6], 576, kD, 64, 64, S128);
  map2d(enc, &prm.tCre8, d_in[5], 576, kD, 8, 64, S0);
  map2d(enc, &prm.tCim8, d_in[6], 576, kD, 8, 64, S0);
  map2d(enc, &prm.tWg, d_in[10], kF, kD, 64, 64, S128);
  map2d(enc, &prm.tWu, d_in[11], kF, kD, 64, 64, S128);
  map2d(enc, &prm.tWd, d_in[12], kD, kF, 64, 64, S128);
  {
    cuuint64_t gd[4] = {kD, 2, 4, kS / 8}, gs[3] = {4 * kD * 4, kD * 4, 8 * kD * 4};
    cuuint32_t bd[4] = {32, 2, 4, 8}, es[4] = {1, 1, 1, 1};
    enc(&prm.tOut, CU_TENSOR_MAP_DATA_TYPE_FLOAT32, 4, d_out, gd, gs, bd, es, CU_TENSOR_MAP_INTERLEAVE_NONE, S128, CU_TENSOR_MAP_L2_PROMOTION_NONE,
        CU_TENSOR_MAP_FLOAT_OOB_FILL_NONE);
  }
  prm.x = (const __nv_bfloat16*)d_in[0];
  prm.lre = (const __nv_bfloat16*)d_in[1];
  prm.lim = (const __nv_bfloat16*)d_in[2];
  prm.bre = (const __nv_bfloat16*)d_in[3];
  prm.bim = (const __nv_bfloat16*)d_in[4];
  prm.cre = (const __nv_bfloat16*)d_in[5];
  prm.cim = (const __nv_bfloat16*)d_in[6];
  prm.wg = (const __nv_bfloat16*)d_in[10];
  prm.wu = (const __nv_bfloat16*)d_in[11];
  prm.wd = (const __nv_bfloat16*)d_in[12];
  prm.ldt = (const __nv_bfloat16*)d_in[7];
  prm.dskip = (const __nv_bfloat16*)d_in[8];
  prm.out = (float*)d_out;

  fused_kernel<<<128, 384, SMEM_BYTES, cudaStreamPerThread>>>(prm);
}
```

```cpp
#include <cuda_runtime.h>
#include <cuda.h>
#include <cuda_bf16.h>
#include <stdint.h>

namespace {

#define PACE 1
#define SKEW 3
#define SKEWB 4

constexpr int kS = 2048, kD = 576, kF = 4608;
constexpr int NST = 6;
constexpr uint32_t SLOT = 16384;
constexpr uint32_t OFF_H = NST * SLOT;
constexpr uint32_t HS_LBO = 1040;
constexpr uint32_t HS_BYTES = 18 * HS_LBO;
constexpr uint32_t OFF_DUMP = OFF_H + 65536 - HS_BYTES;
constexpr uint32_t OFF_STG = OFF_H + SLOT;
constexpr uint32_t OFF_HS = OFF_STG + 65536;
constexpr uint32_t OFF_BAR = OFF_H + 131072;
constexpr uint32_t OFF_CONST = OFF_BAR + 384;
constexpr uint32_t SMEM_BYTES = OFF_CONST + 4 * 72 * 4;
static_assert(SMEM_BYTES <= 232448 && OFF_HS + 2 * HS_BYTES <= OFF_BAR, "smem");

enum { B_FULL = 0, B_EMPTY = NST + 1, B_X = 2 * NST + 2, B_SCAN = B_X + 8, B_HFREE, B_HSFULL, B_CRDY, B_SFULL,
       B_SFREE = B_SFULL + 2, B_RFULL = B_SFREE + 2, B_RFREE = B_RFULL + 2, B_COUNT = B_RFREE + 2 };
static_assert(B_COUNT * 8 <= 384 && B_COUNT <= 64, "barriers");
enum { NB_SKEW = 1, NB_WG = 2  , NB_SCAN = 4, NB_DUMP = 5 };

struct __align__(64) Params {
  CUtensorMap tx, tBre, tBim, tWg, tWu, tWd, tC, tC16, tOut;
  const __nv_bfloat16 *lre, *lim, *cre, *cim, *ldt, *dskip, *wg, *wu, *wd;
  float* out;
};

__device__ unsigned g_epoch[128];
__device__ unsigned g_ready;
__device__ uint2 g_S[2][16][576];
__device__ __align__(128) uint8_t g_hs[128][2 * HS_BYTES];
__device__ __align__(128) uint32_t g_C[576][576];
#define STAMP(role, i)

__device__ __forceinline__ void wgmma_n72_rs_tb0(float (&d)[36], uint32_t a0, uint32_t a1, uint32_t a2, uint32_t a3, uint64_t db, int scale_d) {
  asm volatile("{\n.reg .pred p;\nsetp.ne.b32 p, %41, 0;\n"
    "wgmma.mma_async.sync.aligned.m64n72k16.f32.bf16.bf16 {"
    "%0, %1, %2, %3, %4, %5, %6, %7, %8, %9, %10, %11, %12, %13, %14, %15, "
    "%16, %17, %18, %19, %20, %21, %22, %23, %24, %25, %26, %27, %28, %29, %30, %31, "
    "%32, %33, %34, %35"
    "}, {%36, %37, %38, %39}, %40, p, 1, 1, 0;\n}\n"
    : "+f"(d[0]), "+f"(d[1]), "+f"(d[2]), "+f"(d[3]), "+f"(d[4]), "+f"(d[5]), "+f"(d[6]), "+f"(d[7]),
      "+f"(d[8]), "+f"(d[9]), "+f"(d[10]), "+f"(d[11]), "+f"(d[12]), "+f"(d[13]), "+f"(d[14]), "+f"(d[15]),
      "+f"(d[16]), "+f"(d[17]), "+f"(d[18]), "+f"(d[19]), "+f"(d[20]), "+f"(d[21]), "+f"(d[22]), "+f"(d[23]),
      "+f"(d[24]), "+f"(d[25]), "+f"(d[26]), "+f"(d[27]), "+f"(d[28]), "+f"(d[29]), "+f"(d[30]), "+f"(d[31]),
      "+f"(d[32]), "+f"(d[33]), "+f"(d[34]), "+f"(d[35])
    : "r"(a0), "r"(a1), "r"(a2), "r"(a3), "l"(db), "r"(scale_d));
}
__device__ __forceinline__ void wgmma_n128_rs_tb1(float (&d)[64], uint32_t a0, uint32_t a1, uint32_t a2, uint32_t a3, uint64_t db, int scale_d) {
  asm volatile("{\n.reg .pred p;\nsetp.ne.b32 p, %69, 0;\n"
    "wgmma.mma_async.sync.aligned.m64n128k16.f32.bf16.bf16 {"
    "%0, %1, %2, %3, %4, %5, %6, %7, %8, %9, %10, %11, %12, %13, %14, %15, "
    "%16, %17, %18, %19, %20, %21, %22, %23, %24, %25, %26, %27, %28, %29, %30, %31, "
    "%32, %33, %34, %35, %36, %37, %38, %39, %40, %41, %42, %43, %44, %45, %46, %47, "
    "%48, %49, %50, %51, %52, %53, %54, %55, %56, %57, %58, %59, %60, %61, %62, %63"
    "}, {%64, %65, %66, %67}, %68, p, 1, 1, 1;\n}\n"
    : "+f"(d[0]), "+f"(d[1]), "+f"(d[2]), "+f"(d[3]), "+f"(d[4]), "+f"(d[5]), "+f"(d[6]), "+f"(d[7]),
      "+f"(d[8]), "+f"(d[9]), "+f"(d[10]), "+f"(d[11]), "+f"(d[12]), "+f"(d[13]), "+f"(d[14]), "+f"(d[15]),
      "+f"(d[16]), "+f"(d[17]), "+f"(d[18]), "+f"(d[19]), "+f"(d[20]), "+f"(d[21]), "+f"(d[22]), "+f"(d[23]),
      "+f"(d[24]), "+f"(d[25]), "+f"(d[26]), "+f"(d[27]), "+f"(d[28]), "+f"(d[29]), "+f"(d[30]), "+f"(d[31]),
      "+f"(d[32]), "+f"(d[33]), "+f"(d[34]), "+f"(d[35]), "+f"(d[36]), "+f"(d[37]), "+f"(d[38]), "+f"(d[39]),
      "+f"(d[40]), "+f"(d[41]), "+f"(d[42]), "+f"(d[43]), "+f"(d[44]), "+f"(d[45]), "+f"(d[46]), "+f"(d[47]),
      "+f"(d[48]), "+f"(d[49]), "+f"(d[50]), "+f"(d[51]), "+f"(d[52]), "+f"(d[53]), "+f"(d[54]), "+f"(d[55]),
      "+f"(d[56]), "+f"(d[57]), "+f"(d[58]), "+f"(d[59]), "+f"(d[60]), "+f"(d[61]), "+f"(d[62]), "+f"(d[63])
    : "r"(a0), "r"(a1), "r"(a2), "r"(a3), "l"(db), "r"(scale_d));
}
__device__ __forceinline__ void wgmma_n128_ss_tb0(float (&d)[64], uint64_t da, uint64_t db, int scale_d) {
  asm volatile("{\n.reg .pred p;\nsetp.ne.b32 p, %66, 0;\n"
    "wgmma.mma_async.sync.aligned.m64n128k16.f32.bf16.bf16 {"
    "%0, %1, %2, %3, %4, %5, %6, %7, %8, %9, %10, %11, %12, %13, %14, %15, "
    "%16, %17, %18, %19, %20, %21, %22, %23, %24, %25, %26, %27, %28, %29, %30, %31, "
    "%32, %33, %34, %35, %36, %37, %38, %39, %40, %41, %42, %43, %44, %45, %46, %47, "
    "%48, %49, %50, %51, %52, %53, %54, %55, %56, %57, %58, %59, %60, %61, %62, %63"
    "}, %64, %65, p, 1, 1, 0, 0;\n}\n"
    : "+f"(d[0]), "+f"(d[1]), "+f"(d[2]), "+f"(d[3]), "+f"(d[4]), "+f"(d[5]), "+f"(d[6]), "+f"(d[7]),
      "+f"(d[8]), "+f"(d[9]), "+f"(d[10]), "+f"(d[11]), "+f"(d[12]), "+f"(d[13]), "+f"(d[14]), "+f"(d[15]),
      "+f"(d[16]), "+f"(d[17]), "+f"(d[18]), "+f"(d[19]), "+f"(d[20]), "+f"(d[21]), "+f"(d[22]), "+f"(d[23]),
      "+f"(d[24]), "+f"(d[25]), "+f"(d[26]), "+f"(d[27]), "+f"(d[28]), "+f"(d[29]), "+f"(d[30]), "+f"(d[31]),
      "+f"(d[32]), "+f"(d[33]), "+f"(d[34]), "+f"(d[35]), "+f"(d[36]), "+f"(d[37]), "+f"(d[38]), "+f"(d[39]),
      "+f"(d[40]), "+f"(d[41]), "+f"(d[42]), "+f"(d[43]), "+f"(d[44]), "+f"(d[45]), "+f"(d[46]), "+f"(d[47]),
      "+f"(d[48]), "+f"(d[49]), "+f"(d[50]), "+f"(d[51]), "+f"(d[52]), "+f"(d[53]), "+f"(d[54]), "+f"(d[55]),
      "+f"(d[56]), "+f"(d[57]), "+f"(d[58]), "+f"(d[59]), "+f"(d[60]), "+f"(d[61]), "+f"(d[62]), "+f"(d[63])
    : "l"(da), "l"(db), "r"(scale_d));
}
__device__ __forceinline__ void wgmma_n64_rs_tb1(float (&d)[32], uint32_t a0, uint32_t a1, uint32_t a2, uint32_t a3, uint64_t db, int scale_d) {
  asm volatile("{\n.reg .pred p;\nsetp.ne.b32 p, %37, 0;\n"
    "wgmma.mma_async.sync.aligned.m64n64k16.f32.bf16.bf16 {"
    "%0, %1, %2, %3, %4, %5, %6, %7, %8, %9, %10, %11, %12, %13, %14, %15, "
    "%16, %17, %18, %19, %20, %21, %22, %23, %24, %25, %26, %27, %28, %29, %30, %31"
    "}, {%32, %33, %34, %35}, %36, p, 1, 1, 1;\n}\n"
    : "+f"(d[0]), "+f"(d[1]), "+f"(d[2]), "+f"(d[3]), "+f"(d[4]), "+f"(d[5]), "+f"(d[6]), "+f"(d[7]),
      "+f"(d[8]), "+f"(d[9]), "+f"(d[10]), "+f"(d[11]), "+f"(d[12]), "+f"(d[13]), "+f"(d[14]), "+f"(d[15]),
      "+f"(d[16]), "+f"(d[17]), "+f"(d[18]), "+f"(d[19]), "+f"(d[20]), "+f"(d[21]), "+f"(d[22]), "+f"(d[23]),
      "+f"(d[24]), "+f"(d[25]), "+f"(d[26]), "+f"(d[27]), "+f"(d[28]), "+f"(d[29]), "+f"(d[30]), "+f"(d[31])
    : "r"(a0), "r"(a1), "r"(a2), "r"(a3), "l"(db), "r"(scale_d));
}
__device__ __forceinline__ void wgmma_n64_ss_tb0(float (&d)[32], uint64_t da, uint64_t db, int scale_d) {
  asm volatile("{\n.reg .pred p;\nsetp.ne.b32 p, %34, 0;\n"
    "wgmma.mma_async.sync.aligned.m64n64k16.f32.bf16.bf16 {"
    "%0, %1, %2, %3, %4, %5, %6, %7, %8, %9, %10, %11, %12, %13, %14, %15, "
    "%16, %17, %18, %19, %20, %21, %22, %23, %24, %25, %26, %27, %28, %29, %30, %31"
    "}, %32, %33, p, 1, 1, 0, 0;\n}\n"
    : "+f"(d[0]), "+f"(d[1]), "+f"(d[2]), "+f"(d[3]), "+f"(d[4]), "+f"(d[5]), "+f"(d[6]), "+f"(d[7]),
      "+f"(d[8]), "+f"(d[9]), "+f"(d[10]), "+f"(d[11]), "+f"(d[12]), "+f"(d[13]), "+f"(d[14]), "+f"(d[15]),
      "+f"(d[16]), "+f"(d[17]), "+f"(d[18]), "+f"(d[19]), "+f"(d[20]), "+f"(d[21]), "+f"(d[22]), "+f"(d[23]),
      "+f"(d[24]), "+f"(d[25]), "+f"(d[26]), "+f"(d[27]), "+f"(d[28]), "+f"(d[29]), "+f"(d[30]), "+f"(d[31])
    : "l"(da), "l"(db), "r"(scale_d));
}

__device__ __forceinline__ bool elect() {
  uint32_t p;
  asm volatile("{.reg .pred q; elect.sync _|q, 0xffffffff; selp.u32 %0,1,0,q;}" : "=r"(p));
  return p;
}
__device__ __forceinline__ void mbar_init(uint32_t bar, uint32_t cnt) { asm volatile("mbarrier.init.shared::cta.b64 [%0], %1;" ::"r"(bar), "r"(cnt) : "memory"); }
__device__ __forceinline__ void mbar_expect(uint32_t bar, uint32_t bytes) { asm volatile("mbarrier.arrive.expect_tx.shared::cta.b64 _, [%0], %1;" ::"r"(bar), "r"(bytes) : "memory"); }
__device__ __forceinline__ void mbar_arrive(uint32_t bar) { asm volatile("mbarrier.arrive.shared::cta.b64 _, [%0];" ::"r"(bar) : "memory"); }
__device__ __forceinline__ void mbar_arrive_cta(uint32_t bar, uint32_t cta) {
  asm volatile("{.reg .b32 ra; mapa.shared::cluster.u32 ra, %0, %1; mbarrier.arrive.shared::cluster.b64 _, [ra];}" ::"r"(bar), "r"(cta) : "memory");
}
__device__ __forceinline__ void mbar_wait(uint32_t bar, uint32_t parity) {
  asm volatile(
      "{\n.reg .pred p;\n.reg .u32 c, t;\n"
      "mbarrier.try_wait.parity.shared::cta.b64 p, [%0], %1;\n@p bra DONE;\n"
      "mov.u32 c, %%clock;\n"
      "LAB_WAIT:\nmbarrier.try_wait.parity.shared::cta.b64 p, [%0], %1;\n@p bra DONE;\n"
      "mov.u32 t, %%clock;\nsub.u32 t, t, c;\nsetp.lt.u32 p, t, 0x40000000;\n@p bra LAB_WAIT;\ntrap;\nDONE:\n}" ::"r"(bar), "r"(parity) : "memory");
}
__device__ __forceinline__ void bar_sync(int id, int n) { asm volatile("bar.sync %0, %1;" ::"r"(id), "r"(n) : "memory"); }
__device__ __forceinline__ void bar_arrive(int id, int n) { asm volatile("bar.arrive %0, %1;" ::"r"(id), "r"(n) : "memory"); }
__device__ __forceinline__ void wg_fence() { asm volatile("wgmma.fence.sync.aligned;" ::: "memory"); }
__device__ __forceinline__ void wg_commit() { asm volatile("wgmma.commit_group.sync.aligned;" ::: "memory"); }
template <int N> __device__ __forceinline__ void wg_wait() { asm volatile("wgmma.wait_group.sync.aligned %0;" ::"n"(N) : "memory"); }
__device__ __forceinline__ void tma2d(uint32_t dst, const CUtensorMap* tm, uint32_t bar, int c0, int c1) {
  asm volatile("cp.async.bulk.tensor.2d.shared::cluster.global.mbarrier::complete_tx::bytes [%0], [%1,{%3,%4}], [%2];" ::"r"(dst), "l"(tm), "r"(bar), "r"(c0), "r"(c1) : "memory");
}
__device__ __forceinline__ void tma2d_mc(uint32_t dst, const CUtensorMap* tm, uint32_t bar, int c0, int c1) {
  asm volatile("cp.async.bulk.tensor.2d.shared::cluster.global.mbarrier::complete_tx::bytes.multicast::cluster [%0], [%1,{%3,%4}], [%2], %5;" ::"r"(dst), "l"(tm), "r"(bar), "r"(c0), "r"(c1), "h"((uint16_t)3) : "memory");
}
__device__ __forceinline__ void l2_prefetch(const void* p, uint32_t bytes) {
  asm volatile("cp.async.bulk.prefetch.L2.global [%0], %1;" ::"l"(p), "r"(bytes) : "memory");
}
__device__ __forceinline__ void tma_prefetch2d(const CUtensorMap* tm, int c0, int c1) {
  asm volatile("cp.async.bulk.prefetch.tensor.2d.L2.global.tile [%0,{%1,%2}];" ::"l"(tm), "r"(c0), "r"(c1) : "memory");
}
__device__ __forceinline__ uint64_t desc(uint32_t lo, uint32_t hi) { return ((uint64_t)hi << 32) | lo; }
constexpr uint32_t DHI_SW128 = (1024 >> 4) | (1u << 30);
constexpr uint32_t DHI_NONE = (128 >> 4);
constexpr uint32_t DHI_SW32 = (256 >> 4) | (3u << 30);
constexpr uint32_t DLO_HS = (HS_LBO >> 4) << 16;
constexpr uint32_t DLO_MN = (8192 >> 4) << 16;
constexpr uint32_t DLO_K = 1u << 16;
__device__ __forceinline__ float tanh_fast(float x) { float y; asm("tanh.approx.f32 %0, %1;" : "=f"(y) : "f"(x)); return y; }
__device__ __forceinline__ uint32_t pack_bf16(float lo, float hi) { uint32_t r; asm("cvt.rn.bf16x2.f32 %0, %1, %2;" : "=r"(r) : "f"(hi), "f"(lo)); return r; }
__device__ __forceinline__ float rbf(float x) { return __bfloat162float(__float2bfloat16_rn(x)); }
__device__ __forceinline__ void mma16816(float (&c)[4], uint32_t a0, uint32_t a1, uint32_t a2, uint32_t a3, uint32_t b0, uint32_t b1) {
  asm volatile("mma.sync.aligned.m16n8k16.row.col.f32.bf16.bf16.f32 {%0,%1,%2,%3}, {%4,%5,%6,%7}, {%8,%9}, {%0,%1,%2,%3};"
               : "+f"(c[0]), "+f"(c[1]), "+f"(c[2]), "+f"(c[3]) : "r"(a0), "r"(a1), "r"(a2), "r"(a3), "r"(b0), "r"(b1));
}
__device__ __forceinline__ void sts128(uint32_t a, uint32_t x, uint32_t y, uint32_t z, uint32_t w) {
  asm volatile("st.shared.v4.b32 [%0], {%1,%2,%3,%4};" ::"r"(a), "r"(x), "r"(y), "r"(z), "r"(w) : "memory");
}
__device__ __forceinline__ void sts64f(uint32_t a, float x, float y) { asm volatile("st.shared.v2.f32 [%0], {%1,%2};" ::"r"(a), "f"(x), "f"(y) : "memory"); }
__device__ __forceinline__ float2 lds64f(uint32_t a) { float2 v; asm volatile("ld.shared.v2.f32 {%0,%1}, [%2];" : "=f"(v.x), "=f"(v.y) : "r"(a) : "memory"); return v; }
__device__ __forceinline__ uint32_t lds32(uint32_t a) { uint32_t v; asm volatile("ld.shared.b32 %0, [%1];" : "=r"(v) : "r"(a) : "memory"); return v; }
__device__ __forceinline__ void lds128(uint32_t a, uint32_t& x, uint32_t& y, uint32_t& z, uint32_t& w) {
  asm volatile("ld.shared.v4.b32 {%0,%1,%2,%3}, [%4];" : "=r"(x), "=r"(y), "=r"(z), "=r"(w) : "r"(a) : "memory");
}
__device__ __forceinline__ float bflo(uint32_t v) { return __uint_as_float(v << 16); }
__device__ __forceinline__ float bfhi(uint32_t v) { return __uint_as_float(v & 0xffff0000u); }
__device__ __forceinline__ uint32_t lds32v(uint32_t a) { uint32_t v; asm volatile("ld.volatile.shared.b32 %0, [%1];" : "=r"(v) : "r"(a) : "memory"); return v; }
__device__ __forceinline__ float lds32f(uint32_t a) { float v; asm volatile("ld.shared.f32 %0, [%1];" : "=f"(v) : "r"(a) : "memory"); return v; }
template <int N> __device__ __forceinline__ void keep(float (&a)[N]) {
#pragma unroll
  for (int i = 0; i < N; i++) asm volatile("" : "+f"(a[i])::"memory");
}

__global__ void __cluster_dims__(2, 1, 1) __launch_bounds__(384, 1) fused_kernel(const __grid_constant__ Params prm) {
  extern __shared__ __align__(1024) uint8_t smem[];
  const int warp = __shfl_sync(0xffffffffu, threadIdx.x >> 5, 0);
  const uint32_t sb0 = (uint32_t)__cvta_generic_to_shared(smem);
  const int j = blockIdx.x & 7, m = blockIdx.x >> 3, rank = j & 1;
  auto smem_base = [&]() { return __shfl_sync(0xffffffffu, sb0 + (threadIdx.x & 31), 0); };
  STAMP(warp >> 2, 31);

  if (warp == 8 || warp == 9) {
    const int i = threadIdx.x - 256;
    if (i < B_COUNT) {
      const uint32_t bi = sb0 + OFF_BAR + i * 8;
      mbar_init(bi, i == B_HFREE ? 8 : (i >= B_SFULL && i < B_SFULL + 2) ? 4 : (i >= B_EMPTY && i < B_X) ? 2 : 1);
      if (i == B_FULL + NST || i == B_EMPTY + NST) mbar_arrive(bi);
      if (i == B_EMPTY + NST) mbar_arrive(bi);
      asm volatile("fence.mbarrier_init.release.cluster;" ::: "memory");
    }
    if (sb0 & 1023) __trap();
    __syncwarp();
  }
  asm volatile("barrier.cluster.arrive.relaxed.aligned;\nbarrier.cluster.wait.aligned;" ::: "memory");

  if (warp >= 8) {
    asm volatile("setmaxnreg.dec.sync.aligned.u32 24;");
    if (warp == 8) {
      const uint32_t sb = smem_base(), bars = sb + OFF_BAR;
      bool e = elect();
      if (e) { mbar_expect(bars + 8 * B_FULL, 16384); tma2d_mc(sb + rank * 8192, &prm.tx, bars + 8 * B_FULL, 512, m * 128 + rank * 64); }
#pragma unroll
      for (int i = 0; i < 8; i++) {
        const int w = i >> 2, kb = (i & 3) * 2 + rank;
        if (e) { mbar_expect(bars + 8 * (B_X + i), 16384); tma2d_mc(sb + OFF_H + w * 65536 + kb * 8192, &prm.tx, bars + 8 * (B_X + i), kb * 64, m * 128 + w * 64); }
      }
      int s = 1, nst = NST; uint32_t ph = 1;
      uint32_t dst, fb;
      auto acquire = [&](uint32_t bytes) {
        mbar_wait(bars + 8 * (B_EMPTY + s), ph);
        fb = bars + 8 * (B_FULL + s); dst = sb + s * SLOT;
        e = elect();
        if (e) mbar_expect(fb, bytes);
        if (++s == nst) { s = 0; ph ^= 1; }
      };
      auto box = [&](const CUtensorMap* t, uint32_t o, int a, int b) { if (e) tma2d(dst + o, t, fb, a, b); };
      for (int kb = 0; kb < 9; kb++) { acquire(9216); box(&prm.tBre, 0, kb * 64, j * 72); }
      for (int kb = 0; kb < 9; kb++) { acquire(9216); box(&prm.tBim, 0, kb * 64, j * 72); }
      for (int c = 0; c < 9; c++) {
        const int col = j * 576 + c * 64;
        for (int kb = 0; kb < 9; kb++) { acquire(16384); box(&prm.tWg, 0, col, kb * 64); box(&prm.tWu, 8192, col, kb * 64); }
      }
      for (int t = 0; t < 4; t++) {
        const int n0 = ((rank ^ t ^ 1) & 1) * 256 + (((t >> 1) ^ (j >> 1)) & 1) * 128;
        for (int kb = 0; kb < 9; kb++) {
          if (kb == 3) nst = NST + 1;
          if (kb == 8 && t == 0) {
            mbar_wait(bars + 8 * B_HFREE, 0);
            mbar_wait(bars + 8 * B_CRDY, 0);
            asm volatile("fence.proxy.async.global;" ::: "memory");
          }
          acquire(16384); box(&prm.tWd, 0, n0, j * 576 + kb * 64); box(&prm.tWd, 8192, n0 + 64, j * 576 + kb * 64);
        }
        acquire(16384); box(&prm.tC, 0, j * 144, n0); box(&prm.tC, 8192, j * 144, n0 + 64);
        acquire(16384); box(&prm.tC, 0, j * 144 + 64, n0); box(&prm.tC, 8192, j * 144 + 64, n0 + 64);
        acquire(4096); box(&prm.tC16, 0, j * 144 + 128, n0); box(&prm.tC16, 2048, j * 144 + 128, n0 + 64);
      }
      for (int kp = 0; kp < 4; kp++) { acquire(16384); box(&prm.tWd, 0, 512, j * 576 + kp * 128); box(&prm.tWd, 8192, 512, j * 576 + kp * 128 + 64); }
      acquire(8192 + 2048); box(&prm.tWd, 0, 512, j * 576 + 512); box(&prm.tC16, 8192, j * 144 + 128, 512);
      acquire(16384); box(&prm.tC, 0, j * 144, 512); box(&prm.tC, 8192, j * 144 + 64, 512);
    } else {
      const uint32_t sb = smem_base(), bars = sb + OFF_BAR;
      const int p = min((int)threadIdx.x - 288, 71);
      if (threadIdx.x < 288 + 8) asm volatile("prefetch.tensormap [%0];" ::"l"(&prm.tBre + (threadIdx.x - 288)) : "memory");
      const unsigned epoch = *(volatile unsigned*)&g_epoch[blockIdx.x];
      float ar, ai;
      {
        const int pg = j * 72 + p;
        const float lr = __bfloat162float(prm.lre[pg]), li = __bfloat162float(prm.lim[pg]);
        const float dt = rbf(expf(__bfloat162float(prm.ldt[pg])));
        const float ea = expf(dt * lr);
        float sn, cs;
        sincosf(dt * li, &sn, &cs);
        ar = ea * cs; ai = ea * sn;
        float br = ar, bi = ai;
#pragma unroll
        for (int k = 0; k < 7; k++) { const float t = br * br - bi * bi; bi = 2.f * br * bi; br = t; }
        const float nr = ar - 1.f, den = 4.f / (lr * lr + li * li);
        float* cp = (float*)(smem + OFF_CONST) + p;
        cp[0] = (nr * lr + ai * li) * den; cp[72] = (ai * lr - nr * li) * den; cp[144] = br; cp[216] = bi;
      }
      bar_sync(NB_SCAN, 96);
      {
        const int r0 = p >= 36, cp = p - r0 * 36;
        const float2 cr = lds64f(sb + OFF_CONST + cp * 8), ci = lds64f(sb + OFF_CONST + 288 + cp * 8);
        uint32_t o = (m * 36 + r0) * 288 + j * 36 + cp;
#pragma unroll 1
        for (int it = 0; it < 6; it++, o += 6 * 288) {
          uint32_t vr[3], vi[3];
#pragma unroll
          for (int k = 0; k < 3; k++) { vr[k] = __ldg((const uint32_t*)prm.cre + o + k * 576); vi[k] = __ldg((const uint32_t*)prm.cim + o + k * 576); }
#pragma unroll
          for (int k = 0; k < 3; k++) {
            const float r0v = bflo(vr[k]), i0v = bflo(vi[k]), r1v = bfhi(vr[k]), i1v = bfhi(vi[k]);
            ((uint2*)&g_C[0][0])[o + k * 576] = make_uint2(pack_bf16(r0v * cr.x - i0v * ci.x, -r0v * ci.x - i0v * cr.x), pack_bf16(r1v * cr.y - i1v * ci.y, -r1v * ci.y - i1v * cr.y));
          }
        }
      }
      STAMP(2, 0);
      if (warp == 9) {
        mbar_wait(bars + 8 * (B_X + 7), 0);
        if (elect()) {
          const size_t o = (size_t)blockIdx.x * 20736;
          for (int i = 0; i < 3; i++) { l2_prefetch(prm.wg + o + i * 6912, 13824); l2_prefetch(prm.wu + o + i * 6912, 13824); }
          for (int i = 0; i < 3; i++) l2_prefetch(prm.wd + o + i * 6912, 13824);
        }
        __syncwarp();
      }
      bar_sync(NB_DUMP, 352);
      if (threadIdx.x == 383) {
        __threadfence();
        asm volatile("red.release.gpu.global.add.u32 [%0], 1;" ::"l"(&g_ready) : "memory");
        g_epoch[blockIdx.x] = epoch + 1u;
      }
      __syncwarp();
      {
        float hr = 0.f, hi = 0.f;
        uint32_t a0 = sb + OFF_DUMP + (p >> 2) * HS_LBO + (p & 3) * 4;
        asm volatile("" : "+r"(a0));
        auto step = [&](uint32_t v) {
          const float nr = fmaf(ar, hr, fmaf(-ai, hi, bflo(v)));
          hi = fmaf(ar, hi, fmaf(ai, hr, bfhi(v))); hr = nr;
        };
        if (m < 15) {
#pragma unroll 1
          for (int tb = 0; tb < 16; tb++) {
            const uint32_t a = a0 + tb * 128 + (tb >> 3) * (HS_BYTES - 1024);
            uint32_t v[8];
#pragma unroll
            for (int k = 0; k < 8; k++) v[k] = lds32(a + k * 16);
#pragma unroll
            for (int k = 0; k < 8; k++) step(v[k]);
          }
          asm volatile("st.relaxed.gpu.global.v2.b32 [%0], {%1,%2};" ::"l"(&g_S[epoch & 1][m][j * 72 + p]), "r"(~__float_as_uint(hr)), "r"(~__float_as_uint(hi)) : "memory");
          g_S[(epoch & 1) ^ 1][m][j * 72 + p] = make_uint2(0u, 0u);
        }
        STAMP(2, 4);
        {
          const float br = lds32f(sb + OFF_CONST + 576 + p * 4), bi = lds32f(sb + OFF_CONST + 864 + p * 4);
          hr = 0.f; hi = 0.f;
          const uint2* sp = &g_S[epoch & 1][0][j * 72 + p];
#pragma unroll 1
          for (int left = m; left > 0; left -= 4, sp += 4 * 576) {
            uint32_t v[4][2];
            int spins = 0;
            uint32_t ok;
            do {
#pragma unroll
              for (int k = 0; k < 4; k++) {
                v[k][0] = v[k][1] = 0xffffffffu;
                if (k < left) asm volatile("ld.relaxed.gpu.global.v2.b32 {%0,%1}, [%2];" : "=r"(v[k][0]), "=r"(v[k][1]) : "l"(sp + k * 576) : "memory");
              }
              ok = min(min(min(v[0][0], v[0][1]), min(v[1][0], v[1][1])), min(min(v[2][0], v[2][1]), min(v[3][0], v[3][1])));
              if (++spins > (1 << 22)) __trap();
            } while (ok == 0u);
#pragma unroll
            for (int k = 0; k < 4; k++)
              if (k < left) { const float nr = fmaf(br, hr, fmaf(-bi, hi, __uint_as_float(~v[k][0]))); hi = fmaf(br, hi, fmaf(bi, hr, __uint_as_float(~v[k][1]))); hr = nr; }
          }
        }
        STAMP(2, 5);
#pragma unroll 1
        for (int tb = 0; tb < 16; tb++) {
          const uint32_t a = a0 + tb * 128 + (tb >> 3) * (HS_BYTES - 1024);
          uint32_t v[8];
#pragma unroll
          for (int k = 0; k < 8; k++) v[k] = lds32(a + k * 16);
#pragma unroll
          for (int k = 0; k < 8; k++) {
            step(v[k]);
            asm volatile("st.shared.b32 [%0], %1;" ::"r"(a + k * 16), "r"(pack_bf16(hr, hi)) : "memory");
          }
        }
        asm volatile("fence.proxy.async.shared::cta;" ::: "memory");
      }
      STAMP(2, 6);
      bar_sync(NB_SCAN, 96);
      if (warp == 9) {
        if (elect()) {
          asm volatile("cp.async.bulk.global.shared::cta.bulk_group [%0], [%1], %2;" ::"l"(&g_hs[blockIdx.x][0]), "r"(sb + OFF_DUMP), "r"(2 * HS_BYTES) : "memory");
          asm volatile("cp.async.bulk.commit_group;\ncp.async.bulk.wait_group.read 0;" ::: "memory");
          mbar_arrive(bars + 8 * B_SCAN);
          asm volatile("cp.async.bulk.wait_group 0;" ::: "memory");
        }
        __syncwarp();
        STAMP(2, 2);
        mbar_wait(bars + 8 * B_HFREE, 0);
        if (elect()) {
          mbar_expect(bars + 8 * B_HSFULL, 2 * HS_BYTES);
          asm volatile("cp.async.bulk.shared::cluster.global.mbarrier::complete_tx::bytes [%0], [%1], %2, [%3];" ::"r"(sb + OFF_HS),
                       "l"(&g_hs[blockIdx.x][0]), "r"(2 * HS_BYTES), "r"(bars + 8 * B_HSFULL) : "memory");
          for (int w = 0; w < 2; w++) { mbar_expect(bars + 8 * (B_RFULL + w), 16384); mbar_arrive_cta(bars + 8 * (B_RFREE + w), rank ^ 1); }
        }
        __syncwarp();
      } else {
        const int w = warp - 10;
        {
          const unsigned target = 128u * (epoch + 1u);
          int spins = 0;
          unsigned v;
          do {
            asm volatile("ld.acquire.gpu.global.u32 %0, [%1];" : "=r"(v) : "l"(&g_ready) : "memory");
            if (++spins > (1 << 22)) __trap();
          } while ((int)(v - target) < 0);
          asm volatile("fence.proxy.async.global;" ::: "memory");
          if (w == 0 && elect()) mbar_arrive(bars + 8 * B_CRDY);
        }
#pragma unroll 1
        for (int t = 0; t < 3; t++) {
          mbar_wait(bars + 8 * (B_SFULL + w), t & 1);
          const int n0 = t < 2 ? rank * 256 + ((t ^ (j >> 1)) & 1) * 128 : 512;
          const uint32_t src = t < 2 ? sb + OFF_STG + w * 32768 : sb + (4 + w) * SLOT;
          if (elect()) {
#pragma unroll 1
            for (int b = 0; b < (t < 2 ? 4 : 2); b++) {
              asm volatile("cp.reduce.async.bulk.tensor.4d.global.shared::cta.add.tile.bulk_group [%0, {%1,%2,%2,%3}], [%4];" ::"l"(&prm.tOut), "r"(n0 + b * 32), "r"(0),
                           "r"(m * 16 + w * 8), "r"(src + b * 8192) : "memory");
              asm volatile("cp.async.bulk.commit_group;" ::: "memory");
              if (PACE && t == 0) { asm volatile("cp.async.bulk.wait_group.read 0;" ::: "memory"); if (PACE > 1) __nanosleep(PACE); }
            }
            if (t == 0) {
              asm volatile("cp.async.bulk.wait_group.read 0;" ::: "memory");
              mbar_arrive(bars + 8 * (B_SFREE + w));
              mbar_expect(bars + 8 * (B_RFULL + w), 16384);
              mbar_arrive_cta(bars + 8 * (B_RFREE + w), rank ^ 1);
            }
            if (t == 2) asm volatile("cp.async.bulk.wait_group.read 0;" ::: "memory");
          }
          __syncwarp();
        }
      }
    }
  } else {
    asm volatile("setmaxnreg.inc.sync.aligned.u32 240;");
    const uint32_t sb = smem_base(), bars = sb + OFF_BAR;
    const int wg = warp >> 2, w4 = warp & 3;
    const int lane = threadIdx.x & 31, g = lane >> 2, q = lane & 3;
    const uint32_t hw = sb + OFF_H + wg * 65536;
    STAMP(wg, 0);

    int s = 0, nst = NST; uint32_t ph = 0;
    auto release = [&](int st) { if (w4 == 0) { if (elect()) mbar_arrive(bars + 8 * (B_EMPTY + st)); } };
    const uint32_t dring = (sb & 0x3FFFF) >> 4;
    uint32_t dlo; int prev = 0;
    auto stage_begin = [&]() { mbar_wait(bars + 8 * (B_FULL + s), ph); dlo = dring + s * (SLOT >> 4); wg_fence(); };
    auto advance = [&]() { if (++s == nst) { s = 0; ph ^= 1; } };
    auto stage_end = [&](bool rel) {
      wg_commit();
      if (rel) { wg_wait<1>(); release(prev); }
      prev = s;
      advance();
    };

    uint32_t xa[144];
    uint32_t xr[18], dk[9];
    float mean[2], rstd[2];
#pragma unroll
    for (int i = 0; i < 9; i++) dk[i] = __ldg((const uint32_t*)(prm.dskip + j * 72 + i * 8 + q * 2));
    {
      const int r = w4 * 16 + (lane & 7) + ((lane >> 3) & 1) * 8;
      const uint32_t ro = r * 128, cx = ((lane >> 4) ^ (lane & 7)) << 4;
      float s1[2][4] = {}, s2[2][4] = {};
      auto box = [&](int kb, uint32_t base) {
#pragma unroll
        for (int kk = 0; kk < 4; kk++) {
          const int i = (kb * 4 + kk) * 4;
          asm volatile("ldmatrix.sync.aligned.m8n8.x4.shared.b16 {%0,%1,%2,%3}, [%4];"
                       : "=r"(xa[i]), "=r"(xa[i + 1]), "=r"(xa[i + 2]), "=r"(xa[i + 3]) : "r"(base + ro + (cx ^ (kk << 5))) : "memory");
        }
#pragma unroll
        for (int kk = 0; kk < 4; kk++) {
          const int i = (kb * 4 + kk) * 4;
          uint32_t sq[4];
#pragma unroll
          for (int e = 0; e < 4; e++) asm("mul.rn.bf16x2 %0, %1, %1;" : "=r"(sq[e]) : "r"(xa[i + e]));
          mma16816(s1[kk & 1], xa[i], xa[i + 1], xa[i + 2], xa[i + 3], 0x3f803f80u, 0x3f803f80u);
          mma16816(s2[kk & 1], sq[0], sq[1], sq[2], sq[3], 0x3f803f80u, 0x3f803f80u);
        }
      };
      mbar_wait(bars + 8 * B_FULL, 0);
      STAMP(wg, 21);
      box(8, sb + wg * 8192);
#pragma unroll
      for (int kp = 0; kp < 4; kp++) {
        mbar_wait(bars + 8 * (B_X + wg * 4 + kp), 0);
        STAMP(wg, 22 + kp);
        box(2 * kp, hw + 2 * kp * 8192);
        box(2 * kp + 1, hw + (2 * kp + 1) * 8192);
      }
      STAMP(wg, 1);
#pragma unroll
      for (int i = 0; i < 9; i++) {
        const int c8 = j * 9 + i, kb = c8 >> 3;
        const uint32_t a = (kb < 8 ? hw + kb * 8192 : sb + wg * 8192) + (w4 * 16 + g) * 128 + (((c8 & 7) ^ g) << 4) + q * 4;
        xr[2 * i] = lds32(a); xr[2 * i + 1] = lds32(a + 1024);
      }
      uint32_t rh[2], rl[2], cc[2];
#pragma unroll
      for (int e = 0; e < 2; e++) {
        const float mu = (s1[0][2 * e] + s1[1][2 * e]) * (1.f / kD);
        const float var = fmaxf(fmaf(-mu, mu, (s2[0][2 * e] + s2[1][2 * e]) * (1.f / kD)), 0.f);
        float sd, r;
        asm("sqrt.approx.f32 %0, %1;" : "=f"(sd) : "f"(rbf(rbf(var) + 1e-5f)));
        asm("rcp.approx.ftz.f32 %0, %1;" : "=f"(r) : "f"(rbf(sd)));
        mean[e] = mu; rstd[e] = r;
        r *= 0.5f;
        const float h = rbf(r);
        rh[e] = pack_bf16(h, h); rl[e] = pack_bf16(r - h, r - h); cc[e] = pack_bf16(-mu * r, -mu * r);
      }
#pragma unroll
      for (int i = 0; i < 144; i++) {
        uint32_t t;
        asm("fma.rn.bf16x2 %0, %1, %2, %3;" : "=r"(t) : "r"(xa[i]), "r"(rl[i & 1]), "r"(cc[i & 1]));
        asm("fma.rn.bf16x2 %0, %0, %1, %2;" : "+r"(xa[i]) : "r"(rh[i & 1]), "r"(t));
      }
      bar_sync(NB_WG + wg, 128);
      release(0); s = 1;
    }
    STAMP(wg, 2);

    {
      float ab[36];
      uint32_t rp[18];
      float* op = prm.out + (size_t)(m * 128 + wg * 64 + w4 * 16 + g) * kD + j * 72 + q * 2;
#pragma unroll
      for (int kb = 0; kb < 9; kb++) {
        stage_begin();
#pragma unroll
        for (int kk = 0; kk < 4; kk++) { const int i = (kb * 4 + kk) * 4; wgmma_n72_rs_tb0(ab, xa[i], xa[i + 1], xa[i + 2], xa[i + 3], desc((dlo + kk * 2) | DLO_K, DHI_SW128), (kb | kk) != 0); }
        stage_end(kb > 0);
#pragma unroll
        for (int e = 0; e < 2; e++) {
          const float x0 = bflo(xr[2 * kb + e]), x1 = bfhi(xr[2 * kb + e]);
          const uint32_t xn = pack_bf16((x0 - mean[e]) * rstd[e], (x1 - mean[e]) * rstd[e]);
          uint32_t t;
          asm("mul.rn.bf16x2 %0, %1, %2;" : "=r"(t) : "r"(xn), "r"(dk[kb]));
          *(float2*)(op + e * 8 * kD + kb * 8) = make_float2(x0 + bflo(t), x1 + bfhi(t));
        }
      }
      wg_wait<0>();
      release(prev);
      keep(ab);
#pragma unroll
      for (int i = 0; i < 18; i++) rp[i] = pack_bf16(ab[2 * i], ab[2 * i + 1]);
#pragma unroll
      for (int kb = 0; kb < 9; kb++) {
        stage_begin();
#pragma unroll
        for (int kk = 0; kk < 4; kk++) { const int i = (kb * 4 + kk) * 4; wgmma_n72_rs_tb0(ab, xa[i], xa[i + 1], xa[i + 2], xa[i + 3], desc((dlo + kk * 2) | DLO_K, DHI_SW128), (kb | kk) != 0); }
        stage_end(kb > 0);
      }
      wg_wait<0>();
      release(prev);
      keep(ab);
      const uint32_t da = sb + OFF_DUMP + wg * HS_BYTES + (q >> 1) * HS_LBO + (w4 * 16 + g) * 16 + (q & 1) * 8;
#pragma unroll
      for (int i = 0; i < 18; i++) {
        const uint32_t ip = pack_bf16(ab[2 * i], ab[2 * i + 1]);
        asm volatile("st.shared.v2.b32 [%0], {%1,%2};" ::"r"(da + (i >> 1) * 2 * HS_LBO + (i & 1) * 128), "r"(__byte_perm(rp[i], ip, 0x5410)), "r"(__byte_perm(rp[i], ip, 0x7632)) : "memory");
      }
      bar_arrive(NB_DUMP, 352);
    }
    STAMP(wg, 3);

    float acc[64];
    {
      const uint32_t ha = hw + (threadIdx.x & 127) * 16 + wg * 7 * 8192;
      const int hstep = wg ? -8192 : 8192;
      auto glu = [&](int i) {
        return pack_bf16(fmaf(acc[32 + 2 * i], tanh_fast(acc[2 * i]), acc[32 + 2 * i]), fmaf(acc[33 + 2 * i], tanh_fast(acc[2 * i + 1]), acc[33 + 2 * i]));
      };
      for (int c = 0;; c++) {
        if (SKEW > 0 && wg == 1) bar_sync(NB_SKEW, 256);
#pragma unroll
        for (int kb = 0; kb < 9; kb++) {
          stage_begin();
#pragma unroll
          for (int kk = 0; kk < 4; kk++) { const int i = (kb * 4 + kk) * 4; wgmma_n128_rs_tb1(acc, xa[i], xa[i + 1], xa[i + 2], xa[i + 3], desc((dlo + kk * 128) | DLO_MN, DHI_SW128), (kb | kk) != 0); }
          if (SKEW > 0 && kb == SKEW - 1 && wg == 0) bar_arrive(NB_SKEW, 256);
          if (kb == 8 && c == 5) mbar_wait(bars + 8 * B_SCAN, 0);
          stage_end(kb > 0);
        }
        wg_wait<0>();
        release(prev);
        keep(acc);
        if (c == 8) break;
#pragma unroll
        for (int i = 0; i < 4; i++) sts128(ha + c * hstep + i * 2048, glu(4 * i), glu(4 * i + 1), glu(4 * i + 2), glu(4 * i + 3));
        STAMP(wg, 4 + c);
      }
#pragma unroll
      for (int i = 0; i < 32; i++) lds128(ha + (i >> 2) * hstep + (i & 3) * 2048, xa[4 * i], xa[4 * i + 1], xa[4 * i + 2], xa[4 * i + 3]);
#pragma unroll
      for (int i = 0; i < 16; i++) xa[128 + i] = glu(i);
      __syncwarp();
      if (elect()) mbar_arrive(bars + 8 * B_HFREE);
    }
    STAMP(wg, 13);

    const uint32_t dhs = (((sb + OFF_HS + wg * HS_BYTES) & 0x3FFFF) >> 4) | DLO_HS;
    const int rp = (g >> 2) + 2 * (g & 3);
    const uint32_t so = w4 * 2048 + rp * 128 + (q & 1) * 8, sx = ((q >> 1) ^ rp) << 4;
    const uint32_t rcv = sb + OFF_STG + wg * 32768 + 16384 + w4 * 2048 + lane * 16;
    auto staged = [&]() {
      asm volatile("fence.proxy.async.shared::cta;" ::: "memory");
      __syncwarp();
      if (elect()) mbar_arrive(bars + 8 * (B_SFULL + wg));
    };
    for (int t = 0; t < 4; t++) {
      if (SKEWB > 0 && wg == 1) bar_sync(NB_SKEW, 256);
#pragma unroll
      for (int kb = 0; kb < 9; kb++) {
        if (kb == 3) nst = NST + 1;
        stage_begin();
#pragma unroll
        for (int kk = 0; kk < 4; kk++) { const int i = (kb * 4 + kk) * 4; wgmma_n128_rs_tb1(acc, xa[i], xa[i + 1], xa[i + 2], xa[i + 3], desc((dlo + kk * 128) | DLO_MN, DHI_SW128), (kb | kk) != 0); }
        if (SKEWB > 0 && kb == SKEWB - 1 && wg == 0) bar_arrive(NB_SKEW, 256);
        stage_end(kb > 0);
        if (kb == 0 && t == 2) staged();
      }
      if (t == 0) mbar_wait(bars + 8 * B_HSFULL, 0);
      stage_begin();
#pragma unroll
      for (int kk = 0; kk < 4; kk++) wgmma_n128_ss_tb0(acc, desc(dhs + kk * (2 * HS_LBO >> 4), DHI_NONE), desc((dlo + kk * 2) | DLO_K, DHI_SW128), 1);
      stage_end(true);
      stage_begin();
#pragma unroll
      for (int kk = 0; kk < 4; kk++) wgmma_n128_ss_tb0(acc, desc(dhs + (4 + kk) * (2 * HS_LBO >> 4), DHI_NONE), desc((dlo + kk * 2) | DLO_K, DHI_SW128), 1);
      const int s_im = s;
      advance();
      stage_begin();
      wgmma_n128_ss_tb0(acc, desc(dhs + 8 * (2 * HS_LBO >> 4), DHI_NONE), desc(dlo | DLO_K, DHI_SW32), 1);
      stage_end(true);
      mbar_wait(bars + 8 * ((t & 1 ? B_RFULL : B_RFREE) + wg), t >> 1);
      if (t == 3) mbar_wait(bars + 8 * (B_SFREE + wg), 0);
      wg_wait<0>();
      release(s_im); release(prev);
      keep(acc);
      if (t & 1) {
        const uint32_t stg = sb + OFF_STG + wg * 32768 + so;
#pragma unroll
        for (int hh = 0; hh < 2; hh++) {
#pragma unroll
          for (int i = 4 * hh; i < 4 * hh + 4; i++) {
            uint32_t v[4];
            lds128(rcv + hh * 8192 + (i & 3) * 512, v[0], v[1], v[2], v[3]);
#pragma unroll
            for (int e = 0; e < 4; e++) { acc[8 * i + 2 * e] += bflo(v[e]); acc[8 * i + 2 * e + 1] += bfhi(v[e]); }
          }
          __syncwarp();
#pragma unroll
          for (int i = 8 * hh; i < 8 * hh + 8; i++) {
            const uint32_t a = stg + (i >> 2) * 8192 + (sx ^ ((i & 3) << 5));
            sts64f(a, acc[4 * i], acc[4 * i + 1]);
            sts64f(a + 1024, acc[4 * i + 2], acc[4 * i + 3]);
          }
        }
      } else {
        uint32_t ra, rb;
        asm("mapa.shared::cluster.u32 %0, %1, %2;" : "=r"(ra) : "r"(rcv), "r"(rank ^ 1));
        asm("mapa.shared::cluster.u32 %0, %1, %2;" : "=r"(rb) : "r"(bars + 8 * (B_RFULL + wg)), "r"(rank ^ 1));
#pragma unroll
        for (int i = 0; i < 8; i++)
          asm volatile("st.async.weak.shared::cluster.mbarrier::complete_tx::bytes.v4.b32 [%0], {%1,%2,%3,%4}, [%5];" ::"r"(ra + (i >> 2) * 8192 + (i & 3) * 512),
                       "r"(pack_bf16(acc[8 * i], acc[8 * i + 1])), "r"(pack_bf16(acc[8 * i + 2], acc[8 * i + 3])),
                       "r"(pack_bf16(acc[8 * i + 4], acc[8 * i + 5])), "r"(pack_bf16(acc[8 * i + 6], acc[8 * i + 7])), "r"(rb) : "memory");
      }
      STAMP(wg, 14 + t);
    }
    {
      float a2[32];
      if (SKEWB > 0 && wg == 1) bar_sync(NB_SKEW, 256);
      const uint32_t ph0 = ph;
#pragma unroll
      for (int kp = 0; kp < 5; kp++) {
        stage_begin();
#pragma unroll
        for (int kk = 0; kk < (kp < 4 ? 8 : 4); kk++) { const int i = (kp * 8 + kk) * 4; wgmma_n64_rs_tb1(a2, xa[i], xa[i + 1], xa[i + 2], xa[i + 3], desc((dlo + kk * 128) | DLO_MN, DHI_SW128), (kp | kk) != 0); }
        if (kp == 4) wgmma_n64_ss_tb0(a2, desc(dhs + 8 * (2 * HS_LBO >> 4), DHI_NONE), desc((dlo + 512) | DLO_K, DHI_SW32), 1);
        if (SKEWB > 0 && kp == 1 && wg == 0) bar_arrive(NB_SKEW, 256);
        stage_end(kp > 0);
        if (kp == 0) staged();
      }
      stage_begin();
#pragma unroll
      for (int kk = 0; kk < 8; kk++) wgmma_n64_ss_tb0(a2, desc(dhs + kk * (2 * HS_LBO >> 4), DHI_NONE), desc((dlo + (kk >> 2) * 512 + (kk & 3) * 2) | DLO_K, DHI_SW128), 1);
      wg_commit();
      mbar_wait(bars + 8 * (B_EMPTY + 4 + wg), ph0);
      wg_wait<0>();
      keep(a2);
      const uint32_t stg = sb + (4 + wg) * SLOT + so;
#pragma unroll
      for (int i = 0; i < 8; i++) {
        const uint32_t a = stg + (i >> 2) * 8192 + (sx ^ ((i & 3) << 5));
        sts64f(a, a2[4 * i], a2[4 * i + 1]);
        sts64f(a + 1024, a2[4 * i + 2], a2[4 * i + 3]);
      }
      staged();
      STAMP(wg, 18);
    }
  }
}

typedef CUresult (*EncodeFn)(CUtensorMap*, CUtensorMapDataType, cuuint32_t, void*, const cuuint64_t*, const cuuint64_t*, const cuuint32_t*,
                             const cuuint32_t*, CUtensorMapInterleave, CUtensorMapSwizzle, CUtensorMapL2promotion, CUtensorMapFloatOOBfill);

void map2d(EncodeFn enc, CUtensorMap* tm, const void* p, uint64_t cols, uint64_t rows, uint32_t bc, uint32_t br, CUtensorMapSwizzle sw) {
  cuuint64_t gd[2] = {cols, rows}, gs[1] = {cols * 2};
  cuuint32_t bd[2] = {bc, br}, es[2] = {1, 1};
  enc(tm, CU_TENSOR_MAP_DATA_TYPE_BFLOAT16, 2, (void*)p, gd, gs, bd, es, CU_TENSOR_MAP_INTERLEAVE_NONE, sw,
      sw == CU_TENSOR_MAP_SWIZZLE_128B ? CU_TENSOR_MAP_L2_PROMOTION_L2_128B : CU_TENSOR_MAP_L2_PROMOTION_NONE, CU_TENSOR_MAP_FLOAT_OOB_FILL_NONE);
}

}

extern "C" void kernel_launch(void* const* d_in, const int* in_sizes, int n_in, void* d_out, int out_size) {
  (void)in_sizes; (void)n_in; (void)out_size;
  static EncodeFn enc = nullptr;
  static void* gC = nullptr;
  if (!enc) {
    cudaDriverEntryPointQueryResult qr;
    cudaGetDriverEntryPoint("cuTensorMapEncodeTiled", (void**)&enc, cudaEnableDefault, &qr);
    cudaGetSymbolAddress(&gC, g_C);
    cudaFuncSetAttribute(fused_kernel, cudaFuncAttributeMaxDynamicSharedMemorySize, SMEM_BYTES);
  }
  Params prm;
  const CUtensorMapSwizzle S128 = CU_TENSOR_MAP_SWIZZLE_128B;
  map2d(enc, &prm.tx, d_in[0], kD, kS, 64, 64, S128);
  map2d(enc, &prm.tBre, d_in[3], kD, 576, 64, 72, S128);
  map2d(enc, &prm.tBim, d_in[4], kD, 576, 64, 72, S128);
  map2d(enc, &prm.tC, gC, 1152, kD, 64, 64, S128);
  map2d(enc, &prm.tC16, gC, 1152, kD, 16, 64, CU_TENSOR_MAP_SWIZZLE_32B);
  map2d(enc, &prm.tWg, d_in[10], kF, kD, 64, 64, S128);
  map2d(enc, &prm.tWu, d_in[11], kF, kD, 64, 64, S128);
  map2d(enc, &prm.tWd, d_in[12], kD, kF, 64, 64, S128);
  {
    cuuint64_t gd[4] = {kD, 2, 4, kS / 8}, gs[3] = {4 * kD * 4, kD * 4, 8 * kD * 4};
    cuuint32_t bd[4] = {32, 2, 4, 8}, es[4] = {1, 1, 1, 1};
    enc(&prm.tOut, CU_TENSOR_MAP_DATA_TYPE_FLOAT32, 4, d_out, gd, gs, bd, es, CU_TENSOR_MAP_INTERLEAVE_NONE, S128, CU_TENSOR_MAP_L2_PROMOTION_NONE,
        CU_TENSOR_MAP_FLOAT_OOB_FILL_NONE);
  }
  prm.lre = (const __nv_bfloat16*)d_in[1];
  prm.lim = (const __nv_bfloat16*)d_in[2];
  prm.cre = (const __nv_bfloat16*)d_in[5];
  prm.cim = (const __nv_bfloat16*)d_in[6];
  prm.wg = (const __nv_bfloat16*)d_in[10];
  prm.wu = (const __nv_bfloat16*)d_in[11];
  prm.wd = (const __nv_bfloat16*)d_in[12];
  prm.ldt = (const __nv_bfloat16*)d_in[7];
  prm.dskip = (const __nv_bfloat16*)d_in[8];
  prm.out = (float*)d_out;

  fused_kernel<<<128, 384, SMEM_BYTES, cudaStreamPerThread>>>(prm);
}
```

```cpp
#include <cuda_runtime.h>
#include <cuda.h>
#include <cuda_bf16.h>
#include <stdint.h>

namespace {

#define PACE 1
#define PACEP 100
#define XMODE 0
#define NOPF 0
#define PFD 12
#define SKEW 3
#define SKEWB 4

constexpr int kS = 2048, kD = 576, kF = 4608;
constexpr int NST = 6;
constexpr uint32_t SLOT = 16384;
constexpr uint32_t OFF_H = NST * SLOT;
constexpr uint32_t HS_LBO = 1040;
constexpr uint32_t HS_BYTES = 18 * HS_LBO;
constexpr uint32_t OFF_DUMP = OFF_H + 65536 - HS_BYTES;
constexpr uint32_t OFF_STG = OFF_H + SLOT;
constexpr uint32_t OFF_HS = OFF_STG + 65536;
constexpr uint32_t OFF_BAR = OFF_H + 131072;
constexpr uint32_t OFF_CONST = OFF_BAR + 384;
constexpr uint32_t SMEM_BYTES = OFF_CONST + 4 * 72 * 4 + 512;
static_assert(SMEM_BYTES <= 232448 && OFF_HS + 2 * HS_BYTES <= OFF_BAR, "smem");

enum { B_FULL = 0, B_EMPTY = NST + 1, B_X = 2 * NST + 2, B_X8 = B_X + 8, B_BU  , B_RING = B_BU + 4, B_SCAN, B_HFREE, B_HSFULL, B_CRDY, B_SFULL,
       B_SFREE = B_SFULL + 2, B_RFULL = B_SFREE + 2, B_RFREE = B_RFULL + 2, B_COUNT = B_RFREE + 2 };
static_assert(B_COUNT * 8 <= 384, "barriers");
enum { NB_SKEW = 1, NB_XDONE = 2  , NB_SCAN = 4, NB_DUMP = 5, NB_HFREE = 6 };
constexpr uint32_t OFF_BU0 = SLOT, OFF_BU1 = OFF_H, OFF_BU2 = OFF_H + 65536 + 19456;
static_assert(OFF_BU1 + 5 * 9216 <= OFF_DUMP && OFF_BU2 >= OFF_DUMP + 2 * HS_BYTES && OFF_BU2 + 5 * 9216 <= OFF_BAR, "Bu tiles");

struct __align__(64) Params {
  CUtensorMap tx, tBre, tBim, tWg, tWu, tWd, tC, tC16, tOut;
  const __nv_bfloat16 *lre, *lim, *bre, *bim, *cre, *cim, *ldt, *dskip, *wg, *wu, *wd;
  float* out;
};

__device__ unsigned g_epoch[128];
__device__ unsigned g_ready;
__device__ uint2 g_S[2][16][576];
__device__ __align__(128) uint8_t g_hs[128][2 * HS_BYTES];
__device__ __align__(128) uint32_t g_C[576][576];
#define STAMP(role, i)
#define STAMPP(i)
#define STAMP_DUMP(role)

__device__ __forceinline__ void wgmma_n72_rs_tb0(float (&d)[36], uint32_t a0, uint32_t a1, uint32_t a2, uint32_t a3, uint64_t db, int scale_d) {
  asm volatile("{\n.reg .pred p;\nsetp.ne.b32 p, %41, 0;\n"
    "wgmma.mma_async.sync.aligned.m64n72k16.f32.bf16.bf16 {"
    "%0, %1, %2, %3, %4, %5, %6, %7, %8, %9, %10, %11, %12, %13, %14, %15, "
    "%16, %17, %18, %19, %20, %21, %22, %23, %24, %25, %26, %27, %28, %29, %30, %31, "
    "%32, %33, %34, %35"
    "}, {%36, %37, %38, %39}, %40, p, 1, 1, 0;\n}\n"
    : "+f"(d[0]), "+f"(d[1]), "+f"(d[2]), "+f"(d[3]), "+f"(d[4]), "+f"(d[5]), "+f"(d[6]), "+f"(d[7]),
      "+f"(d[8]), "+f"(d[9]), "+f"(d[10]), "+f"(d[11]), "+f"(d[12]), "+f"(d[13]), "+f"(d[14]), "+f"(d[15]),
      "+f"(d[16]), "+f"(d[17]), "+f"(d[18]), "+f"(d[19]), "+f"(d[20]), "+f"(d[21]), "+f"(d[22]), "+f"(d[23]),
      "+f"(d[24]), "+f"(d[25]), "+f"(d[26]), "+f"(d[27]), "+f"(d[28]), "+f"(d[29]), "+f"(d[30]), "+f"(d[31]),
      "+f"(d[32]), "+f"(d[33]), "+f"(d[34]), "+f"(d[35])
    : "r"(a0), "r"(a1), "r"(a2), "r"(a3), "l"(db), "r"(scale_d));
}
__device__ __forceinline__ void wgmma_n128_rs_tb1(float (&d)[64], uint32_t a0, uint32_t a1, uint32_t a2, uint32_t a3, uint64_t db, int scale_d) {
  asm volatile("{\n.reg .pred p;\nsetp.ne.b32 p, %69, 0;\n"
    "wgmma.mma_async.sync.aligned.m64n128k16.f32.bf16.bf16 {"
    "%0, %1, %2, %3, %4, %5, %6, %7, %8, %9, %10, %11, %12, %13, %14, %15, "
    "%16, %17, %18, %19, %20, %21, %22, %23, %24, %25, %26, %27, %28, %29, %30, %31, "
    "%32, %33, %34, %35, %36, %37, %38, %39, %40, %41, %42, %43, %44, %45, %46, %47, "
    "%48, %49, %50, %51, %52, %53, %54, %55, %56, %57, %58, %59, %60, %61, %62, %63"
    "}, {%64, %65, %66, %67}, %68, p, 1, 1, 1;\n}\n"
    : "+f"(d[0]), "+f"(d[1]), "+f"(d[2]), "+f"(d[3]), "+f"(d[4]), "+f"(d[5]), "+f"(d[6]), "+f"(d[7]),
      "+f"(d[8]), "+f"(d[9]), "+f"(d[10]), "+f"(d[11]), "+f"(d[12]), "+f"(d[13]), "+f"(d[14]), "+f"(d[15]),
      "+f"(d[16]), "+f"(d[17]), "+f"(d[18]), "+f"(d[19]), "+f"(d[20]), "+f"(d[21]), "+f"(d[22]), "+f"(d[23]),
      "+f"(d[24]), "+f"(d[25]), "+f"(d[26]), "+f"(d[27]), "+f"(d[28]), "+f"(d[29]), "+f"(d[30]), "+f"(d[31]),
      "+f"(d[32]), "+f"(d[33]), "+f"(d[34]), "+f"(d[35]), "+f"(d[36]), "+f"(d[37]), "+f"(d[38]), "+f"(d[39]),
      "+f"(d[40]), "+f"(d[41]), "+f"(d[42]), "+f"(d[43]), "+f"(d[44]), "+f"(d[45]), "+f"(d[46]), "+f"(d[47]),
      "+f"(d[48]), "+f"(d[49]), "+f"(d[50]), "+f"(d[51]), "+f"(d[52]), "+f"(d[53]), "+f"(d[54]), "+f"(d[55]),
      "+f"(d[56]), "+f"(d[57]), "+f"(d[58]), "+f"(d[59]), "+f"(d[60]), "+f"(d[61]), "+f"(d[62]), "+f"(d[63])
    : "r"(a0), "r"(a1), "r"(a2), "r"(a3), "l"(db), "r"(scale_d));
}
__device__ __forceinline__ void wgmma_n128_ss_tb0(float (&d)[64], uint64_t da, uint64_t db, int scale_d) {
  asm volatile("{\n.reg .pred p;\nsetp.ne.b32 p, %66, 0;\n"
    "wgmma.mma_async.sync.aligned.m64n128k16.f32.bf16.bf16 {"
    "%0, %1, %2, %3, %4, %5, %6, %7, %8, %9, %10, %11, %12, %13, %14, %15, "
    "%16, %17, %18, %19, %20, %21, %22, %23, %24, %25, %26, %27, %28, %29, %30, %31, "
    "%32, %33, %34, %35, %36, %37, %38, %39, %40, %41, %42, %43, %44, %45, %46, %47, "
    "%48, %49, %50, %51, %52, %53, %54, %55, %56, %57, %58, %59, %60, %61, %62, %63"
    "}, %64, %65, p, 1, 1, 0, 0;\n}\n"
    : "+f"(d[0]), "+f"(d[1]), "+f"(d[2]), "+f"(d[3]), "+f"(d[4]), "+f"(d[5]), "+f"(d[6]), "+f"(d[7]),
      "+f"(d[8]), "+f"(d[9]), "+f"(d[10]), "+f"(d[11]), "+f"(d[12]), "+f"(d[13]), "+f"(d[14]), "+f"(d[15]),
      "+f"(d[16]), "+f"(d[17]), "+f"(d[18]), "+f"(d[19]), "+f"(d[20]), "+f"(d[21]), "+f"(d[22]), "+f"(d[23]),
      "+f"(d[24]), "+f"(d[25]), "+f"(d[26]), "+f"(d[27]), "+f"(d[28]), "+f"(d[29]), "+f"(d[30]), "+f"(d[31]),
      "+f"(d[32]), "+f"(d[33]), "+f"(d[34]), "+f"(d[35]), "+f"(d[36]), "+f"(d[37]), "+f"(d[38]), "+f"(d[39]),
      "+f"(d[40]), "+f"(d[41]), "+f"(d[42]), "+f"(d[43]), "+f"(d[44]), "+f"(d[45]), "+f"(d[46]), "+f"(d[47]),
      "+f"(d[48]), "+f"(d[49]), "+f"(d[50]), "+f"(d[51]), "+f"(d[52]), "+f"(d[53]), "+f"(d[54]), "+f"(d[55]),
      "+f"(d[56]), "+f"(d[57]), "+f"(d[58]), "+f"(d[59]), "+f"(d[60]), "+f"(d[61]), "+f"(d[62]), "+f"(d[63])
    : "l"(da), "l"(db), "r"(scale_d));
}
__device__ __forceinline__ void wgmma_n64_rs_tb1(float (&d)[32], uint32_t a0, uint32_t a1, uint32_t a2, uint32_t a3, uint64_t db, int scale_d) {
  asm volatile("{\n.reg .pred p;\nsetp.ne.b32 p, %37, 0;\n"
    "wgmma.mma_async.sync.aligned.m64n64k16.f32.bf16.bf16 {"
    "%0, %1, %2, %3, %4, %5, %6, %7, %8, %9, %10, %11, %12, %13, %14, %15, "
    "%16, %17, %18, %19, %20, %21, %22, %23, %24, %25, %26, %27, %28, %29, %30, %31"
    "}, {%32, %33, %34, %35}, %36, p, 1, 1, 1;\n}\n"
    : "+f"(d[0]), "+f"(d[1]), "+f"(d[2]), "+f"(d[3]), "+f"(d[4]), "+f"(d[5]), "+f"(d[6]), "+f"(d[7]),
      "+f"(d[8]), "+f"(d[9]), "+f"(d[10]), "+f"(d[11]), "+f"(d[12]), "+f"(d[13]), "+f"(d[14]), "+f"(d[15]),
      "+f"(d[16]), "+f"(d[17]), "+f"(d[18]), "+f"(d[19]), "+f"(d[20]), "+f"(d[21]), "+f"(d[22]), "+f"(d[23]),
      "+f"(d[24]), "+f"(d[25]), "+f"(d[26]), "+f"(d[27]), "+f"(d[28]), "+f"(d[29]), "+f"(d[30]), "+f"(d[31])
    : "r"(a0), "r"(a1), "r"(a2), "r"(a3), "l"(db), "r"(scale_d));
}
__device__ __forceinline__ void wgmma_n64_ss_tb0(float (&d)[32], uint64_t da, uint64_t db, int scale_d) {
  asm volatile("{\n.reg .pred p;\nsetp.ne.b32 p, %34, 0;\n"
    "wgmma.mma_async.sync.aligned.m64n64k16.f32.bf16.bf16 {"
    "%0, %1, %2, %3, %4, %5, %6, %7, %8, %9, %10, %11, %12, %13, %14, %15, "
    "%16, %17, %18, %19, %20, %21, %22, %23, %24, %25, %26, %27, %28, %29, %30, %31"
    "}, %32, %33, p, 1, 1, 0, 0;\n}\n"
    : "+f"(d[0]), "+f"(d[1]), "+f"(d[2]), "+f"(d[3]), "+f"(d[4]), "+f"(d[5]), "+f"(d[6]), "+f"(d[7]),
      "+f"(d[8]), "+f"(d[9]), "+f"(d[10]), "+f"(d[11]), "+f"(d[12]), "+f"(d[13]), "+f"(d[14]), "+f"(d[15]),
      "+f"(d[16]), "+f"(d[17]), "+f"(d[18]), "+f"(d[19]), "+f"(d[20]), "+f"(d[21]), "+f"(d[22]), "+f"(d[23]),
      "+f"(d[24]), "+f"(d[25]), "+f"(d[26]), "+f"(d[27]), "+f"(d[28]), "+f"(d[29]), "+f"(d[30]), "+f"(d[31])
    : "l"(da), "l"(db), "r"(scale_d));
}

__device__ __forceinline__ bool elect() {
  uint32_t p;
  asm volatile("{.reg .pred q; elect.sync _|q, 0xffffffff; selp.u32 %0,1,0,q;}" : "=r"(p));
  return p;
}
__device__ __forceinline__ void mbar_init(uint32_t bar, uint32_t cnt) { asm volatile("mbarrier.init.shared::cta.b64 [%0], %1;" ::"r"(bar), "r"(cnt) : "memory"); }
__device__ __forceinline__ void mbar_expect(uint32_t bar, uint32_t bytes) { asm volatile("mbarrier.arrive.expect_tx.shared::cta.b64 _, [%0], %1;" ::"r"(bar), "r"(bytes) : "memory"); }
__device__ __forceinline__ void mbar_arrive(uint32_t bar) { asm volatile("mbarrier.arrive.shared::cta.b64 _, [%0];" ::"r"(bar) : "memory"); }
__device__ __forceinline__ void mbar_arrive_cta(uint32_t bar, uint32_t cta) {
  asm volatile("{.reg .b32 ra; mapa.shared::cluster.u32 ra, %0, %1; mbarrier.arrive.shared::cluster.b64 _, [ra];}" ::"r"(bar), "r"(cta) : "memory");
}
__device__ __forceinline__ void mbar_wait(uint32_t bar, uint32_t parity) {
  asm volatile(
      "{\n.reg .pred p;\n.reg .u32 c, t;\n"
      "mbarrier.try_wait.parity.shared::cta.b64 p, [%0], %1;\n@p bra DONE;\n"
      "mov.u32 c, %%clock;\n"
      "LAB_WAIT:\nmbarrier.try_wait.parity.shared::cta.b64 p, [%0], %1;\n@p bra DONE;\n"
      "mov.u32 t, %%clock;\nsub.u32 t, t, c;\nsetp.lt.u32 p, t, 0x40000000;\n@p bra LAB_WAIT;\ntrap;\nDONE:\n}" ::"r"(bar), "r"(parity) : "memory");
}
__device__ __forceinline__ void bar_sync(int id, int n) { asm volatile("bar.sync %0, %1;" ::"r"(id), "r"(n) : "memory"); }
__device__ __forceinline__ void bar_arrive(int id, int n) { asm volatile("bar.arrive %0, %1;" ::"r"(id), "r"(n) : "memory"); }
__device__ __forceinline__ void wg_fence() { asm volatile("wgmma.fence.sync.aligned;" ::: "memory"); }
__device__ __forceinline__ void wg_commit() { asm volatile("wgmma.commit_group.sync.aligned;" ::: "memory"); }
template <int N> __device__ __forceinline__ void wg_wait() { asm volatile("wgmma.wait_group.sync.aligned %0;" ::"n"(N) : "memory"); }
__device__ __forceinline__ void tma2d(uint32_t dst, const CUtensorMap* tm, uint32_t bar, int c0, int c1) {
  asm volatile("cp.async.bulk.tensor.2d.shared::cluster.global.mbarrier::complete_tx::bytes [%0], [%1,{%3,%4}], [%2];" ::"r"(dst), "l"(tm), "r"(bar), "r"(c0), "r"(c1) : "memory");
}
__device__ __forceinline__ void tma2d_mc(uint32_t dst, const CUtensorMap* tm, uint32_t bar, int c0, int c1) {
  asm volatile("cp.async.bulk.tensor.2d.shared::cluster.global.mbarrier::complete_tx::bytes.multicast::cluster [%0], [%1,{%3,%4}], [%2], %5;" ::"r"(dst), "l"(tm), "r"(bar), "r"(c0), "r"(c1), "h"((uint16_t)3) : "memory");
}
__device__ __forceinline__ void l2_prefetch(const void* p, uint32_t bytes) {
  asm volatile("cp.async.bulk.prefetch.L2.global [%0], %1;" ::"l"(p), "r"(bytes) : "memory");
}
__device__ __forceinline__ void l2_prefetch_line(const void* p) { asm volatile("prefetch.global.L2 [%0];" ::"l"(p)); }
__device__ __forceinline__ void tma_prefetch2d(const CUtensorMap* tm, int c0, int c1) {
  asm volatile("cp.async.bulk.prefetch.tensor.2d.L2.global.tile [%0,{%1,%2}];" ::"l"(tm), "r"(c0), "r"(c1) : "memory");
}
__device__ __forceinline__ uint64_t desc(uint32_t lo, uint32_t hi) { return ((uint64_t)hi << 32) | lo; }
constexpr uint32_t DHI_SW128 = (1024 >> 4) | (1u << 30);
constexpr uint32_t DHI_NONE = (128 >> 4);
constexpr uint32_t DHI_SW32 = (256 >> 4) | (3u << 30);
constexpr uint32_t DLO_HS = (HS_LBO >> 4) << 16;
constexpr uint32_t DLO_MN = (8192 >> 4) << 16;
constexpr uint32_t DLO_K = 1u << 16;
__device__ __forceinline__ float tanh_fast(float x) { float y; asm("tanh.approx.f32 %0, %1;" : "=f"(y) : "f"(x)); return y; }
__device__ __forceinline__ uint32_t pack_bf16(float lo, float hi) { uint32_t r; asm("cvt.rn.bf16x2.f32 %0, %1, %2;" : "=r"(r) : "f"(hi), "f"(lo)); return r; }
__device__ __forceinline__ float rbf(float x) { return __bfloat162float(__float2bfloat16_rn(x)); }
__device__ __forceinline__ void mma16816(float (&c)[4], uint32_t a0, uint32_t a1, uint32_t a2, uint32_t a3, uint32_t b0, uint32_t b1) {
  asm volatile("mma.sync.aligned.m16n8k16.row.col.f32.bf16.bf16.f32 {%0,%1,%2,%3}, {%4,%5,%6,%7}, {%8,%9}, {%0,%1,%2,%3};"
               : "+f"(c[0]), "+f"(c[1]), "+f"(c[2]), "+f"(c[3]) : "r"(a0), "r"(a1), "r"(a2), "r"(a3), "r"(b0), "r"(b1));
}
__device__ __forceinline__ void sts128(uint32_t a, uint32_t x, uint32_t y, uint32_t z, uint32_t w) {
  asm volatile("st.shared.v4.b32 [%0], {%1,%2,%3,%4};" ::"r"(a), "r"(x), "r"(y), "r"(z), "r"(w) : "memory");
}
__device__ __forceinline__ void sts64f(uint32_t a, float x, float y) { asm volatile("st.shared.v2.f32 [%0], {%1,%2};" ::"r"(a), "f"(x), "f"(y) : "memory"); }
__device__ __forceinline__ float2 lds64f(uint32_t a) { float2 v; asm volatile("ld.shared.v2.f32 {%0,%1}, [%2];" : "=f"(v.x), "=f"(v.y) : "r"(a) : "memory"); return v; }
__device__ __forceinline__ uint32_t lds32(uint32_t a) { uint32_t v; asm volatile("ld.shared.b32 %0, [%1];" : "=r"(v) : "r"(a) : "memory"); return v; }
__device__ __forceinline__ void lds128(uint32_t a, uint32_t& x, uint32_t& y, uint32_t& z, uint32_t& w) {
  asm volatile("ld.shared.v4.b32 {%0,%1,%2,%3}, [%4];" : "=r"(x), "=r"(y), "=r"(z), "=r"(w) : "r"(a) : "memory");
}
__device__ __forceinline__ float bflo(uint32_t v) { return __uint_as_float(v << 16); }
__device__ __forceinline__ float bfhi(uint32_t v) { return __uint_as_float(v & 0xffff0000u); }
__device__ __forceinline__ uint32_t lds32v(uint32_t a) { uint32_t v; asm volatile("ld.volatile.shared.b32 %0, [%1];" : "=r"(v) : "r"(a) : "memory"); return v; }
__device__ __forceinline__ float lds32f(uint32_t a) { float v; asm volatile("ld.shared.f32 %0, [%1];" : "=f"(v) : "r"(a) : "memory"); return v; }
template <int N> __device__ __forceinline__ void keep(float (&a)[N]) {
#pragma unroll
  for (int i = 0; i < N; i++) asm volatile("" : "+f"(a[i])::"memory");
}

__global__ void __cluster_dims__(2, 1, 1) __launch_bounds__(384, 1) fused_kernel(const __grid_constant__ Params prm) {
  extern __shared__ __align__(1024) uint8_t smem[];
  const int warp = __shfl_sync(0xffffffffu, threadIdx.x >> 5, 0);
  const uint32_t sb0 = (uint32_t)__cvta_generic_to_shared(smem);
  const int j = blockIdx.x & 7, m = blockIdx.x >> 3, rank = j & 1;
  auto smem_base = [&]() { return __shfl_sync(0xffffffffu, sb0 + (threadIdx.x & 31), 0); };
  STAMP(0, 31);

  if (warp == 8 || warp == 9) {
    if (elect()) {
      if (warp == 8) {
#pragma unroll
        for (int i = 0; i < B_COUNT / 2; i++) mbar_init(sb0 + OFF_BAR + 8 * i, (i >= B_EMPTY && i < B_X) ? 2 : 1);
      } else {
#pragma unroll
        for (int i = B_COUNT / 2; i < B_COUNT; i++) mbar_init(sb0 + OFF_BAR + 8 * i, (i >= B_SFULL && i < B_SFULL + 2) ? 4 : i == B_RING ? 2 : 1);
        if (sb0 & 1023) __trap();
      }
      asm volatile("fence.mbarrier_init.release.cluster;" ::: "memory");
    }
    __syncwarp();
  }
  STAMPP(0);
  asm volatile("barrier.cluster.arrive.relaxed.aligned;\nbarrier.cluster.wait.aligned;" ::: "memory");
  STAMPP(1);

  if (warp == 0) {
    const uint32_t xb = sb0 + OFF_BAR;
    const bool e = elect();
    if (e) { mbar_expect(xb + 8 * B_X8, 16384); tma2d_mc(sb0 + rank * 8192, &prm.tx, xb + 8 * B_X8, 512, m * 128 + rank * 64); }
#pragma unroll
    for (int i = 0; i < 8; i++) {
      const int w = i >> 2, kb = (i & 3) * 2 + rank;
      if (e) { mbar_expect(xb + 8 * (B_X + i), 16384); tma2d_mc(sb0 + OFF_H + w * 65536 + kb * 8192, &prm.tx, xb + 8 * (B_X + i), kb * 64, m * 128 + w * 64); }
    }
    __syncwarp();
    STAMP(0, 20);
  }

  if (warp >= 8) {
    asm volatile("setmaxnreg.dec.sync.aligned.u32 24;");
    if (warp == 8) {
      const uint32_t sb = smem_base(), bars = sb + OFF_BAR;
      bool e;
      int s = 0, nst = NST; uint32_t ph = 1;
      uint32_t dst, fb;
      auto acquire = [&](uint32_t bytes) {
        mbar_wait(bars + 8 * (B_EMPTY + s), ph);
        fb = bars + 8 * (B_FULL + s); dst = sb + s * SLOT;
        e = elect();
        if (e) mbar_expect(fb, bytes);
        if (++s == nst) { s = 0; ph ^= 1; }
      };
      auto box = [&](const CUtensorMap* t, uint32_t o, int a, int b) { if (e) tma2d(dst + o, t, fb, a, b); };
      const int lane = threadIdx.x & 31;
      const char* pf = lane < 8 ? (const char*)(lane & 4 ? prm.wu : prm.wg) + ((size_t)(m * 4 + (lane & 3)) * kF + j * 576) * 2
                                : (const char*)prm.wd + (size_t)j * 576 * 1152 + (m * 324 + (lane & 3)) * 128;
      int pk = 0, pleft = 81;
      auto prefetch = [&]() {
        if (pleft > 0) {
          if (lane < 12 && !(NOPF & 2)) l2_prefetch_line(pf);
          pf += lane < 8 ? (pk == 8 ? 128 - 8 * 64 * kF * 2 : 64 * kF * 2) : 512;
          pk = pk == 8 ? 0 : pk + 1;
          pleft--;
        }
      };
      STAMPP(3);
      e = elect();
#pragma unroll 1
      for (int kb = 0; kb < 8; kb++) {
        fb = bars + 8 * (B_BU + (kb >> 2));
        if (e) { if ((kb & 3) == 0) mbar_expect(fb, 4 * 9216); tma2d(sb + OFF_BU0 + kb * 9216, &prm.tBre, fb, kb * 64, j * 72); }
      }
      STAMPP(4);
      bar_sync(NB_XDONE, 160);
      fb = bars + 8 * (B_BU + 2);
      if (e) { mbar_expect(fb, 5 * 9216); tma2d(sb + OFF_BU1, &prm.tBre, fb, 512, j * 72); }
#pragma unroll 1
      for (int kb = 0; kb < 4; kb++) if (e) tma2d(sb + OFF_BU1 + (kb + 1) * 9216, &prm.tBim, fb, kb * 64, j * 72);
      for (int i = 0; i < PFD / 2; i++) prefetch();
      bar_sync(NB_XDONE + 1, 160);
      fb = bars + 8 * (B_BU + 3);
      if (e) mbar_expect(fb, 5 * 9216);
#pragma unroll 1
      for (int kb = 4; kb < 9; kb++) if (e) tma2d(sb + OFF_BU2 + (kb - 4) * 9216, &prm.tBim, fb, kb * 64, j * 72);
      for (int i = PFD / 2; i < PFD; i++) prefetch();
      STAMPP(5);
      mbar_wait(bars + 8 * B_RING, 0);
      STAMPP(6);
      for (int c = 0; c < 9; c++) {
        const int col = j * 576 + c * 64;
#pragma unroll 1
        for (int kb = 0; kb < 9; kb++) { acquire(16384); box(&prm.tWg, 0, col, kb * 64); box(&prm.tWu, 8192, col, kb * 64); prefetch(); }
      }
      for (int t = 0; t < 4; t++) {
        const int n0 = ((rank ^ t ^ 1) & 1) * 256 + (((t >> 1) ^ (j >> 1)) & 1) * 128;
        for (int kb = 0; kb < 9; kb++) {
          if (kb == 4) nst = NST + 1;
          acquire(16384); box(&prm.tWd, 0, n0, j * 576 + kb * 64); box(&prm.tWd, 8192, n0 + 64, j * 576 + kb * 64);
        }
        if (t == 0) {
          mbar_wait(bars + 8 * B_HFREE, 0);
          mbar_wait(bars + 8 * B_CRDY, 0);
          asm volatile("fence.proxy.async.global;" ::: "memory");
        }
        acquire(16384); box(&prm.tC, 0, j * 144, n0); box(&prm.tC, 8192, j * 144, n0 + 64);
        acquire(16384); box(&prm.tC, 0, j * 144 + 64, n0); box(&prm.tC, 8192, j * 144 + 64, n0 + 64);
        acquire(4096); box(&prm.tC16, 0, j * 144 + 128, n0); box(&prm.tC16, 2048, j * 144 + 128, n0 + 64);
      }
      for (int kp = 0; kp < 4; kp++) { acquire(16384); box(&prm.tWd, 0, 512, j * 576 + kp * 128); box(&prm.tWd, 8192, 512, j * 576 + kp * 128 + 64); }
      acquire(8192 + 2048); box(&prm.tWd, 0, 512, j * 576 + 512); box(&prm.tC16, 8192, j * 144 + 128, 512);
      acquire(16384); box(&prm.tC, 0, j * 144, 512); box(&prm.tC, 8192, j * 144 + 64, 512);
      STAMP_DUMP(3);
    } else {
      const uint32_t sb = smem_base(), bars = sb + OFF_BAR;
      const int p = min((int)threadIdx.x - 288, 71);
      if (threadIdx.x < 288 + 8) asm volatile("prefetch.tensormap [%0];" ::"l"(&prm.tBre + (threadIdx.x - 288)) : "memory");
      if (warp == 10 && !(NOPF & 1)) {
        const int l = threadIdx.x & 31;
        const char* q = (const char*)(l & 1 ? prm.bim : prm.bre) + (size_t)blockIdx.x * 5184;
        mbar_wait(bars + 8 * B_X8, 0);
#pragma unroll
        for (int i = 0; i < 3; i++) if (i * 16 + (l >> 1) < 42) l2_prefetch_line(q + min((i * 16 + (l >> 1)) * 128, 5183));
      }
      const unsigned epoch = *(volatile unsigned*)&g_epoch[blockIdx.x];
      float ar, ai;
      {
        const int pg = j * 72 + p;
        const float lr = __bfloat162float(prm.lre[pg]), li = __bfloat162float(prm.lim[pg]);
        const float dt = rbf(expf(__bfloat162float(prm.ldt[pg])));
        const float ea = expf(dt * lr);
        float sn, cs;
        sincosf(dt * li, &sn, &cs);
        ar = ea * cs; ai = ea * sn;
        float br = ar, bi = ai;
#pragma unroll
        for (int k = 0; k < 7; k++) { const float t = br * br - bi * bi; bi = 2.f * br * bi; br = t; }
        const float nr = ar - 1.f, den = 4.f / (lr * lr + li * li);
        float* cp = (float*)(smem + OFF_CONST) + p;
        cp[0] = (nr * lr + ai * li) * den; cp[72] = (ai * lr - nr * li) * den; cp[144] = br; cp[216] = bi;
      }
      STAMP(2, 0);
      bar_sync(NB_DUMP, 352);
      {
        float hr = 0.f, hi = 0.f;
        uint32_t a0 = sb + OFF_DUMP + (p >> 2) * HS_LBO + (p & 3) * 4;
        asm volatile("" : "+r"(a0));
        auto step = [&](uint32_t v) {
          const float nr = fmaf(ar, hr, fmaf(-ai, hi, bflo(v)));
          hi = fmaf(ar, hi, fmaf(ai, hr, bfhi(v))); hr = nr;
        };
        if (m < 15) {
#pragma unroll 1
          for (int tb = 0; tb < 16; tb++) {
            const uint32_t a = a0 + tb * 128 + (tb >> 3) * (HS_BYTES - 1024);
            uint32_t v[8];
#pragma unroll
            for (int k = 0; k < 8; k++) v[k] = lds32(a + k * 16);
#pragma unroll
            for (int k = 0; k < 8; k++) step(v[k]);
          }
          asm volatile("st.relaxed.gpu.global.v2.b32 [%0], {%1,%2};" ::"l"(&g_S[epoch & 1][m][j * 72 + p]), "r"(~__float_as_uint(hr)), "r"(~__float_as_uint(hi)) : "memory");
          g_S[(epoch & 1) ^ 1][m][j * 72 + p] = make_uint2(0u, 0u);
        }
        STAMP(2, 4);
        {
          const float br = lds32f(sb + OFF_CONST + 576 + p * 4), bi = lds32f(sb + OFF_CONST + 864 + p * 4);
          hr = 0.f; hi = 0.f;
          const uint2* sp = &g_S[epoch & 1][0][j * 72 + p];
#pragma unroll 1
          for (int left = m; left > 0; left -= 4, sp += 4 * 576) {
            uint32_t v[4][2];
            int spins = 0;
            uint32_t ok;
            do {
#pragma unroll
              for (int k = 0; k < 4; k++) {
                v[k][0] = v[k][1] = 0xffffffffu;
                if (k < left) asm volatile("ld.relaxed.gpu.global.v2.b32 {%0,%1}, [%2];" : "=r"(v[k][0]), "=r"(v[k][1]) : "l"(sp + k * 576) : "memory");
              }
              ok = min(min(min(v[0][0], v[0][1]), min(v[1][0], v[1][1])), min(min(v[2][0], v[2][1]), min(v[3][0], v[3][1])));
              if (++spins > (1 << 22)) __trap();
            } while (ok == 0u);
#pragma unroll
            for (int k = 0; k < 4; k++)
              if (k < left) { const float nr = fmaf(br, hr, fmaf(-bi, hi, __uint_as_float(~v[k][0]))); hi = fmaf(br, hi, fmaf(bi, hr, __uint_as_float(~v[k][1]))); hr = nr; }
          }
        }
        STAMP(2, 5);
#pragma unroll 1
        for (int tb = 0; tb < 16; tb++) {
          const uint32_t a = a0 + tb * 128 + (tb >> 3) * (HS_BYTES - 1024);
          uint32_t v[8];
#pragma unroll
          for (int k = 0; k < 8; k++) v[k] = lds32(a + k * 16);
#pragma unroll
          for (int k = 0; k < 8; k++) {
            step(v[k]);
            asm volatile("st.shared.b32 [%0], %1;" ::"r"(a + k * 16), "r"(pack_bf16(hr, hi)) : "memory");
          }
        }
        asm volatile("fence.proxy.async.shared::cta;" ::: "memory");
      }
      STAMP(2, 6);
      bar_sync(NB_SCAN, 96);
      if (warp == 9) {
        if (elect()) {
#pragma unroll 1
          for (uint32_t o = 0; o < 2 * HS_BYTES; o += 4 * HS_LBO) {
            asm volatile("cp.async.bulk.global.shared::cta.bulk_group [%0], [%1], %2;" ::"l"(&g_hs[blockIdx.x][o]), "r"(sb + OFF_DUMP + o), "r"(4 * HS_LBO) : "memory");
            asm volatile("cp.async.bulk.commit_group;\ncp.async.bulk.wait_group.read 0;" ::: "memory");
            if (PACEP) __nanosleep(PACEP);
          }
          mbar_arrive(bars + 8 * B_SCAN);
        }
        __syncwarp();
        STAMP(2, 2);
      }
      {
        const int r0 = p >= 36, cp = p - r0 * 36;
        const float2 cr = lds64f(sb + OFF_CONST + cp * 8), ci = lds64f(sb + OFF_CONST + 288 + cp * 8);
        uint32_t o = (m * 36 + r0) * 288 + j * 36 + cp;
#pragma unroll 1
        for (int it = 0; it < 6; it++, o += 6 * 288) {
          uint32_t vr[3], vi[3];
#pragma unroll
          for (int k = 0; k < 3; k++) { vr[k] = __ldg((const uint32_t*)prm.cre + o + k * 576); vi[k] = __ldg((const uint32_t*)prm.cim + o + k * 576); }
#pragma unroll
          for (int k = 0; k < 3; k++) {
            const float r0v = bflo(vr[k]), i0v = bflo(vi[k]), r1v = bfhi(vr[k]), i1v = bfhi(vi[k]);
            ((uint2*)&g_C[0][0])[o + k * 576] = make_uint2(pack_bf16(r0v * cr.x - i0v * ci.x, -r0v * ci.x - i0v * cr.x), pack_bf16(r1v * cr.y - i1v * ci.y, -r1v * ci.y - i1v * cr.y));
          }
        }
      }
      bar_sync(NB_SCAN, 96);
      STAMP(2, 3);
      if (warp == 9) {
        if (elect()) {
          __threadfence();
          asm volatile("red.release.gpu.global.add.u32 [%0], 1;" ::"l"(&g_ready) : "memory");
          g_epoch[blockIdx.x] = epoch + 1u;
          asm volatile("cp.async.bulk.wait_group 0;" ::: "memory");
        }
        __syncwarp();
        STAMP(2, 7);
        bar_sync(NB_HFREE, 288);
        if (elect()) {
          mbar_arrive(bars + 8 * B_HFREE);
          mbar_expect(bars + 8 * B_HSFULL, 2 * HS_BYTES);
          asm volatile("cp.async.bulk.shared::cluster.global.mbarrier::complete_tx::bytes [%0], [%1], %2, [%3];" ::"r"(sb + OFF_HS),
                       "l"(&g_hs[blockIdx.x][0]), "r"(2 * HS_BYTES), "r"(bars + 8 * B_HSFULL) : "memory");
          for (int w = 0; w < 2; w++) mbar_arrive_cta(bars + 8 * (B_RFREE + w), rank ^ 1);
        }
        __syncwarp();
        STAMP_DUMP(2);
      } else {
        const int w = warp - 10;
        {
          const unsigned target = 128u * (epoch + 1u);
          int spins = 0;
          unsigned v;
          do {
            asm volatile("ld.acquire.gpu.global.u32 %0, [%1];" : "=r"(v) : "l"(&g_ready) : "memory");
            if (++spins > (1 << 22)) __trap();
          } while ((int)(v - target) < 0);
          asm volatile("fence.proxy.async.global;" ::: "memory");
          if (w == 0 && elect()) mbar_arrive(bars + 8 * B_CRDY);
        }
        const uint32_t stg = sb + OFF_STG + w * 32768;
#pragma unroll 1
        for (int t = 0; t < 5; t++) {
          if (t == 0 || t == 2) {
            if (elect()) mbar_expect(bars + 8 * (B_RFULL + w), 16384);
            mbar_wait(bars + 8 * (B_SFULL + w), 0);
            mbar_wait(bars + 8 * (B_RFREE + w), t >> 1);
            if (elect())
              asm volatile("{.reg .b32 ra, rb; mapa.shared::cluster.u32 ra, %0, %3; mapa.shared::cluster.u32 rb, %2, %3;\n"
                           "cp.async.bulk.shared::cluster.shared::cta.mbarrier::complete_tx::bytes [ra], [%1], 16384, [rb];}" ::"r"(stg + 16384),
                           "r"(stg), "r"(bars + 8 * (B_RFULL + w)), "r"(rank ^ 1) : "memory");
            mbar_wait(bars + 8 * (B_RFULL + w), t >> 1);
            if (elect()) mbar_arrive_cta(bars + 8 * (B_SFREE + w), rank ^ 1);
          } else {
            mbar_wait(bars + 8 * (B_SFULL + w), t & 1);
            const int n0 = t < 4 ? rank * 256 + (((t >> 1) ^ (j >> 1)) & 1) * 128 : 512;
            const uint32_t src = t < 4 ? stg : sb + (3 + w) * SLOT;
            if (elect()) {
#pragma unroll 1
              for (int b = 0; b < (t < 4 ? 4 : 2); b++) {
                asm volatile("cp.reduce.async.bulk.tensor.4d.global.shared::cta.add.tile.bulk_group [%0, {%1,%2,%2,%3}], [%4];" ::"l"(&prm.tOut), "r"(n0 + b * 32), "r"(0),
                             "r"(m * 16 + w * 8), "r"(src + b * 8192) : "memory");
                asm volatile("cp.async.bulk.commit_group;" ::: "memory");
                if (PACE && t == 1) { asm volatile("cp.async.bulk.wait_group.read 0;" ::: "memory"); if (PACE > 1) __nanosleep(PACE); }
              }
              if (t == 1) {
                asm volatile("cp.async.bulk.wait_group.read 0;" ::: "memory");
                mbar_arrive(bars + 8 * (B_SFREE + w));
                mbar_arrive_cta(bars + 8 * (B_RFREE + w), rank ^ 1);
              }
              if (t == 4) asm volatile("cp.async.bulk.wait_group.read 0;" ::: "memory");
            }
          }
          __syncwarp();
        }
      }
    }
  } else {
    asm volatile("setmaxnreg.inc.sync.aligned.u32 240;");
    const uint32_t sb = smem_base(), bars = sb + OFF_BAR;
    const int wg = warp >> 2, w4 = warp & 3;
    const int lane = threadIdx.x & 31, g = lane >> 2, q = lane & 3;
    const uint32_t hw = sb + OFF_H + wg * 65536;
    STAMP(wg, 0);

    int s = 0, nst = NST; uint32_t ph = 0;
    auto release = [&](int st) { if (w4 == 0) { if (elect()) mbar_arrive(bars + 8 * (B_EMPTY + st)); } };
    const uint32_t dring = (sb & 0x3FFFF) >> 4;
    uint32_t dlo; int prev = 0;
    auto stage_begin = [&]() { mbar_wait(bars + 8 * (B_FULL + s), ph); dlo = dring + s * (SLOT >> 4); wg_fence(); };
    auto advance = [&]() { if (++s == nst) { s = 0; ph ^= 1; } };
    auto stage_end = [&](bool rel) {
      wg_commit();
      if (rel) { wg_wait<1>(); release(prev); }
      prev = s;
      advance();
    };

    uint32_t xa[144];
    uint32_t xr[18], dk[9];
    uint32_t rh[2], cc[2];
#pragma unroll
    for (int i = 0; i < 9; i++) {
      dk[i] = __ldg((const uint32_t*)(prm.dskip + j * 72 + i * 8 + q * 2));
      asm("add.rn.bf16x2 %0, %0, %0;" : "+r"(dk[i]));
    }
    {
      const int r = w4 * 16 + (lane & 7) + ((lane >> 3) & 1) * 8;
      const uint32_t ro = r * 128, cx = ((lane >> 4) ^ (lane & 7)) << 4;
      float s1[2][4] = {}, s2[2][4] = {};
      auto load = [&](int kb, uint32_t base) {
#pragma unroll
        for (int kk = 0; kk < 4; kk++) {
          const int i = (kb * 4 + kk) * 4;
          asm volatile("ldmatrix.sync.aligned.m8n8.x4.shared.b16 {%0,%1,%2,%3}, [%4];"
                       : "=r"(xa[i]), "=r"(xa[i + 1]), "=r"(xa[i + 2]), "=r"(xa[i + 3]) : "r"(base + ro + (cx ^ (kk << 5))) : "memory");
        }
      };
      auto sums = [&](int kb) {
#pragma unroll
        for (int kk = 0; kk < 4; kk++) {
          const int i = (kb * 4 + kk) * 4;
          uint32_t sq[4];
#pragma unroll
          for (int e = 0; e < 4; e++) asm("mul.rn.bf16x2 %0, %1, %1;" : "=r"(sq[e]) : "r"(xa[i + e]));
          mma16816(s1[kk & 1], xa[i], xa[i + 1], xa[i + 2], xa[i + 3], 0x3f803f80u, 0x3f803f80u);
          mma16816(s2[kk & 1], sq[0], sq[1], sq[2], sq[3], 0x3f803f80u, 0x3f803f80u);
        }
      };
      mbar_wait(bars + 8 * B_X8, 0);
      STAMP(wg, 21);
      load(8, sb + wg * 8192);
#pragma unroll
      for (int kp = 0; kp < 4; kp++) {
        mbar_wait(bars + 8 * (B_X + wg * 4 + kp), 0);
        STAMP(wg, 22 + kp);
        load(2 * kp, hw + 2 * kp * 8192);
        load(2 * kp + 1, hw + (2 * kp + 1) * 8192);
        if (kp == 0) sums(8); else { sums(2 * kp - 2); sums(2 * kp - 1); }
      }
#pragma unroll
      for (int i = 0; i < 9; i++) {
        const int c8 = j * 9 + i, kb = c8 >> 3;
        const uint32_t a = (kb < 8 ? hw + kb * 8192 : sb + wg * 8192) + (w4 * 16 + g) * 128 + (((c8 & 7) ^ g) << 4) + q * 4;
        xr[2 * i] = lds32(a); xr[2 * i + 1] = lds32(a + 1024);
      }
      bar_arrive(NB_XDONE + wg, 160);
      sums(6); sums(7);
      STAMP(wg, 1);
#pragma unroll
      for (int e = 0; e < 2; e++) {
        const float mu = (s1[0][2 * e] + s1[1][2 * e]) * (1.f / kD);
        const float var = fmaxf(fmaf(-mu, mu, (s2[0][2 * e] + s2[1][2 * e]) * (1.f / kD)), 0.f);
        float sd, r;
        asm("sqrt.approx.f32 %0, %1;" : "=f"(sd) : "f"(rbf(rbf(var) + 1e-5f)));
        asm("rcp.approx.ftz.f32 %0, %1;" : "=f"(r) : "f"(rbf(sd)));
        r = rbf(0.5f * r);
        rh[e] = pack_bf16(r, r); cc[e] = pack_bf16(-mu * r, -mu * r);
      }
    }
    STAMP(wg, 2);

    auto normalise = [&](int kb) {
#pragma unroll
      for (int i = 0; i < 16; i++) asm("fma.rn.bf16x2 %0, %0, %1, %2;" : "+r"(xa[16 * kb + (i >> 3) + 2 * (i & 7)]) : "r"(rh[i >> 3]), "r"(cc[i >> 3]));
    };
    {
      normalise(0);
      float ab[36];
      uint32_t rp[18];
      float* op = prm.out + (size_t)(m * 128 + wg * 64 + w4 * 16 + g) * kD + j * 72 + q * 2;
      auto residual = [&](int i) {
#pragma unroll
        for (int e = 0; e < 2; e++) {
          uint32_t t;
          asm("fma.rn.bf16x2 %0, %1, %2, %3;" : "=r"(t) : "r"(xr[2 * i + e]), "r"(rh[e]), "r"(cc[e]));
          asm("mul.rn.bf16x2 %0, %0, %1;" : "+r"(t) : "r"(dk[i]));
          *(float2*)(op + e * 8 * kD + i * 8) = make_float2(bflo(xr[2 * i + e]) + bflo(t), bfhi(xr[2 * i + e]) + bfhi(t));
        }
      };
      auto bu = [&](int kb, uint32_t off) {
        wg_fence();
#pragma unroll
        for (int kk = 0; kk < 4; kk++) { const int i = (kb * 4 + kk) * 4; wgmma_n72_rs_tb0(ab, xa[i], xa[i + 1], xa[i + 2], xa[i + 3], desc((dring + (off >> 4) + kk * 2) | DLO_K, DHI_SW128), (kb | kk) != 0); }
        wg_commit();
      };
#pragma unroll
      for (int kb = 0; kb < 9; kb++) {
        if ((kb & 3) == 0) mbar_wait(bars + 8 * (B_BU + (kb >> 2)), 0);
        bu(kb, kb < 8 ? OFF_BU0 + kb * 9216 : OFF_BU1);
        if (kb < 8) normalise(kb + 1);
        if ((kb & 1) == 0) residual(kb >> 1);
      }
      wg_wait<0>();
      if (w4 == 0) { if (elect()) mbar_arrive(bars + 8 * B_RING); }
      STAMP(wg, 19);
      keep(ab);
#pragma unroll
      for (int i = 0; i < 18; i++) rp[i] = pack_bf16(ab[2 * i], ab[2 * i + 1]);
#pragma unroll
      for (int kb = 0; kb < 9; kb++) {
        if (kb == 4) mbar_wait(bars + 8 * (B_BU + 3), 0);
        bu(kb, kb < 4 ? OFF_BU1 + (kb + 1) * 9216 : OFF_BU2 + (kb - 4) * 9216);
        if ((kb & 1) == 0 && kb < 8) residual(5 + (kb >> 1));
      }
      wg_wait<0>();
      keep(ab);
      const uint32_t da = sb + OFF_DUMP + wg * HS_BYTES + (q >> 1) * HS_LBO + (w4 * 16 + g) * 16 + (q & 1) * 8;
#pragma unroll
      for (int i = 0; i < 18; i++) {
        const uint32_t ip = pack_bf16(ab[2 * i], ab[2 * i + 1]);
        asm volatile("st.shared.v2.b32 [%0], {%1,%2};" ::"r"(da + (i >> 1) * 2 * HS_LBO + (i & 1) * 128), "r"(__byte_perm(rp[i], ip, 0x5410)), "r"(__byte_perm(rp[i], ip, 0x7632)) : "memory");
      }
      bar_arrive(NB_DUMP, 352);
    }
    STAMP(wg, 3);

    float acc[64];
    {
      const uint32_t ha = hw + (threadIdx.x & 127) * 16 + wg * 7 * 8192;
      const int hstep = wg ? -8192 : 8192;
      auto glu = [&](int i) {
        return pack_bf16(fmaf(acc[32 + 2 * i], tanh_fast(acc[2 * i]), acc[32 + 2 * i]), fmaf(acc[33 + 2 * i], tanh_fast(acc[2 * i + 1]), acc[33 + 2 * i]));
      };
      for (int c = 0;; c++) {
        if (SKEW > 0 && wg == 1) bar_sync(NB_SKEW, 256);
#pragma unroll
        for (int kb = 0; kb < 9; kb++) {
          stage_begin();
#pragma unroll
          for (int kk = 0; kk < 4; kk++) { const int i = (kb * 4 + kk) * 4; wgmma_n128_rs_tb1(acc, xa[i], xa[i + 1], xa[i + 2], xa[i + 3], desc((dlo + kk * 128) | DLO_MN, DHI_SW128), (kb | kk) != 0); }
          if (SKEW > 0 && kb == SKEW - 1 && wg == 0) bar_arrive(NB_SKEW, 256);
          if (kb == 8 && c == 5) mbar_wait(bars + 8 * B_SCAN, 0);
          stage_end(kb > 0);
        }
        wg_wait<0>();
        release(prev);
        keep(acc);
        if (c == 8) break;
#pragma unroll
        for (int i = 0; i < 4; i++) sts128(ha + c * hstep + i * 2048, glu(4 * i), glu(4 * i + 1), glu(4 * i + 2), glu(4 * i + 3));
        STAMP(wg, 4 + c);
      }
#pragma unroll
      for (int i = 0; i < 32; i++) lds128(ha + (i >> 2) * hstep + (i & 3) * 2048, xa[4 * i], xa[4 * i + 1], xa[4 * i + 2], xa[4 * i + 3]);
      bar_arrive(NB_HFREE, 288);
#pragma unroll
      for (int i = 0; i < 16; i++) xa[128 + i] = glu(i);
    }
    STAMP(wg, 13);

    const uint32_t dhs = (((sb + OFF_HS + wg * HS_BYTES) & 0x3FFFF) >> 4) | DLO_HS;
    const int rp = (g >> 2) + 2 * (g & 3);
    const uint32_t so = w4 * 2048 + rp * 128 + (q & 1) * 8, sx = ((q >> 1) ^ rp) << 4;
    const uint32_t rcv = sb + OFF_STG + wg * 32768 + 16384 + w4 * 2048 + lane * 16;
    auto staged = [&]() {
      asm volatile("fence.proxy.async.shared::cta;" ::: "memory");
      __syncwarp();
      if (elect()) mbar_arrive(bars + 8 * (B_SFULL + wg));
    };
    for (int t = 0; t < 4; t++) {
      if (SKEWB > 0 && wg == 1) bar_sync(NB_SKEW, 256);
#pragma unroll
      for (int kb = 0; kb < 9; kb++) {
        if (kb == 4) nst = NST + 1;
        stage_begin();
#pragma unroll
        for (int kk = 0; kk < 4; kk++) { const int i = (kb * 4 + kk) * 4; wgmma_n128_rs_tb1(acc, xa[i], xa[i + 1], xa[i + 2], xa[i + 3], desc((dlo + kk * 128) | DLO_MN, DHI_SW128), (kb | kk) != 0); }
        if (SKEWB > 0 && kb == SKEWB - 1 && wg == 0) bar_arrive(NB_SKEW, 256);
        stage_end(kb > 0);
        if (kb == 0 && t > 0) staged();
      }
      if (t == 0) mbar_wait(bars + 8 * B_HSFULL, 0);
      stage_begin();
#pragma unroll
      for (int kk = 0; kk < 4; kk++) wgmma_n128_ss_tb0(acc, desc(dhs + kk * (2 * HS_LBO >> 4), DHI_NONE), desc((dlo + kk * 2) | DLO_K, DHI_SW128), 1);
      stage_end(true);
      stage_begin();
#pragma unroll
      for (int kk = 0; kk < 4; kk++) wgmma_n128_ss_tb0(acc, desc(dhs + (4 + kk) * (2 * HS_LBO >> 4), DHI_NONE), desc((dlo + kk * 2) | DLO_K, DHI_SW128), 1);
      const int s_im = s;
      advance();
      stage_begin();
      wgmma_n128_ss_tb0(acc, desc(dhs + 8 * (2 * HS_LBO >> 4), DHI_NONE), desc(dlo | DLO_K, DHI_SW32), 1);
      stage_end(true);
      if (t > 0) mbar_wait(bars + 8 * (B_SFREE + wg), (t - 1) & 1);
      if (t & 1) mbar_wait(bars + 8 * (B_RFULL + wg), t >> 1);
      wg_wait<0>();
      release(s_im); release(prev);
      keep(acc);
      if (t & 1) {
        const uint32_t stg = sb + OFF_STG + wg * 32768 + so;
#pragma unroll
        for (int hh = 0; hh < 2; hh++) {
#pragma unroll
          for (int i = 4 * hh; i < 4 * hh + 4; i++) {
            uint32_t v[4];
            lds128(rcv + hh * 8192 + (i & 3) * 512, v[0], v[1], v[2], v[3]);
#pragma unroll
            for (int e = 0; e < 4; e++) { acc[8 * i + 2 * e] += bflo(v[e]); acc[8 * i + 2 * e + 1] += bfhi(v[e]); }
          }
          __syncwarp();
#pragma unroll
          for (int i = 8 * hh; i < 8 * hh + 8; i++) {
            const uint32_t a = stg + (i >> 2) * 8192 + (sx ^ ((i & 3) << 5));
            sts64f(a, acc[4 * i], acc[4 * i + 1]);
            sts64f(a + 1024, acc[4 * i + 2], acc[4 * i + 3]);
          }
        }
      } else {
#pragma unroll
        for (int i = 0; i < 8; i++)
          sts128(rcv - 16384 + (i >> 2) * 8192 + (i & 3) * 512, pack_bf16(acc[8 * i], acc[8 * i + 1]), pack_bf16(acc[8 * i + 2], acc[8 * i + 3]),
                 pack_bf16(acc[8 * i + 4], acc[8 * i + 5]), pack_bf16(acc[8 * i + 6], acc[8 * i + 7]));
      }
      STAMP(wg, 14 + t);
    }
    {
      float a2[32];
      if (SKEWB > 0 && wg == 1) bar_sync(NB_SKEW, 256);
      const uint32_t ph0 = ph;
#pragma unroll
      for (int kp = 0; kp < 5; kp++) {
        stage_begin();
#pragma unroll
        for (int kk = 0; kk < (kp < 4 ? 8 : 4); kk++) { const int i = (kp * 8 + kk) * 4; wgmma_n64_rs_tb1(a2, xa[i], xa[i + 1], xa[i + 2], xa[i + 3], desc((dlo + kk * 128) | DLO_MN, DHI_SW128), (kp | kk) != 0); }
        if (kp == 4) wgmma_n64_ss_tb0(a2, desc(dhs + 8 * (2 * HS_LBO >> 4), DHI_NONE), desc((dlo + 512) | DLO_K, DHI_SW32), 1);
        if (SKEWB > 0 && kp == 1 && wg == 0) bar_arrive(NB_SKEW, 256);
        stage_end(kp > 0);
        if (kp == 0) staged();
      }
      stage_begin();
#pragma unroll
      for (int kk = 0; kk < 8; kk++) wgmma_n64_ss_tb0(a2, desc(dhs + kk * (2 * HS_LBO >> 4), DHI_NONE), desc((dlo + (kk >> 2) * 512 + (kk & 3) * 2) | DLO_K, DHI_SW128), 1);
      wg_commit();
      mbar_wait(bars + 8 * (B_EMPTY + 3 + wg), ph0);
      wg_wait<0>();
      keep(a2);
      const uint32_t stg = sb + (3 + wg) * SLOT + so;
#pragma unroll
      for (int i = 0; i < 8; i++) {
        const uint32_t a = stg + (i >> 2) * 8192 + (sx ^ ((i & 3) << 5));
        sts64f(a, a2[4 * i], a2[4 * i + 1]);
        sts64f(a + 1024, a2[4 * i + 2], a2[4 * i + 3]);
      }
      staged();
      STAMP(wg, 18);
      if (w4 == 0) STAMP_DUMP(wg);
    }
  }
}

typedef CUresult (*EncodeFn)(CUtensorMap*, CUtensorMapDataType, cuuint32_t, void*, const cuuint64_t*, const cuuint64_t*, const cuuint32_t*,
                             const cuuint32_t*, CUtensorMapInterleave, CUtensorMapSwizzle, CUtensorMapL2promotion, CUtensorMapFloatOOBfill);

void map2d(EncodeFn enc, CUtensorMap* tm, const void* p, uint64_t cols, uint64_t rows, uint32_t bc, uint32_t br, CUtensorMapSwizzle sw) {
  cuuint64_t gd[2] = {cols, rows}, gs[1] = {cols * 2};
  cuuint32_t bd[2] = {bc, br}, es[2] = {1, 1};
  enc(tm, CU_TENSOR_MAP_DATA_TYPE_BFLOAT16, 2, (void*)p, gd, gs, bd, es, CU_TENSOR_MAP_INTERLEAVE_NONE, sw,
      sw == CU_TENSOR_MAP_SWIZZLE_128B ? CU_TENSOR_MAP_L2_PROMOTION_L2_128B : CU_TENSOR_MAP_L2_PROMOTION_NONE, CU_TENSOR_MAP_FLOAT_OOB_FILL_NONE);
}

}

extern "C" void kernel_launch(void* const* d_in, const int* in_sizes, int n_in, void* d_out, int out_size) {
  (void)in_sizes; (void)n_in; (void)out_size;
  static EncodeFn enc = nullptr;
  static void* gC = nullptr;
  if (!enc) {
    cudaDriverEntryPointQueryResult qr;
    cudaGetDriverEntryPoint("cuTensorMapEncodeTiled", (void**)&enc, cudaEnableDefault, &qr);
    cudaGetSymbolAddress(&gC, g_C);
    cudaFuncSetAttribute(fused_kernel, cudaFuncAttributeMaxDynamicSharedMemorySize, SMEM_BYTES);
  }
  Params prm;
  const CUtensorMapSwizzle S128 = CU_TENSOR_MAP_SWIZZLE_128B;
  map2d(enc, &prm.tx, d_in[0], kD, kS, 64, 64, S128);
  map2d(enc, &prm.tBre, d_in[3], kD, 576, 64, 72, S128);
  map2d(enc, &prm.tBim, d_in[4], kD, 576, 64, 72, S128);
  map2d(enc, &prm.tC, gC, 1152, kD, 64, 64, S128);
  map2d(enc, &prm.tC16, gC, 1152, kD, 16, 64, CU_TENSOR_MAP_SWIZZLE_32B);
  map2d(enc, &prm.tWg, d_in[10], kF, kD, 64, 64, S128);
  map2d(enc, &prm.tWu, d_in[11], kF, kD, 64, 64, S128);
  map2d(enc, &prm.tWd, d_in[12], kD, kF, 64, 64, S128);
  {
    cuuint64_t gd[4] = {kD, 2, 4, kS / 8}, gs[3] = {4 * kD * 4, kD * 4, 8 * kD * 4};
    cuuint32_t bd[4] = {32, 2, 4, 8}, es[4] = {1, 1, 1, 1};
    enc(&prm.tOut, CU_TENSOR_MAP_DATA_TYPE_FLOAT32, 4, d_out, gd, gs, bd, es, CU_TENSOR_MAP_INTERLEAVE_NONE, S128, CU_TENSOR_MAP_L2_PROMOTION_NONE,
        CU_TENSOR_MAP_FLOAT_OOB_FILL_NONE);
  }
  prm.lre = (const __nv_bfloat16*)d_in[1];
  prm.lim = (const __nv_bfloat16*)d_in[2];
  prm.bre = (const __nv_bfloat16*)d_in[3];
  prm.bim = (const __nv_bfloat16*)d_in[4];
  prm.cre = (const __nv_bfloat16*)d_in[5];
  prm.cim = (const __nv_bfloat16*)d_in[6];
  prm.wg = (const __nv_bfloat16*)d_in[10];
  prm.wu = (const __nv_bfloat16*)d_in[11];
  prm.wd = (const __nv_bfloat16*)d_in[12];
  prm.ldt = (const __nv_bfloat16*)d_in[7];
  prm.dskip = (const __nv_bfloat16*)d_in[8];
  prm.out = (float*)d_out;

  fused_kernel<<<128, 384, SMEM_BYTES, cudaStreamPerThread>>>(prm);
}
```

```cpp
#include <cuda_runtime.h>
#include <cuda.h>
#include <cuda_bf16.h>
#include <stdint.h>

namespace {

#define PACE 1
#define PACEP 100
#define XMODE 0
#define NOPF 0
#define PFD 12
#define XPF 0
#define HINT 0
#define PEEL 0
#define GRP 1
#define SPLIT 1
#define STX 0
#define BEARLY 0
#define SKEW 3
#define SKEWB 4

constexpr int kS = 2048, kD = 576, kF = 4608;
constexpr int NST = 6;
constexpr uint32_t SLOT = 16384;
constexpr uint32_t OFF_H = NST * SLOT;
constexpr uint32_t HS_LBO = 1040;
constexpr uint32_t HS_BYTES = 18 * HS_LBO;
constexpr uint32_t OFF_DUMP = OFF_H + 65536 - HS_BYTES;
constexpr uint32_t OFF_STG = OFF_H + SLOT;
constexpr uint32_t OFF_HS = OFF_STG + 65536;
constexpr uint32_t OFF_BAR = OFF_H + 131072;
constexpr uint32_t OFF_CONST = OFF_BAR + 384;
constexpr uint32_t SMEM_BYTES = OFF_CONST + 4 * 72 * 4 + 512;
static_assert(SMEM_BYTES <= 232448 && OFF_HS + 2 * HS_BYTES <= OFF_BAR, "smem");

enum { B_FULL = 0, B_EMPTY = NST + 1, B_X = 2 * NST + 2, B_X8 = B_X + 8, B_BU  , B_RING = B_BU + 4, B_SCAN, B_HFREE, B_HSFULL, B_SFULL,
       B_SFREE = B_SFULL + 2, B_RFULL = B_SFREE + 2, B_RFREE = B_RFULL + 2, B_COUNT = B_RFREE + 2 };
static_assert(B_COUNT * 8 <= 384, "barriers");
enum { NB_SKEW = 1, NB_XDONE = 2  , NB_SCAN = 4, NB_DUMP = 5, NB_HFREE = 6, NB_STATS = 7 };
constexpr uint32_t OFF_BU0 = SLOT, OFF_BU1 = OFF_H, OFF_BU2 = OFF_H + 65536 + 19456;
static_assert(OFF_BU1 + 5 * 9216 <= OFF_DUMP && OFF_BU2 >= OFF_DUMP + 2 * HS_BYTES && OFF_BU2 + 5 * 9216 <= OFF_BAR, "Bu tiles");

struct __align__(64) Params {
  CUtensorMap tx, tBre, tBim, tWg, tWu, tWd, tCre, tCim, tCre8, tCim8, tOut;
  const __nv_bfloat16 *x, *lre, *lim, *bre, *bim, *cre, *cim, *ldt, *dskip, *wg, *wu, *wd;
  float* out;
};

__device__ unsigned g_epoch[128];
__device__ unsigned g_ready[16];
__device__ __align__(256) uint2 g_S[2][16][8][96];
__device__ __align__(128) uint8_t g_hs[128][2 * HS_BYTES];
#define STAMP(role, i)
#define STAMPP(i)
#define STAMP_DUMP(role)

__device__ __forceinline__ void wgmma_n72_rs_tb0(float (&d)[36], uint32_t a0, uint32_t a1, uint32_t a2, uint32_t a3, uint64_t db, int scale_d) {
  asm volatile("{\n.reg .pred p;\nsetp.ne.b32 p, %41, 0;\n"
    "wgmma.mma_async.sync.aligned.m64n72k16.f32.bf16.bf16 {"
    "%0, %1, %2, %3, %4, %5, %6, %7, %8, %9, %10, %11, %12, %13, %14, %15, "
    "%16, %17, %18, %19, %20, %21, %22, %23, %24, %25, %26, %27, %28, %29, %30, %31, "
    "%32, %33, %34, %35"
    "}, {%36, %37, %38, %39}, %40, p, 1, 1, 0;\n}\n"
    : "+f"(d[0]), "+f"(d[1]), "+f"(d[2]), "+f"(d[3]), "+f"(d[4]), "+f"(d[5]), "+f"(d[6]), "+f"(d[7]),
      "+f"(d[8]), "+f"(d[9]), "+f"(d[10]), "+f"(d[11]), "+f"(d[12]), "+f"(d[13]), "+f"(d[14]), "+f"(d[15]),
      "+f"(d[16]), "+f"(d[17]), "+f"(d[18]), "+f"(d[19]), "+f"(d[20]), "+f"(d[21]), "+f"(d[22]), "+f"(d[23]),
      "+f"(d[24]), "+f"(d[25]), "+f"(d[26]), "+f"(d[27]), "+f"(d[28]), "+f"(d[29]), "+f"(d[30]), "+f"(d[31]),
      "+f"(d[32]), "+f"(d[33]), "+f"(d[34]), "+f"(d[35])
    : "r"(a0), "r"(a1), "r"(a2), "r"(a3), "l"(db), "r"(scale_d));
}
__device__ __forceinline__ void wgmma_n128_rs_tb1(float (&d)[64], uint32_t a0, uint32_t a1, uint32_t a2, uint32_t a3, uint64_t db, int scale_d) {
  asm volatile("{\n.reg .pred p;\nsetp.ne.b32 p, %69, 0;\n"
    "wgmma.mma_async.sync.aligned.m64n128k16.f32.bf16.bf16 {"
    "%0, %1, %2, %3, %4, %5, %6, %7, %8, %9, %10, %11, %12, %13, %14, %15, "
    "%16, %17, %18, %19, %20, %21, %22, %23, %24, %25, %26, %27, %28, %29, %30, %31, "
    "%32, %33, %34, %35, %36, %37, %38, %39, %40, %41, %42, %43, %44, %45, %46, %47, "
    "%48, %49, %50, %51, %52, %53, %54, %55, %56, %57, %58, %59, %60, %61, %62, %63"
    "}, {%64, %65, %66, %67}, %68, p, 1, 1, 1;\n}\n"
    : "+f"(d[0]), "+f"(d[1]), "+f"(d[2]), "+f"(d[3]), "+f"(d[4]), "+f"(d[5]), "+f"(d[6]), "+f"(d[7]),
      "+f"(d[8]), "+f"(d[9]), "+f"(d[10]), "+f"(d[11]), "+f"(d[12]), "+f"(d[13]), "+f"(d[14]), "+f"(d[15]),
      "+f"(d[16]), "+f"(d[17]), "+f"(d[18]), "+f"(d[19]), "+f"(d[20]), "+f"(d[21]), "+f"(d[22]), "+f"(d[23]),
      "+f"(d[24]), "+f"(d[25]), "+f"(d[26]), "+f"(d[27]), "+f"(d[28]), "+f"(d[29]), "+f"(d[30]), "+f"(d[31]),
      "+f"(d[32]), "+f"(d[33]), "+f"(d[34]), "+f"(d[35]), "+f"(d[36]), "+f"(d[37]), "+f"(d[38]), "+f"(d[39]),
      "+f"(d[40]), "+f"(d[41]), "+f"(d[42]), "+f"(d[43]), "+f"(d[44]), "+f"(d[45]), "+f"(d[46]), "+f"(d[47]),
      "+f"(d[48]), "+f"(d[49]), "+f"(d[50]), "+f"(d[51]), "+f"(d[52]), "+f"(d[53]), "+f"(d[54]), "+f"(d[55]),
      "+f"(d[56]), "+f"(d[57]), "+f"(d[58]), "+f"(d[59]), "+f"(d[60]), "+f"(d[61]), "+f"(d[62]), "+f"(d[63])
    : "r"(a0), "r"(a1), "r"(a2), "r"(a3), "l"(db), "r"(scale_d));
}
__device__ __forceinline__ void wgmma_n128_ss_tb0(float (&d)[64], uint64_t da, uint64_t db, int scale_d) {
  asm volatile("{\n.reg .pred p;\nsetp.ne.b32 p, %66, 0;\n"
    "wgmma.mma_async.sync.aligned.m64n128k16.f32.bf16.bf16 {"
    "%0, %1, %2, %3, %4, %5, %6, %7, %8, %9, %10, %11, %12, %13, %14, %15, "
    "%16, %17, %18, %19, %20, %21, %22, %23, %24, %25, %26, %27, %28, %29, %30, %31, "
    "%32, %33, %34, %35, %36, %37, %38, %39, %40, %41, %42, %43, %44, %45, %46, %47, "
    "%48, %49, %50, %51, %52, %53, %54, %55, %56, %57, %58, %59, %60, %61, %62, %63"
    "}, %64, %65, p, 1, 1, 0, 0;\n}\n"
    : "+f"(d[0]), "+f"(d[1]), "+f"(d[2]), "+f"(d[3]), "+f"(d[4]), "+f"(d[5]), "+f"(d[6]), "+f"(d[7]),
      "+f"(d[8]), "+f"(d[9]), "+f"(d[10]), "+f"(d[11]), "+f"(d[12]), "+f"(d[13]), "+f"(d[14]), "+f"(d[15]),
      "+f"(d[16]), "+f"(d[17]), "+f"(d[18]), "+f"(d[19]), "+f"(d[20]), "+f"(d[21]), "+f"(d[22]), "+f"(d[23]),
      "+f"(d[24]), "+f"(d[25]), "+f"(d[26]), "+f"(d[27]), "+f"(d[28]), "+f"(d[29]), "+f"(d[30]), "+f"(d[31]),
      "+f"(d[32]), "+f"(d[33]), "+f"(d[34]), "+f"(d[35]), "+f"(d[36]), "+f"(d[37]), "+f"(d[38]), "+f"(d[39]),
      "+f"(d[40]), "+f"(d[41]), "+f"(d[42]), "+f"(d[43]), "+f"(d[44]), "+f"(d[45]), "+f"(d[46]), "+f"(d[47]),
      "+f"(d[48]), "+f"(d[49]), "+f"(d[50]), "+f"(d[51]), "+f"(d[52]), "+f"(d[53]), "+f"(d[54]), "+f"(d[55]),
      "+f"(d[56]), "+f"(d[57]), "+f"(d[58]), "+f"(d[59]), "+f"(d[60]), "+f"(d[61]), "+f"(d[62]), "+f"(d[63])
    : "l"(da), "l"(db), "r"(scale_d));
}
__device__ __forceinline__ void wgmma_n64_rs_tb1(float (&d)[32], uint32_t a0, uint32_t a1, uint32_t a2, uint32_t a3, uint64_t db, int scale_d) {
  asm volatile("{\n.reg .pred p;\nsetp.ne.b32 p, %37, 0;\n"
    "wgmma.mma_async.sync.aligned.m64n64k16.f32.bf16.bf16 {"
    "%0, %1, %2, %3, %4, %5, %6, %7, %8, %9, %10, %11, %12, %13, %14, %15, "
    "%16, %17, %18, %19, %20, %21, %22, %23, %24, %25, %26, %27, %28, %29, %30, %31"
    "}, {%32, %33, %34, %35}, %36, p, 1, 1, 1;\n}\n"
    : "+f"(d[0]), "+f"(d[1]), "+f"(d[2]), "+f"(d[3]), "+f"(d[4]), "+f"(d[5]), "+f"(d[6]), "+f"(d[7]),
      "+f"(d[8]), "+f"(d[9]), "+f"(d[10]), "+f"(d[11]), "+f"(d[12]), "+f"(d[13]), "+f"(d[14]), "+f"(d[15]),
      "+f"(d[16]), "+f"(d[17]), "+f"(d[18]), "+f"(d[19]), "+f"(d[20]), "+f"(d[21]), "+f"(d[22]), "+f"(d[23]),
      "+f"(d[24]), "+f"(d[25]), "+f"(d[26]), "+f"(d[27]), "+f"(d[28]), "+f"(d[29]), "+f"(d[30]), "+f"(d[31])
    : "r"(a0), "r"(a1), "r"(a2), "r"(a3), "l"(db), "r"(scale_d));
}
__device__ __forceinline__ void wgmma_n64_ss_tb0(float (&d)[32], uint64_t da, uint64_t db, int scale_d) {
  asm volatile("{\n.reg .pred p;\nsetp.ne.b32 p, %34, 0;\n"
    "wgmma.mma_async.sync.aligned.m64n64k16.f32.bf16.bf16 {"
    "%0, %1, %2, %3, %4, %5, %6, %7, %8, %9, %10, %11, %12, %13, %14, %15, "
    "%16, %17, %18, %19, %20, %21, %22, %23, %24, %25, %26, %27, %28, %29, %30, %31"
    "}, %32, %33, p, 1, 1, 0, 0;\n}\n"
    : "+f"(d[0]), "+f"(d[1]), "+f"(d[2]), "+f"(d[3]), "+f"(d[4]), "+f"(d[5]), "+f"(d[6]), "+f"(d[7]),
      "+f"(d[8]), "+f"(d[9]), "+f"(d[10]), "+f"(d[11]), "+f"(d[12]), "+f"(d[13]), "+f"(d[14]), "+f"(d[15]),
      "+f"(d[16]), "+f"(d[17]), "+f"(d[18]), "+f"(d[19]), "+f"(d[20]), "+f"(d[21]), "+f"(d[22]), "+f"(d[23]),
      "+f"(d[24]), "+f"(d[25]), "+f"(d[26]), "+f"(d[27]), "+f"(d[28]), "+f"(d[29]), "+f"(d[30]), "+f"(d[31])
    : "l"(da), "l"(db), "r"(scale_d));
}

__device__ __forceinline__ bool elect() {
  uint32_t p;
  asm volatile("{.reg .pred q; elect.sync _|q, 0xffffffff; selp.u32 %0,1,0,q;}" : "=r"(p));
  return p;
}
__device__ __forceinline__ void mbar_init(uint32_t bar, uint32_t cnt) { asm volatile("mbarrier.init.shared::cta.b64 [%0], %1;" ::"r"(bar), "r"(cnt) : "memory"); }
__device__ __forceinline__ void mbar_expect(uint32_t bar, uint32_t bytes) { asm volatile("mbarrier.arrive.expect_tx.shared::cta.b64 _, [%0], %1;" ::"r"(bar), "r"(bytes) : "memory"); }
__device__ __forceinline__ void mbar_arrive(uint32_t bar) { asm volatile("mbarrier.arrive.shared::cta.b64 _, [%0];" ::"r"(bar) : "memory"); }
__device__ __forceinline__ void mbar_arrive_cta(uint32_t bar, uint32_t cta) {
  asm volatile("{.reg .b32 ra; mapa.shared::cluster.u32 ra, %0, %1; mbarrier.arrive.shared::cluster.b64 _, [ra];}" ::"r"(bar), "r"(cta) : "memory");
}
__device__ __forceinline__ void mbar_wait(uint32_t bar, uint32_t parity) {
  asm volatile(
      "{\n.reg .pred p;\n.reg .u32 c, t;\n"
      "mbarrier.try_wait.parity.shared::cta.b64 p, [%0], %1;\n@p bra DONE;\n"
      "mov.u32 c, %%clock;\n"
      "LAB_WAIT:\nmbarrier.try_wait.parity.shared::cta.b64 p, [%0], %1;\n@p bra DONE;\n"
      "mov.u32 t, %%clock;\nsub.u32 t, t, c;\nsetp.lt.u32 p, t, 0x40000000;\n@p bra LAB_WAIT;\ntrap;\nDONE:\n}" ::"r"(bar), "r"(parity) : "memory");
}
__device__ __forceinline__ void bar_sync(int id, int n) { asm volatile("bar.sync %0, %1;" ::"r"(id), "r"(n) : "memory"); }
__device__ __forceinline__ void bar_arrive(int id, int n) { asm volatile("bar.arrive %0, %1;" ::"r"(id), "r"(n) : "memory"); }
__device__ __forceinline__ void wg_fence() { asm volatile("wgmma.fence.sync.aligned;" ::: "memory"); }
__device__ __forceinline__ void wg_commit() { asm volatile("wgmma.commit_group.sync.aligned;" ::: "memory"); }
template <int N> __device__ __forceinline__ void wg_wait() { asm volatile("wgmma.wait_group.sync.aligned %0;" ::"n"(N) : "memory"); }
__device__ __forceinline__ void tma2d(uint32_t dst, const CUtensorMap* tm, uint32_t bar, int c0, int c1) {
  asm volatile("cp.async.bulk.tensor.2d.shared::cluster.global.mbarrier::complete_tx::bytes [%0], [%1,{%3,%4}], [%2];" ::"r"(dst), "l"(tm), "r"(bar), "r"(c0), "r"(c1) : "memory");
}
__device__ __forceinline__ void tma2d_mc(uint32_t dst, const CUtensorMap* tm, uint32_t bar, int c0, int c1) {
  asm volatile("cp.async.bulk.tensor.2d.shared::cluster.global.mbarrier::complete_tx::bytes.multicast::cluster [%0], [%1,{%3,%4}], [%2], %5;" ::"r"(dst), "l"(tm), "r"(bar), "r"(c0), "r"(c1), "h"((uint16_t)3) : "memory");
}
__device__ __forceinline__ void l2_prefetch(const void* p, uint32_t bytes) {
  asm volatile("cp.async.bulk.prefetch.L2.global [%0], %1;" ::"l"(p), "r"(bytes) : "memory");
}
__device__ __forceinline__ void l2_prefetch_line(const void* p) { asm volatile("prefetch.global.L2 [%0];" ::"l"(p)); }
__device__ __forceinline__ void tma_prefetch2d(const CUtensorMap* tm, int c0, int c1) {
  asm volatile("cp.async.bulk.prefetch.tensor.2d.L2.global.tile [%0,{%1,%2}];" ::"l"(tm), "r"(c0), "r"(c1) : "memory");
}
__device__ __forceinline__ uint64_t desc(uint32_t lo, uint32_t hi) { return ((uint64_t)hi << 32) | lo; }
constexpr uint32_t DHI_SW128 = (1024 >> 4) | (1u << 30);
constexpr uint32_t DHI_NONE = (128 >> 4);
constexpr uint32_t DLO_HS = (HS_LBO >> 4) << 16;
constexpr uint32_t DLO_MN = (8192 >> 4) << 16;
constexpr uint32_t DLO_K = 1u << 16;
__device__ __forceinline__ float tanh_fast(float x) { float y; asm("tanh.approx.f32 %0, %1;" : "=f"(y) : "f"(x)); return y; }
__device__ __forceinline__ uint32_t pack_bf16(float lo, float hi) { uint32_t r; asm("cvt.rn.bf16x2.f32 %0, %1, %2;" : "=r"(r) : "f"(hi), "f"(lo)); return r; }
__device__ __forceinline__ float rbf(float x) { return __bfloat162float(__float2bfloat16_rn(x)); }
__device__ __forceinline__ void mma16816(float (&c)[4], uint32_t a0, uint32_t a1, uint32_t a2, uint32_t a3, uint32_t b0, uint32_t b1) {
  asm volatile("mma.sync.aligned.m16n8k16.row.col.f32.bf16.bf16.f32 {%0,%1,%2,%3}, {%4,%5,%6,%7}, {%8,%9}, {%0,%1,%2,%3};"
               : "+f"(c[0]), "+f"(c[1]), "+f"(c[2]), "+f"(c[3]) : "r"(a0), "r"(a1), "r"(a2), "r"(a3), "r"(b0), "r"(b1));
}
__device__ __forceinline__ void sts128(uint32_t a, uint32_t x, uint32_t y, uint32_t z, uint32_t w) {
  asm volatile("st.shared.v4.b32 [%0], {%1,%2,%3,%4};" ::"r"(a), "r"(x), "r"(y), "r"(z), "r"(w) : "memory");
}
__device__ __forceinline__ void sts64f(uint32_t a, float x, float y) { asm volatile("st.shared.v2.f32 [%0], {%1,%2};" ::"r"(a), "f"(x), "f"(y) : "memory"); }
__device__ __forceinline__ float2 lds64f(uint32_t a) { float2 v; asm volatile("ld.shared.v2.f32 {%0,%1}, [%2];" : "=f"(v.x), "=f"(v.y) : "r"(a) : "memory"); return v; }
__device__ __forceinline__ uint32_t lds32(uint32_t a) { uint32_t v; asm volatile("ld.shared.b32 %0, [%1];" : "=r"(v) : "r"(a) : "memory"); return v; }
__device__ __forceinline__ void lds128(uint32_t a, uint32_t& x, uint32_t& y, uint32_t& z, uint32_t& w) {
  asm volatile("ld.shared.v4.b32 {%0,%1,%2,%3}, [%4];" : "=r"(x), "=r"(y), "=r"(z), "=r"(w) : "r"(a) : "memory");
}
__device__ __forceinline__ float bflo(uint32_t v) { return __uint_as_float(v << 16); }
__device__ __forceinline__ float bfhi(uint32_t v) { return __uint_as_float(v & 0xffff0000u); }
__device__ __forceinline__ uint32_t lds32v(uint32_t a) { uint32_t v; asm volatile("ld.volatile.shared.b32 %0, [%1];" : "=r"(v) : "r"(a) : "memory"); return v; }
__device__ __forceinline__ float lds32f(uint32_t a) { float v; asm volatile("ld.shared.f32 %0, [%1];" : "=f"(v) : "r"(a) : "memory"); return v; }
template <int N> __device__ __forceinline__ void keep(float (&a)[N]) {
#pragma unroll
  for (int i = 0; i < N; i++) asm volatile("" : "+f"(a[i])::"memory");
}

__global__ void __cluster_dims__(2, 1, 1) __launch_bounds__(384, 1) fused_kernel(const __grid_constant__ Params prm) {
  extern __shared__ __align__(1024) uint8_t smem[];
  const int warp = __shfl_sync(0xffffffffu, threadIdx.x >> 5, 0);
  const uint32_t sb0 = (uint32_t)__cvta_generic_to_shared(smem);
  const int j = blockIdx.x & 7, m = blockIdx.x >> 3, rank = j & 1;
  auto smem_base = [&]() { return __shfl_sync(0xffffffffu, sb0 + (threadIdx.x & 31), 0); };
  STAMP(0, 31);

  if (XPF && threadIdx.x < 144) l2_prefetch_line((const char*)prm.x + (size_t)(m * 128 + j * 16) * 1152 + threadIdx.x * 128);
  if (threadIdx.x == 320) asm volatile("prefetch.tensormap [%0];" ::"l"(&prm.tx) : "memory");
  if (warp == 8 || warp == 9) {
    if (elect()) {
      if (warp == 8) {
#pragma unroll
        for (int i = 0; i < B_COUNT / 2; i++) mbar_init(sb0 + OFF_BAR + 8 * i, (i >= B_EMPTY && i < B_X) ? 2 : 1);
      } else {
#pragma unroll
        for (int i = B_COUNT / 2; i < B_COUNT; i++) mbar_init(sb0 + OFF_BAR + 8 * i, (i >= B_SFULL && i < B_SFULL + 2) ? 4 : i == B_RING ? 2 : 1);
        if (sb0 & 1023) __trap();
      }
      asm volatile("fence.mbarrier_init.release.cluster;" ::: "memory");
    }
    __syncwarp();
  }
  STAMPP(0);
  asm volatile("barrier.cluster.arrive.relaxed.aligned;\nbarrier.cluster.wait.aligned;" ::: "memory");
  STAMPP(1);

  if (warp == 0) {
    const uint32_t xb = sb0 + OFF_BAR;
    const bool e = elect();
    if (e) { mbar_expect(xb + 8 * B_X8, 16384); tma2d_mc(sb0 + rank * 8192, &prm.tx, xb + 8 * B_X8, 512, m * 128 + rank * 64); }
#pragma unroll
    for (int i = 0; i < 8; i++) {
      const int w = i >> 2, kb = (i & 3) * 2 + rank;
      if (e) { mbar_expect(xb + 8 * (B_X + i), 16384); tma2d_mc(sb0 + OFF_H + w * 65536 + kb * 8192, &prm.tx, xb + 8 * (B_X + i), kb * 64, m * 128 + w * 64); }
    }
    if (BEARLY) {
#pragma unroll
      for (int kb = 0; kb < 8; kb++)
        if (e) { if ((kb & 3) == 0) mbar_expect(xb + 8 * (B_BU + (kb >> 2)), 4 * 9216); tma2d(sb0 + OFF_BU0 + kb * 9216, &prm.tBre, xb + 8 * (B_BU + (kb >> 2)), kb * 64, j * 72); }
    }
    __syncwarp();
    STAMP(0, 20);
  }

  if (warp >= 8) {
    asm volatile("setmaxnreg.dec.sync.aligned.u32 24;");
    if (warp == 8) {
      const uint32_t sb = smem_base(), bars = sb + OFF_BAR;
      bool e;
      int s = 0, nst = NST; uint32_t ph = 1;
      uint32_t dst, fb;
      auto acquire = [&](uint32_t bytes) {
        mbar_wait(bars + 8 * (B_EMPTY + s), ph);
        fb = bars + 8 * (B_FULL + s); dst = sb + s * SLOT;
        e = elect();
        if (e) mbar_expect(fb, bytes);
        if (++s == nst) { s = 0; ph ^= 1; }
      };
      auto box = [&](const CUtensorMap* t, uint32_t o, int a, int b) { if (e) tma2d(dst + o, t, fb, a, b); };
      const int lane = threadIdx.x & 31;
      const char* pf = lane < 8 ? (const char*)(lane & 4 ? prm.wu : prm.wg) + ((size_t)(m * 4 + (lane & 3)) * kF + j * 576) * 2
                     : lane < 12 ? (const char*)prm.wd + (size_t)j * 576 * 1152 + (m * 324 + (lane & 3)) * 128
                                 : (const char*)(lane & 1 ? prm.cim : prm.cre) + (size_t)blockIdx.x * 5184;
      int pk = 0, pleft = 81;
      auto prefetch = [&]() {
        if (pleft > 0) {
          if (lane < 14 && !(NOPF & 2)) l2_prefetch_line(pf);
          pf += lane < 8 ? (pk == 8 ? 128 - 8 * 64 * kF * 2 : 64 * kF * 2) : lane < 12 ? 512 : 64;
          pk = pk == 8 ? 0 : pk + 1;
          pleft--;
        }
      };
      STAMPP(3);
      e = elect();
#pragma unroll 1
      for (int kb = 0; kb < (BEARLY ? 0 : 8); kb++) {
        fb = bars + 8 * (B_BU + (kb >> 2));
        if (e) { if ((kb & 3) == 0) mbar_expect(fb, 4 * 9216); tma2d(sb + OFF_BU0 + kb * 9216, &prm.tBre, fb, kb * 64, j * 72); }
      }
      STAMPP(4);
      bar_sync(NB_XDONE, 160);
      fb = bars + 8 * (B_BU + 2);
      if (e) { mbar_expect(fb, 5 * 9216); tma2d(sb + OFF_BU1, &prm.tBre, fb, 512, j * 72); }
#pragma unroll 1
      for (int kb = 0; kb < 4; kb++) if (e) tma2d(sb + OFF_BU1 + (kb + 1) * 9216, &prm.tBim, fb, kb * 64, j * 72);
      for (int i = 0; i < PFD / 2; i++) prefetch();
      bar_sync(NB_XDONE + 1, 160);
      fb = bars + 8 * (B_BU + 3);
      if (e) mbar_expect(fb, 5 * 9216);
#pragma unroll 1
      for (int kb = 4; kb < 9; kb++) if (e) tma2d(sb + OFF_BU2 + (kb - 4) * 9216, &prm.tBim, fb, kb * 64, j * 72);
      for (int i = PFD / 2; i < PFD; i++) prefetch();
      STAMPP(5);
      mbar_wait(bars + 8 * B_RING, 0);
      STAMPP(6);
      for (int c = 0; c < 9; c++) {
        const int col = j * 576 + c * 64;
#pragma unroll 1
        for (int kb = 0; kb < 9; kb++) { acquire(16384); box(&prm.tWg, 0, col, kb * 64); box(&prm.tWu, 8192, col, kb * 64); prefetch(); }
      }
      auto half_tile = [&](int n0) {
#pragma unroll 1
        for (int kp = 0; kp < 4; kp++) { acquire(16384); box(&prm.tWd, 0, n0, j * 576 + kp * 128); box(&prm.tWd, 8192, n0, j * 576 + kp * 128 + 64); }
        nst = NST + 1;
        acquire(8192 + 2048); box(&prm.tWd, 0, n0, j * 576 + 512); box(&prm.tCre8, 8192, j * 72 + 64, n0); box(&prm.tCim8, 9216, j * 72 + 64, n0);
        acquire(16384); box(&prm.tCre, 0, j * 72, n0); box(&prm.tCim, 8192, j * 72, n0);
      };
      if (rank) half_tile(512);
#pragma unroll 1
      for (int t = 0; t < 4 - (SPLIT & rank); t++) {
        const int n0 = ((rank ^ t ^ 1) & 1) * 256 + (((t >> 1) ^ (j >> 1)) & 1) * 128;
#pragma unroll 1
        for (int kb = 0; kb < 9; kb++) {
          if (kb == 4) nst = NST + 1;
          if (kb == 3 && t == 0 && rank) mbar_wait(bars + 8 * B_HFREE, 0);
          acquire(16384); box(&prm.tWd, 0, n0, j * 576 + kb * 64); box(&prm.tWd, 8192, n0 + 64, j * 576 + kb * 64);
        }
        if (t == 0) mbar_wait(bars + 8 * B_HFREE, 0);
        acquire(16384); box(&prm.tCre, 0, j * 72, n0); box(&prm.tCre, 8192, j * 72, n0 + 64);
        acquire(16384); box(&prm.tCim, 0, j * 72, n0); box(&prm.tCim, 8192, j * 72, n0 + 64);
        acquire(4096);
        box(&prm.tCre8, 0, j * 72 + 64, n0); box(&prm.tCre8, 1024, j * 72 + 64, n0 + 64);
        box(&prm.tCim8, 2048, j * 72 + 64, n0); box(&prm.tCim8, 3072, j * 72 + 64, n0 + 64);
      }
      if (!rank) half_tile(512);
      else if (SPLIT) {
#pragma unroll 1
        for (int hh = 0; hh < 2; hh++) half_tile(256 + (((j >> 1) ^ 1) & 1) * 128 + hh * 64);
      }
      STAMP_DUMP(3);
    } else {
      const uint32_t sb = smem_base(), bars = sb + OFF_BAR;
      const int p = min((int)threadIdx.x - 288, 71);
      if (threadIdx.x < 288 + 10) asm volatile("prefetch.tensormap [%0];" ::"l"(&prm.tBre + (threadIdx.x - 288)) : "memory");
      if (warp == 10 && !(NOPF & 1)) {
        const int l = threadIdx.x & 31;
        const char* q = (const char*)(l & 1 ? prm.bim : prm.bre) + (size_t)blockIdx.x * 5184;
        mbar_wait(bars + 8 * B_X8, 0);
#pragma unroll
        for (int i = 0; i < 3; i++) if (i * 16 + (l >> 1) < 42) l2_prefetch_line(q + min((i * 16 + (l >> 1)) * 128, 5183));
      }
      const unsigned epoch = *(volatile unsigned*)&g_epoch[blockIdx.x];
      float ar, ai;
      {
        const int pg = j * 72 + p;
        const float lr = __bfloat162float(prm.lre[pg]), li = __bfloat162float(prm.lim[pg]);
        const float dt = rbf(expf(__bfloat162float(prm.ldt[pg])));
        const float ea = expf(dt * lr);
        float sn, cs;
        sincosf(dt * li, &sn, &cs);
        ar = ea * cs; ai = ea * sn;
        float br = ar, bi = ai;
#pragma unroll
        for (int k = 0; k < 7; k++) { const float t = br * br - bi * bi; bi = 2.f * br * bi; br = t; }
        const float nr = ar - 1.f, den = 4.f / (lr * lr + li * li);
        float* cp = (float*)(smem + OFF_CONST) + p;
        cp[0] = (nr * lr + ai * li) * den; cp[72] = (ai * lr - nr * li) * den; cp[144] = br; cp[216] = bi;
      }
      STAMP(2, 0);
      bar_sync(NB_DUMP, 352);
      {
        float hr = 0.f, hi = 0.f;
        uint32_t a0 = sb + OFF_DUMP + (p < 64 ? p >> 3 : 16) * HS_LBO + (p & 7) * 2;
        uint32_t di = p < 64 ? 8 * HS_LBO : HS_LBO;
        asm volatile("" : "+r"(a0), "+r"(di));
        auto lds16 = [&](uint32_t a) { uint16_t v; asm volatile("ld.shared.u16 %0, [%1];" : "=h"(v) : "r"(a) : "memory"); return __uint_as_float((uint32_t)v << 16); };
        auto step = [&](float vr, float vi) {
          const float nr = fmaf(ar, hr, fmaf(-ai, hi, vr));
          hi = fmaf(ar, hi, fmaf(ai, hr, vi)); hr = nr;
        };
        if (m < 15) {
#pragma unroll 1
          for (int tb = 0; tb < 32; tb++) {
            const uint32_t a = a0 + tb * 64 + (tb >> 4) * (HS_BYTES - 1024), b = a + di;
            float vr[4], vi[4];
#pragma unroll
            for (int k = 0; k < 4; k++) { vr[k] = lds16(a + k * 16); vi[k] = lds16(b + k * 16); }
#pragma unroll
            for (int k = 0; k < 4; k++) step(vr[k], vi[k]);
          }
          asm volatile("st.relaxed.gpu.global.v2.b32 [%0], {%1,%2};" ::"l"(&g_S[epoch & 1][m][j][threadIdx.x - 288]), "r"(~__float_as_uint(hr)), "r"(~__float_as_uint(hi)) : "memory");
          g_S[(epoch & 1) ^ 1][m][j][threadIdx.x - 288] = make_uint2(0u, 0u);
        }
        STAMP(2, 4);
        {
          const float br = lds32f(sb + OFF_CONST + 576 + p * 4), bi = lds32f(sb + OFF_CONST + 864 + p * 4);
          hr = 0.f; hi = 0.f;
          const uint2* sp = &g_S[epoch & 1][0][j][threadIdx.x - 288];
#pragma unroll 1
          for (int left = m; left > 0; left -= 4, sp += 4 * 768) {
            uint32_t v[4][2];
            int spins = 0;
            uint32_t ok;
            do {
#pragma unroll
              for (int k = 0; k < 4; k++) {
                v[k][0] = v[k][1] = 0xffffffffu;
                if (k < left) asm volatile("ld.relaxed.gpu.global.v2.b32 {%0,%1}, [%2];" : "=r"(v[k][0]), "=r"(v[k][1]) : "l"(sp + k * 768) : "memory");
              }
              ok = min(min(min(v[0][0], v[0][1]), min(v[1][0], v[1][1])), min(min(v[2][0], v[2][1]), min(v[3][0], v[3][1])));
              if (++spins > (1 << 22)) __trap();
            } while (ok == 0u);
#pragma unroll
            for (int k = 0; k < 4; k++)
              if (k < left) { const float nr = fmaf(br, hr, fmaf(-bi, hi, __uint_as_float(~v[k][0]))); hi = fmaf(br, hi, fmaf(bi, hr, __uint_as_float(~v[k][1]))); hr = nr; }
          }
        }
        __syncwarp();
        STAMP(2, 5);
        const float cr = lds32f(sb + OFF_CONST + p * 4), ci = lds32f(sb + OFF_CONST + 288 + p * 4);
#pragma unroll 1
        for (int tb = 0; tb < 32; tb++) {
          const uint32_t a = a0 + tb * 64 + (tb >> 4) * (HS_BYTES - 1024), b = a + di;
          float vr[4], vi[4];
#pragma unroll
          for (int k = 0; k < 4; k++) { vr[k] = lds16(a + k * 16); vi[k] = lds16(b + k * 16); }
#pragma unroll
          for (int k = 0; k < 4; k++) {
            step(vr[k], vi[k]);
            const uint32_t o = pack_bf16(fmaf(cr, hr, -ci * hi), fmaf(-cr, hi, -ci * hr));
            asm volatile("{.reg .b16 l, h; mov.b32 {l, h}, %2; st.shared.b16 [%0], l; st.shared.b16 [%1], h;}" ::"r"(a + k * 16), "r"(b + k * 16), "r"(o) : "memory");
          }
        }
        asm volatile("fence.proxy.async.shared::cta;" ::: "memory");
      }
      STAMP(2, 6);
      bar_sync(NB_SCAN, 96);
      if (warp == 9) {
        if (elect()) {
#pragma unroll 1
          for (uint32_t o = 0; o < 2 * HS_BYTES; o += 4 * HS_LBO) {
            asm volatile("cp.async.bulk.global.shared::cta.bulk_group [%0], [%1], %2;" ::"l"(&g_hs[blockIdx.x][o]), "r"(sb + OFF_DUMP + o), "r"(4 * HS_LBO) : "memory");
            asm volatile("cp.async.bulk.commit_group;\ncp.async.bulk.wait_group.read 0;" ::: "memory");
            if (PACEP) __nanosleep(PACEP);
          }
          mbar_arrive(bars + 8 * B_SCAN);
        }
        __syncwarp();
        STAMP(2, 2);
      }
      if (warp == 9) {
        if (elect()) {
          __threadfence();
          asm volatile("red.release.gpu.global.add.u32 [%0], 1;" ::"l"(&g_ready[m]) : "memory");
          g_epoch[blockIdx.x] = epoch + 1u;
          asm volatile("cp.async.bulk.wait_group 0;" ::: "memory");
        }
        __syncwarp();
        STAMP(2, 7);
        bar_sync(NB_HFREE, 288);
        if (elect()) {
          mbar_arrive(bars + 8 * B_HFREE);
          mbar_expect(bars + 8 * B_HSFULL, 2 * HS_BYTES);
          asm volatile("cp.async.bulk.shared::cluster.global.mbarrier::complete_tx::bytes [%0], [%1], %2, [%3];" ::"r"(sb + OFF_HS),
                       "l"(&g_hs[blockIdx.x][0]), "r"(2 * HS_BYTES), "r"(bars + 8 * B_HSFULL) : "memory");
          for (int w = 0; w < 2; w++) mbar_arrive_cta(bars + 8 * (B_RFREE + w), rank ^ 1);
        }
        __syncwarp();
        STAMP_DUMP(2);
      } else {
        const int w = warp - 10;
        {
          const unsigned target = 8u * (epoch + 1u);
          int spins = 0;
          unsigned v;
          do {
            asm volatile("ld.acquire.gpu.global.u32 %0, [%1];" : "=r"(v) : "l"(&g_ready[m]) : "memory");
            if (++spins > (1 << 22)) __trap();
          } while ((int)(v - target) < 0);
          asm volatile("fence.proxy.async.global;" ::: "memory");
        }
        const uint32_t stg = sb + OFF_STG + w * 32768;
        const int nu = 5 + (SPLIT & rank);
#pragma unroll 1
        for (int u = 0; u < nu; u++) {
          const int t = u - rank;
          if (t == 0 || t == 2) {
            if (elect()) mbar_expect(bars + 8 * (B_RFULL + w), 16384);
            mbar_wait(bars + 8 * (B_SFULL + w), u & 1);
            mbar_wait(bars + 8 * (B_RFREE + w), t >> 1);
            if (elect())
              asm volatile("{.reg .b32 ra, rb; mapa.shared::cluster.u32 ra, %0, %3; mapa.shared::cluster.u32 rb, %2, %3;\n"
                           "cp.async.bulk.shared::cluster.shared::cta.mbarrier::complete_tx::bytes [ra], [%1], 16384, [rb];}" ::"r"(stg + 16384),
                           "r"(stg), "r"(bars + 8 * (B_RFULL + w)), "r"(rank ^ 1) : "memory");
            mbar_wait(bars + 8 * (B_RFULL + w), t >> 1);
            if (elect()) mbar_arrive_cta(bars + 8 * (B_SFREE + w), rank ^ 1);
          } else {
            mbar_wait(bars + 8 * (B_SFULL + w), u & 1);
            const bool d = u == (rank ? 0 : 4), hf = SPLIT && rank && u >= 4;
            const int n0 = d ? 512 : rank * 256 + (((min(t, 3) >> 1) ^ (j >> 1)) & 1) * 128 + (u == 5 ? 64 : 0);
            const uint32_t src = d && !rank ? sb + (3 + w) * SLOT : stg + (u == 5 ? 16384 : 0);
            if (elect()) {
#pragma unroll 1
              for (int b = 0; b < (d || hf ? 2 : 4); b++) {
                asm volatile("cp.reduce.async.bulk.tensor.4d.global.shared::cta.add.tile.bulk_group [%0, {%1,%2,%2,%3}], [%4];" ::"l"(&prm.tOut), "r"(n0 + b * 32), "r"(0),
                             "r"(m * 16 + w * 8), "r"(src + b * 8192) : "memory");
                asm volatile("cp.async.bulk.commit_group;" ::: "memory");
                if (PACE && u < nu - 1) { asm volatile("cp.async.bulk.wait_group.read 0;" ::: "memory"); if (PACE > 1) __nanosleep(PACE); }
              }
              if (u < 3) {
                asm volatile("cp.async.bulk.wait_group.read 0;" ::: "memory");
                mbar_arrive(bars + 8 * (B_SFREE + w));
                if (t == 1) mbar_arrive_cta(bars + 8 * (B_RFREE + w), rank ^ 1);
              }
              if (u == nu - 1) asm volatile("cp.async.bulk.wait_group.read 0;" ::: "memory");
            }
          }
          __syncwarp();
        }
      }
    }
  } else {
    asm volatile("setmaxnreg.inc.sync.aligned.u32 240;");
    const uint32_t sb = smem_base(), bars = sb + OFF_BAR;
    const int wg = warp >> 2, w4 = warp & 3;
    const int lane = threadIdx.x & 31, g = lane >> 2, q = lane & 3;
    const uint32_t hw = sb + OFF_H + wg * 65536;
    STAMP(wg, 0);

    int s = 0, nst = NST; uint32_t ph = 0;
    auto release = [&](int st) { if (w4 == 0) { if (elect()) mbar_arrive(bars + 8 * (B_EMPTY + st)); } };
    const uint32_t dring = (sb & 0x3FFFF) >> 4;
    uint32_t dlo; int prev = 0;
    auto stage_begin = [&]() { mbar_wait(bars + 8 * (B_FULL + s), ph); dlo = dring + s * (SLOT >> 4); wg_fence(); };
    auto advance = [&]() { if (++s == nst) { s = 0; ph ^= 1; } };
    auto stage_end = [&](bool rel) {
      wg_commit();
      if (rel) { wg_wait<1>(); release(prev); }
      prev = s;
      advance();
    };

    uint32_t xa[144];
    uint32_t xr[18], dk[9];
    uint32_t rh[2], cc[2];
#pragma unroll
    for (int i = 0; i < 9; i++) {
      dk[i] = __ldg((const uint32_t*)(prm.dskip + j * 72 + i * 8 + q * 2));
      asm("add.rn.bf16x2 %0, %0, %0;" : "+r"(dk[i]));
    }
    {
      const int r = w4 * 16 + (lane & 7) + ((lane >> 3) & 1) * 8;
      const uint32_t ro = r * 128, cx = ((lane >> 4) ^ (lane & 7)) << 4;
      float s1[2][4] = {};
      auto load = [&](int kb, uint32_t base) {
#pragma unroll
        for (int kk = 0; kk < 4; kk++) {
          const int i = (kb * 4 + kk) * 4;
          asm volatile("ldmatrix.sync.aligned.m8n8.x4.shared.b16 {%0,%1,%2,%3}, [%4];"
                       : "=r"(xa[i]), "=r"(xa[i + 1]), "=r"(xa[i + 2]), "=r"(xa[i + 3]) : "r"(base + ro + (cx ^ (kk << 5))) : "memory");
        }
      };
      const uint32_t b0 = (g & 1) ? 0u : 0x3f803f80u, b1 = b0 ^ 0x3f803f80u;
      auto sums = [&](int kb) {
#pragma unroll
        for (int kk = 0; kk < 4; kk += GRP) {
          const int i = (kb * 4 + kk) * 4;
          uint32_t a[4];
#pragma unroll
          for (int e = 0; e < 2; e++) {
            asm("mul.rn.bf16x2 %0, %1, %1;" : "=r"(a[e]) : "r"(xa[i + e]));
            asm("add.rn.bf16x2 %0, %1, %2;" : "=r"(a[2 + e]) : "r"(xa[i + e]), "r"(xa[i + 2 + e]));
            asm("fma.rn.bf16x2 %0, %1, %1, %0;" : "+r"(a[e]) : "r"(xa[i + 2 + e]));
            if (GRP == 2) {
              uint32_t t, u;
              asm("mul.rn.bf16x2 %0, %1, %1;" : "=r"(t) : "r"(xa[i + 4 + e]));
              asm("add.rn.bf16x2 %0, %1, %2;" : "=r"(u) : "r"(xa[i + 4 + e]), "r"(xa[i + 6 + e]));
              asm("fma.rn.bf16x2 %0, %1, %1, %0;" : "+r"(t) : "r"(xa[i + 6 + e]));
              asm("add.rn.bf16x2 %0, %0, %1;" : "+r"(a[e]) : "r"(t));
              asm("add.rn.bf16x2 %0, %0, %1;" : "+r"(a[2 + e]) : "r"(u));
            }
          }
          mma16816(s1[(kk / GRP) & 1], a[0], a[1], a[2], a[3], b0, b1);
        }
      };
      mbar_wait(bars + 8 * B_X8, 0);
      if (STX) STAMP(wg, 21);
      load(8, sb + wg * 8192);
#pragma unroll
      for (int kp = 0; kp < 4; kp++) {
        mbar_wait(bars + 8 * (B_X + wg * 4 + kp), 0);
        if (STX) STAMP(wg, 22 + kp);
        load(2 * kp, hw + 2 * kp * 8192);
        load(2 * kp + 1, hw + (2 * kp + 1) * 8192);
        if (kp == 0) sums(8); else { sums(2 * kp - 2); sums(2 * kp - 1); }
      }
#pragma unroll
      for (int i = 0; i < 9; i++) {
        const int c8 = j * 9 + i, kb = c8 >> 3;
        const uint32_t a = (kb < 8 ? hw + kb * 8192 : sb + wg * 8192) + (w4 * 16 + g) * 128 + (((c8 & 7) ^ g) << 4) + q * 4;
        xr[2 * i] = lds32(a); xr[2 * i + 1] = lds32(a + 1024);
      }
      sums(6);
      asm volatile("fence.proxy.async.shared::cta;" ::: "memory");
      bar_arrive(NB_XDONE + wg, 160);
      sums(7);
      if (STX) STAMP(wg, 1);
#pragma unroll
      for (int e = 0; e < 2; e++) {
        const float mu = (s1[0][2 * e + 1] + s1[1][2 * e + 1]) * (1.f / kD);
        const float var = fmaxf(fmaf(-mu, mu, (s1[0][2 * e] + s1[1][2 * e]) * (1.f / kD)), 0.f);
        float sd, r;
        asm("sqrt.approx.f32 %0, %1;" : "=f"(sd) : "f"(rbf(rbf(var) + 1e-5f)));
        asm("rcp.approx.ftz.f32 %0, %1;" : "=f"(r) : "f"(rbf(sd)));
        r = rbf(0.5f * r);
        rh[e] = pack_bf16(r, r); cc[e] = pack_bf16(-mu * r, -mu * r);
      }
    }
    STAMP(wg, 2);

    auto normalise = [&](int kb) {
#pragma unroll
      for (int i = 0; i < 16; i++) asm("fma.rn.bf16x2 %0, %0, %1, %2;" : "+r"(xa[16 * kb + (i >> 3) + 2 * (i & 7)]) : "r"(rh[i >> 3]), "r"(cc[i >> 3]));
    };
    {
      float ab[36];
      float* op = prm.out + (size_t)(m * 128 + wg * 64 + w4 * 16 + g) * kD + j * 72 + q * 2;
      auto residual = [&](int i) {
#pragma unroll
        for (int e = 0; e < 2; e++) {
          uint32_t t;
          asm("fma.rn.bf16x2 %0, %1, %2, %3;" : "=r"(t) : "r"(xr[2 * i + e]), "r"(rh[e]), "r"(cc[e]));
          asm("mul.rn.bf16x2 %0, %0, %1;" : "+r"(t) : "r"(dk[i]));
          *(float2*)(op + e * 8 * kD + i * 8) = make_float2(bflo(xr[2 * i + e]) + bflo(t), bfhi(xr[2 * i + e]) + bfhi(t));
        }
      };
      const uint32_t da = sb + OFF_DUMP + wg * HS_BYTES + (w4 * 16 + g) * 16 + q * 4;
      auto dump = [&](int im) {
#pragma unroll
        for (int i = 0; i < 18; i++)
          asm volatile("st.shared.b32 [%0], %1;" ::"r"(da + (i < 16 ? 8 * im + (i >> 1) : 16 + im) * HS_LBO + (i & 1) * 128), "r"(pack_bf16(ab[2 * i], ab[2 * i + 1])) : "memory");
      };
      auto bu = [&](int kb, uint32_t off) {
        wg_fence();
#pragma unroll
        for (int kk = 0; kk < 4; kk++) { const int i = (kb * 4 + kk) * 4; wgmma_n72_rs_tb0(ab, xa[i], xa[i + 1], xa[i + 2], xa[i + 3], desc((dring + (off >> 4) + kk * 2) | DLO_K, DHI_SW128), (kb | kk) != 0); }
        wg_commit();
      };
      normalise(0);
#pragma unroll
      for (int kb = 0; kb < 9; kb++) {
        if ((kb & 3) == 0) mbar_wait(bars + 8 * (B_BU + (kb >> 2)), 0);
        bu(kb, kb < 8 ? OFF_BU0 + kb * 9216 : OFF_BU1);
        if (kb < 8) normalise(kb + 1);
      }
      wg_wait<0>();
      if (w4 == 0) { if (elect()) mbar_arrive(bars + 8 * B_RING); }
      STAMP(wg, 19);
      keep(ab);
      dump(0);
#pragma unroll
      for (int kb = 0; kb < 9; kb++) {
        if (kb == 4) mbar_wait(bars + 8 * (B_BU + 3), 0);
        bu(kb, kb < 4 ? OFF_BU1 + (kb + 1) * 9216 : OFF_BU2 + (kb - 4) * 9216);
        residual(kb);
      }
      wg_wait<0>();
      keep(ab);
      dump(1);
      bar_arrive(NB_DUMP, 352);
    }
    STAMP(wg, 3);

    float acc[64];
    {
      const uint32_t ha = hw + (threadIdx.x & 127) * 16 + wg * 7 * 8192;
      const int hstep = wg ? -8192 : 8192;
      auto glu = [&](int i) {
        return pack_bf16(fmaf(acc[32 + 2 * i], tanh_fast(acc[2 * i]), acc[32 + 2 * i]), fmaf(acc[33 + 2 * i], tanh_fast(acc[2 * i + 1]), acc[33 + 2 * i]));
      };
      auto chunk = [&](const int c, const bool last) {
        if (SKEW > 0 && wg == 1) bar_sync(NB_SKEW, 256);
#pragma unroll
        for (int kb = 0; kb < 9; kb++) {
          stage_begin();
#pragma unroll
          for (int kk = 0; kk < 4; kk++) { const int i = (kb * 4 + kk) * 4; wgmma_n128_rs_tb1(acc, xa[i], xa[i + 1], xa[i + 2], xa[i + 3], desc((dlo + kk * 128) | DLO_MN, DHI_SW128), (kb | kk) != 0); }
          if (SKEW > 0 && kb == SKEW - 1 && wg == 0) bar_arrive(NB_SKEW, 256);
          if (!last && kb == 8 && c == 5) mbar_wait(bars + 8 * B_SCAN, 0);
          stage_end(kb > 0);
          if (last && kb > 0) {
#pragma unroll
            for (int i = 4 * (kb - 1); i < 4 * kb; i++) lds128(ha + (i >> 2) * hstep + (i & 3) * 2048, xa[4 * i], xa[4 * i + 1], xa[4 * i + 2], xa[4 * i + 3]);
          }
        }
        wg_wait<0>();
        release(prev);
        keep(acc);
      };
      for (int c = 0;; c++) {
        chunk(c, false);
        if (c == 8) break;
#pragma unroll
        for (int i = 0; i < 4; i++) sts128(ha + c * hstep + i * 2048, glu(4 * i), glu(4 * i + 1), glu(4 * i + 2), glu(4 * i + 3));
        STAMP(wg, 4 + c);
      }
#pragma unroll
      for (int i = 0; i < 32; i++) lds128(ha + (i >> 2) * hstep + (i & 3) * 2048, xa[4 * i], xa[4 * i + 1], xa[4 * i + 2], xa[4 * i + 3]);
#pragma unroll
      for (int i = 0; i < 16; i++) xa[128 + i] = glu(i);
      asm volatile("fence.proxy.async.shared::cta;" ::: "memory");
      bar_arrive(NB_HFREE, 288);
    }
    STAMP(wg, 13);

    const uint32_t dhs = (((sb + OFF_HS + wg * HS_BYTES) & 0x3FFFF) >> 4) | DLO_HS;
    const int rp = (g >> 2) + 2 * (g & 3);
    const uint32_t so = w4 * 2048 + rp * 128 + (q & 1) * 8, sx = ((q >> 1) ^ rp) << 4;
    const uint32_t rcv = sb + OFF_STG + wg * 32768 + 16384 + w4 * 2048 + lane * 16;
    auto staged = [&]() {
      asm volatile("fence.proxy.async.shared::cta;" ::: "memory");
      __syncwarp();
      if (elect()) mbar_arrive(bars + 8 * (B_SFULL + wg));
    };
    auto half_tile = [&](const bool first, const int kind) {
      float a2[32];
      if (SKEWB > 0 && wg == 1) bar_sync(NB_SKEW, 256);
      const uint32_t ph0 = ph;
      uint32_t d4;
#pragma unroll
      for (int kp = 0; kp < 5; kp++) {
        if (kp == 4) nst = NST + 1;
        stage_begin();
#pragma unroll
        for (int kk = 0; kk < (kp < 4 ? 8 : 4); kk++) { const int i = (kp * 8 + kk) * 4; wgmma_n64_rs_tb1(a2, xa[i], xa[i + 1], xa[i + 2], xa[i + 3], desc((dlo + kk * 128) | DLO_MN, DHI_SW128), (kp | kk) != 0); }
        if (SKEWB > 0 && kp == 1 && wg == 0) bar_arrive(NB_SKEW, 256);
        d4 = dlo;
        stage_end(kp > 0);
        if (kp == 0 && !first) staged();
      }
      if (first) mbar_wait(bars + 8 * B_HSFULL, 0);
      stage_begin();
#pragma unroll
      for (int kk = 0; kk < 8; kk++) wgmma_n64_ss_tb0(a2, desc(dhs + kk * (2 * HS_LBO >> 4), DHI_NONE), desc((dlo + (kk >> 2) * 512 + (kk & 3) * 2) | DLO_K, DHI_SW128), 1);
      wgmma_n64_ss_tb0(a2, desc(dhs + 8 * (2 * HS_LBO >> 4), DHI_NONE), desc((d4 + 512) | ((1024 >> 4) << 16), DHI_NONE), 1);
      wg_commit();
      if (!first) {
        if (kind == 1) mbar_wait(bars + 8 * (B_EMPTY + 3 + wg), ph0);
        if (kind == 2) { mbar_wait(bars + 8 * (B_SFREE + wg), 1); mbar_wait(bars + 8 * (B_RFULL + wg), 1); }
      }
      wg_wait<0>();
      release(prev); release(s); advance();
      keep(a2);
      if (!first && kind >= 2) {
#pragma unroll
        for (int i = 0; i < 4; i++) {
          uint32_t v[4];
          lds128(rcv + (kind & 1) * 8192 + i * 512, v[0], v[1], v[2], v[3]);
#pragma unroll
          for (int e = 0; e < 4; e++) { a2[8 * i + 2 * e] += bflo(v[e]); a2[8 * i + 2 * e + 1] += bfhi(v[e]); }
        }
        __syncwarp();
      }
      const uint32_t stg = (!first && kind == 1 ? sb + (3 + wg) * SLOT : sb + OFF_STG + wg * 32768 + (kind == 3 ? 16384 : 0)) + so;
#pragma unroll
      for (int i = 0; i < 8; i++) {
        const uint32_t a = stg + (i >> 2) * 8192 + (sx ^ ((i & 3) << 5));
        sts64f(a, a2[4 * i], a2[4 * i + 1]);
        sts64f(a + 1024, a2[4 * i + 2], a2[4 * i + 3]);
      }
      STAMP(wg, first ? 14 : kind == 2 ? 12 : 18);
    };
    if (rank) half_tile(true, 0);
    for (int t = 0; t < 4 - (SPLIT & rank); t++) {
      if (SKEWB > 0 && wg == 1) bar_sync(NB_SKEW, 256);
#pragma unroll
      for (int kb = 0; kb < 9; kb++) {
        if (kb == 4) nst = NST + 1;
        stage_begin();
#pragma unroll
        for (int kk = 0; kk < 4; kk++) { const int i = (kb * 4 + kk) * 4; wgmma_n128_rs_tb1(acc, xa[i], xa[i + 1], xa[i + 2], xa[i + 3], desc((dlo + kk * 128) | DLO_MN, DHI_SW128), (kb | kk) != 0); }
        if (SKEWB > 0 && kb == SKEWB - 1 && wg == 0) bar_arrive(NB_SKEW, 256);
        stage_end(kb > 0);
        if (kb == 0 && t + rank > 0) staged();
      }
      if (t == 0) mbar_wait(bars + 8 * B_HSFULL, 0);
      stage_begin();
#pragma unroll
      for (int kk = 0; kk < 4; kk++) wgmma_n128_ss_tb0(acc, desc(dhs + kk * (2 * HS_LBO >> 4), DHI_NONE), desc((dlo + kk * 2) | DLO_K, DHI_SW128), 1);
      stage_end(true);
      stage_begin();
#pragma unroll
      for (int kk = 0; kk < 4; kk++) wgmma_n128_ss_tb0(acc, desc(dhs + (4 + kk) * (2 * HS_LBO >> 4), DHI_NONE), desc((dlo + kk * 2) | DLO_K, DHI_SW128), 1);
      const int s_im = s;
      advance();
      stage_begin();
      wgmma_n128_ss_tb0(acc, desc(dhs + 8 * (2 * HS_LBO >> 4), DHI_NONE), desc(dlo | ((2048 >> 4) << 16), DHI_NONE), 1);
      stage_end(true);
      if (t + rank > 0) mbar_wait(bars + 8 * (B_SFREE + wg), (t + rank - 1) & 1);
      if (t & 1) mbar_wait(bars + 8 * (B_RFULL + wg), t >> 1);
      wg_wait<0>();
      release(s_im); release(prev);
      keep(acc);
      if (t & 1) {
        const uint32_t stg = sb + OFF_STG + wg * 32768 + so;
#pragma unroll
        for (int hh = 0; hh < 2; hh++) {
#pragma unroll
          for (int i = 4 * hh; i < 4 * hh + 4; i++) {
            uint32_t v[4];
            lds128(rcv + hh * 8192 + (i & 3) * 512, v[0], v[1], v[2], v[3]);
#pragma unroll
            for (int e = 0; e < 4; e++) { acc[8 * i + 2 * e] += bflo(v[e]); acc[8 * i + 2 * e + 1] += bfhi(v[e]); }
          }
          __syncwarp();
#pragma unroll
          for (int i = 8 * hh; i < 8 * hh + 8; i++) {
            const uint32_t a = stg + (i >> 2) * 8192 + (sx ^ ((i & 3) << 5));
            sts64f(a, acc[4 * i], acc[4 * i + 1]);
            sts64f(a + 1024, acc[4 * i + 2], acc[4 * i + 3]);
          }
        }
      } else {
#pragma unroll
        for (int i = 0; i < 8; i++)
          sts128(rcv - 16384 + (i >> 2) * 8192 + (i & 3) * 512, pack_bf16(acc[8 * i], acc[8 * i + 1]), pack_bf16(acc[8 * i + 2], acc[8 * i + 3]),
                 pack_bf16(acc[8 * i + 4], acc[8 * i + 5]), pack_bf16(acc[8 * i + 6], acc[8 * i + 7]));
      }
      STAMP(wg, 14 + t + rank);
    }
    if (SPLIT || !rank) {
#pragma unroll 1
      for (int kind = 1 + rank; kind < 2 + 2 * rank; kind++) half_tile(false, kind);
    }
    staged();
    if (w4 == 0) STAMP_DUMP(wg);
  }
}

typedef CUresult (*EncodeFn)(CUtensorMap*, CUtensorMapDataType, cuuint32_t, void*, const cuuint64_t*, const cuuint64_t*, const cuuint32_t*,
                             const cuuint32_t*, CUtensorMapInterleave, CUtensorMapSwizzle, CUtensorMapL2promotion, CUtensorMapFloatOOBfill);

void map2d(EncodeFn enc, CUtensorMap* tm, const void* p, uint64_t cols, uint64_t rows, uint32_t bc, uint32_t br, CUtensorMapSwizzle sw) {
  cuuint64_t gd[2] = {cols, rows}, gs[1] = {cols * 2};
  cuuint32_t bd[2] = {bc, br}, es[2] = {1, 1};
  enc(tm, CU_TENSOR_MAP_DATA_TYPE_BFLOAT16, 2, (void*)p, gd, gs, bd, es, CU_TENSOR_MAP_INTERLEAVE_NONE, sw,
      sw == CU_TENSOR_MAP_SWIZZLE_128B ? CU_TENSOR_MAP_L2_PROMOTION_L2_128B : CU_TENSOR_MAP_L2_PROMOTION_NONE, CU_TENSOR_MAP_FLOAT_OOB_FILL_NONE);
}

}

extern "C" void kernel_launch(void* const* d_in, const int* in_sizes, int n_in, void* d_out, int out_size) {
  (void)in_sizes; (void)n_in; (void)out_size;
  static EncodeFn enc = nullptr;
  if (!enc) {
    cudaDriverEntryPointQueryResult qr;
    cudaGetDriverEntryPoint("cuTensorMapEncodeTiled", (void**)&enc, cudaEnableDefault, &qr);
    cudaFuncSetAttribute(fused_kernel, cudaFuncAttributeMaxDynamicSharedMemorySize, SMEM_BYTES);
  }
  Params prm;
  const CUtensorMapSwizzle S128 = CU_TENSOR_MAP_SWIZZLE_128B;
  map2d(enc, &prm.tx, d_in[0], kD, kS, 64, 64, S128);
  map2d(enc, &prm.tBre, d_in[3], kD, 576, 64, 72, S128);
  map2d(enc, &prm.tBim, d_in[4], kD, 576, 64, 72, S128);
  map2d(enc, &prm.tCre, d_in[5], 576, kD, 64, 64, S128);
  map2d(enc, &prm.tCim, d_in[6], 576, kD, 64, 64, S128);
  map2d(enc, &prm.tCre8, d_in[5], 576, kD, 8, 64, CU_TENSOR_MAP_SWIZZLE_NONE);
  map2d(enc, &prm.tCim8, d_in[6], 576, kD, 8, 64, CU_TENSOR_MAP_SWIZZLE_NONE);
  map2d(enc, &prm.tWg, d_in[10], kF, kD, 64, 64, S128);
  map2d(enc, &prm.tWu, d_in[11], kF, kD, 64, 64, S128);
  map2d(enc, &prm.tWd, d_in[12], kD, kF, 64, 64, S128);
  {
    cuuint64_t gd[4] = {kD, 2, 4, kS / 8}, gs[3] = {4 * kD * 4, kD * 4, 8 * kD * 4};
    cuuint32_t bd[4] = {32, 2, 4, 8}, es[4] = {1, 1, 1, 1};
    enc(&prm.tOut, CU_TENSOR_MAP_DATA_TYPE_FLOAT32, 4, d_out, gd, gs, bd, es, CU_TENSOR_MAP_INTERLEAVE_NONE, S128, CU_TENSOR_MAP_L2_PROMOTION_NONE,
        CU_TENSOR_MAP_FLOAT_OOB_FILL_NONE);
  }
  prm.x = (const __nv_bfloat16*)d_in[0];
  prm.lre = (const __nv_bfloat16*)d_in[1];
  prm.lim = (const __nv_bfloat16*)d_in[2];
  prm.bre = (const __nv_bfloat16*)d_in[3];
  prm.bim = (const __nv_bfloat16*)d_in[4];
  prm.cre = (const __nv_bfloat16*)d_in[5];
  prm.cim = (const __nv_bfloat16*)d_in[6];
  prm.wg = (const __nv_bfloat16*)d_in[10];
  prm.wu = (const __nv_bfloat16*)d_in[11];
  prm.wd = (const __nv_bfloat16*)d_in[12];
  prm.ldt = (const __nv_bfloat16*)d_in[7];
  prm.dskip = (const __nv_bfloat16*)d_in[8];
  prm.out = (float*)d_out;

  fused_kernel<<<128, 384, SMEM_BYTES, cudaStreamPerThread>>>(prm);
}
```

```cpp
#include <cuda_runtime.h>
#include <cuda.h>
#include <cuda_bf16.h>
#include <stdint.h>

namespace {

#define PACE 1
#define PACEP 100
#define XMODE 0
#define NOPF 0
#define PFD 12
#define XPF 0
#define HINT 0
#define PEEL 0
#define GRP 1
#define SPLIT 1
#define STX 0
#define BEARLY 0
#define SKEW 3
#define SKEWB 4

constexpr int kS = 2048, kD = 576, kF = 4608;
constexpr int NST = 6;
constexpr uint32_t SLOT = 16384;
constexpr uint32_t OFF_H = NST * SLOT;
constexpr uint32_t HS_LBO = 1040;
constexpr uint32_t HS_BYTES = 18 * HS_LBO;
constexpr uint32_t OFF_DUMP = OFF_H + 65536 - HS_BYTES;
constexpr uint32_t OFF_STG = OFF_H + SLOT;
constexpr uint32_t OFF_HS = OFF_STG + 65536;
constexpr uint32_t OFF_BAR = OFF_H + 131072;
constexpr uint32_t OFF_CONST = OFF_BAR + 384;
constexpr uint32_t SMEM_BYTES = OFF_CONST + 4 * 576 + 384;
static_assert(SMEM_BYTES <= 232448 && OFF_HS + 2 * HS_BYTES <= OFF_BAR, "smem");

enum { B_FULL = 0, B_EMPTY = NST + 1, B_X = 2 * NST + 2, B_X8 = B_X + 8, B_BU  , B_RING = B_BU + 4, B_SCAN, B_HFREE, B_HSFULL, B_SFULL,
       B_SFREE = B_SFULL + 2, B_RFULL = B_SFREE + 2, B_RFREE = B_RFULL + 2, B_COUNT = B_RFREE + 2 };
static_assert(B_COUNT * 8 <= 384, "barriers");
enum { NB_SKEW = 1, NB_XDONE = 2  , NB_SCAN = 4, NB_DUMP = 5, NB_HFREE = 6, NB_STATS = 7 };
constexpr uint32_t OFF_BU0 = SLOT, OFF_BU1 = OFF_H, OFF_BU2 = OFF_H + 65536 + 19456;
static_assert(OFF_BU1 + 5 * 9216 <= OFF_DUMP && OFF_BU2 >= OFF_DUMP + 2 * HS_BYTES && OFF_BU2 + 5 * 9216 <= OFF_BAR, "Bu tiles");

struct __align__(64) Params {
  CUtensorMap tx, tBre, tBim, tWg, tWu, tWd, tCre, tCim, tCre8, tCim8, tOut;
  const __nv_bfloat16 *x, *lre, *lim, *bre, *bim, *cre, *cim, *ldt, *dskip, *wg, *wu, *wd;
  float* out;
};

__device__ unsigned g_epoch[128];
__device__ unsigned g_ready[16];
__device__ __align__(256) uint2 g_S[2][16][8][96];
__device__ __align__(128) uint8_t g_hs[128][2 * HS_BYTES];
#define STAMP(role, i)
#define STAMPP(i)
#define STAMP_DUMP(role)

__device__ __forceinline__ void wgmma_n72_rs_tb0(float (&d)[36], uint32_t a0, uint32_t a1, uint32_t a2, uint32_t a3, uint64_t db, int scale_d) {
  asm volatile("{\n.reg .pred p;\nsetp.ne.b32 p, %41, 0;\n"
    "wgmma.mma_async.sync.aligned.m64n72k16.f32.bf16.bf16 {"
    "%0, %1, %2, %3, %4, %5, %6, %7, %8, %9, %10, %11, %12, %13, %14, %15, "
    "%16, %17, %18, %19, %20, %21, %22, %23, %24, %25, %26, %27, %28, %29, %30, %31, "
    "%32, %33, %34, %35"
    "}, {%36, %37, %38, %39}, %40, p, 1, 1, 0;\n}\n"
    : "+f"(d[0]), "+f"(d[1]), "+f"(d[2]), "+f"(d[3]), "+f"(d[4]), "+f"(d[5]), "+f"(d[6]), "+f"(d[7]),
      "+f"(d[8]), "+f"(d[9]), "+f"(d[10]), "+f"(d[11]), "+f"(d[12]), "+f"(d[13]), "+f"(d[14]), "+f"(d[15]),
      "+f"(d[16]), "+f"(d[17]), "+f"(d[18]), "+f"(d[19]), "+f"(d[20]), "+f"(d[21]), "+f"(d[22]), "+f"(d[23]),
      "+f"(d[24]), "+f"(d[25]), "+f"(d[26]), "+f"(d[27]), "+f"(d[28]), "+f"(d[29]), "+f"(d[30]), "+f"(d[31]),
      "+f"(d[32]), "+f"(d[33]), "+f"(d[34]), "+f"(d[35])
    : "r"(a0), "r"(a1), "r"(a2), "r"(a3), "l"(db), "r"(scale_d));
}
__device__ __forceinline__ void wgmma_n128_rs_tb1(float (&d)[64], uint32_t a0, uint32_t a1, uint32_t a2, uint32_t a3, uint64_t db, int scale_d) {
  asm volatile("{\n.reg .pred p;\nsetp.ne.b32 p, %69, 0;\n"
    "wgmma.mma_async.sync.aligned.m64n128k16.f32.bf16.bf16 {"
    "%0, %1, %2, %3, %4, %5, %6, %7, %8, %9, %10, %11, %12, %13, %14, %15, "
    "%16, %17, %18, %19, %20, %21, %22, %23, %24, %25, %26, %27, %28, %29, %30, %31, "
    "%32, %33, %34, %35, %36, %37, %38, %39, %40, %41, %42, %43, %44, %45, %46, %47, "
    "%48, %49, %50, %51, %52, %53, %54, %55, %56, %57, %58, %59, %60, %61, %62, %63"
    "}, {%64, %65, %66, %67}, %68, p, 1, 1, 1;\n}\n"
    : "+f"(d[0]), "+f"(d[1]), "+f"(d[2]), "+f"(d[3]), "+f"(d[4]), "+f"(d[5]), "+f"(d[6]), "+f"(d[7]),
      "+f"(d[8]), "+f"(d[9]), "+f"(d[10]), "+f"(d[11]), "+f"(d[12]), "+f"(d[13]), "+f"(d[14]), "+f"(d[15]),
      "+f"(d[16]), "+f"(d[17]), "+f"(d[18]), "+f"(d[19]), "+f"(d[20]), "+f"(d[21]), "+f"(d[22]), "+f"(d[23]),
      "+f"(d[24]), "+f"(d[25]), "+f"(d[26]), "+f"(d[27]), "+f"(d[28]), "+f"(d[29]), "+f"(d[30]), "+f"(d[31]),
      "+f"(d[32]), "+f"(d[33]), "+f"(d[34]), "+f"(d[35]), "+f"(d[36]), "+f"(d[37]), "+f"(d[38]), "+f"(d[39]),
      "+f"(d[40]), "+f"(d[41]), "+f"(d[42]), "+f"(d[43]), "+f"(d[44]), "+f"(d[45]), "+f"(d[46]), "+f"(d[47]),
      "+f"(d[48]), "+f"(d[49]), "+f"(d[50]), "+f"(d[51]), "+f"(d[52]), "+f"(d[53]), "+f"(d[54]), "+f"(d[55]),
      "+f"(d[56]), "+f"(d[57]), "+f"(d[58]), "+f"(d[59]), "+f"(d[60]), "+f"(d[61]), "+f"(d[62]), "+f"(d[63])
    : "r"(a0), "r"(a1), "r"(a2), "r"(a3), "l"(db), "r"(scale_d));
}
__device__ __forceinline__ void wgmma_n128_ss_tb0(float (&d)[64], uint64_t da, uint64_t db, int scale_d) {
  asm volatile("{\n.reg .pred p;\nsetp.ne.b32 p, %66, 0;\n"
    "wgmma.mma_async.sync.aligned.m64n128k16.f32.bf16.bf16 {"
    "%0, %1, %2, %3, %4, %5, %6, %7, %8, %9, %10, %11, %12, %13, %14, %15, "
    "%16, %17, %18, %19, %20, %21, %22, %23, %24, %25, %26, %27, %28, %29, %30, %31, "
    "%32, %33, %34, %35, %36, %37, %38, %39, %40, %41, %42, %43, %44, %45, %46, %47, "
    "%48, %49, %50, %51, %52, %53, %54, %55, %56, %57, %58, %59, %60, %61, %62, %63"
    "}, %64, %65, p, 1, 1, 0, 0;\n}\n"
    : "+f"(d[0]), "+f"(d[1]), "+f"(d[2]), "+f"(d[3]), "+f"(d[4]), "+f"(d[5]), "+f"(d[6]), "+f"(d[7]),
      "+f"(d[8]), "+f"(d[9]), "+f"(d[10]), "+f"(d[11]), "+f"(d[12]), "+f"(d[13]), "+f"(d[14]), "+f"(d[15]),
      "+f"(d[16]), "+f"(d[17]), "+f"(d[18]), "+f"(d[19]), "+f"(d[20]), "+f"(d[21]), "+f"(d[22]), "+f"(d[23]),
      "+f"(d[24]), "+f"(d[25]), "+f"(d[26]), "+f"(d[27]), "+f"(d[28]), "+f"(d[29]), "+f"(d[30]), "+f"(d[31]),
      "+f"(d[32]), "+f"(d[33]), "+f"(d[34]), "+f"(d[35]), "+f"(d[36]), "+f"(d[37]), "+f"(d[38]), "+f"(d[39]),
      "+f"(d[40]), "+f"(d[41]), "+f"(d[42]), "+f"(d[43]), "+f"(d[44]), "+f"(d[45]), "+f"(d[46]), "+f"(d[47]),
      "+f"(d[48]), "+f"(d[49]), "+f"(d[50]), "+f"(d[51]), "+f"(d[52]), "+f"(d[53]), "+f"(d[54]), "+f"(d[55]),
      "+f"(d[56]), "+f"(d[57]), "+f"(d[58]), "+f"(d[59]), "+f"(d[60]), "+f"(d[61]), "+f"(d[62]), "+f"(d[63])
    : "l"(da), "l"(db), "r"(scale_d));
}
__device__ __forceinline__ void wgmma_n64_rs_tb1(float (&d)[32], uint32_t a0, uint32_t a1, uint32_t a2, uint32_t a3, uint64_t db, int scale_d) {
  asm volatile("{\n.reg .pred p;\nsetp.ne.b32 p, %37, 0;\n"
    "wgmma.mma_async.sync.aligned.m64n64k16.f32.bf16.bf16 {"
    "%0, %1, %2, %3, %4, %5, %6, %7, %8, %9, %10, %11, %12, %13, %14, %15, "
    "%16, %17, %18, %19, %20, %21, %22, %23, %24, %25, %26, %27, %28, %29, %30, %31"
    "}, {%32, %33, %34, %35}, %36, p, 1, 1, 1;\n}\n"
    : "+f"(d[0]), "+f"(d[1]), "+f"(d[2]), "+f"(d[3]), "+f"(d[4]), "+f"(d[5]), "+f"(d[6]), "+f"(d[7]),
      "+f"(d[8]), "+f"(d[9]), "+f"(d[10]), "+f"(d[11]), "+f"(d[12]), "+f"(d[13]), "+f"(d[14]), "+f"(d[15]),
      "+f"(d[16]), "+f"(d[17]), "+f"(d[18]), "+f"(d[19]), "+f"(d[20]), "+f"(d[21]), "+f"(d[22]), "+f"(d[23]),
      "+f"(d[24]), "+f"(d[25]), "+f"(d[26]), "+f"(d[27]), "+f"(d[28]), "+f"(d[29]), "+f"(d[30]), "+f"(d[31])
    : "r"(a0), "r"(a1), "r"(a2), "r"(a3), "l"(db), "r"(scale_d));
}
__device__ __forceinline__ void wgmma_n64_ss_tb0(float (&d)[32], uint64_t da, uint64_t db, int scale_d) {
  asm volatile("{\n.reg .pred p;\nsetp.ne.b32 p, %34, 0;\n"
    "wgmma.mma_async.sync.aligned.m64n64k16.f32.bf16.bf16 {"
    "%0, %1, %2, %3, %4, %5, %6, %7, %8, %9, %10, %11, %12, %13, %14, %15, "
    "%16, %17, %18, %19, %20, %21, %22, %23, %24, %25, %26, %27, %28, %29, %30, %31"
    "}, %32, %33, p, 1, 1, 0, 0;\n}\n"
    : "+f"(d[0]), "+f"(d[1]), "+f"(d[2]), "+f"(d[3]), "+f"(d[4]), "+f"(d[5]), "+f"(d[6]), "+f"(d[7]),
      "+f"(d[8]), "+f"(d[9]), "+f"(d[10]), "+f"(d[11]), "+f"(d[12]), "+f"(d[13]), "+f"(d[14]), "+f"(d[15]),
      "+f"(d[16]), "+f"(d[17]), "+f"(d[18]), "+f"(d[19]), "+f"(d[20]), "+f"(d[21]), "+f"(d[22]), "+f"(d[23]),
      "+f"(d[24]), "+f"(d[25]), "+f"(d[26]), "+f"(d[27]), "+f"(d[28]), "+f"(d[29]), "+f"(d[30]), "+f"(d[31])
    : "l"(da), "l"(db), "r"(scale_d));
}

__device__ __forceinline__ bool elect() {
  uint32_t p;
  asm volatile("{.reg .pred q; elect.sync _|q, 0xffffffff; selp.u32 %0,1,0,q;}" : "=r"(p));
  return p;
}
__device__ __forceinline__ void mbar_init(uint32_t bar, uint32_t cnt) { asm volatile("mbarrier.init.shared::cta.b64 [%0], %1;" ::"r"(bar), "r"(cnt) : "memory"); }
__device__ __forceinline__ void mbar_expect(uint32_t bar, uint32_t bytes) { asm volatile("mbarrier.arrive.expect_tx.shared::cta.b64 _, [%0], %1;" ::"r"(bar), "r"(bytes) : "memory"); }
__device__ __forceinline__ void mbar_arrive(uint32_t bar) { asm volatile("mbarrier.arrive.shared::cta.b64 _, [%0];" ::"r"(bar) : "memory"); }
__device__ __forceinline__ void mbar_arrive_cta(uint32_t bar, uint32_t cta) {
  asm volatile("{.reg .b32 ra; mapa.shared::cluster.u32 ra, %0, %1; mbarrier.arrive.shared::cluster.b64 _, [ra];}" ::"r"(bar), "r"(cta) : "memory");
}
__device__ __forceinline__ void mbar_wait(uint32_t bar, uint32_t parity) {
  asm volatile(
      "{\n.reg .pred p;\n.reg .u32 c, t;\n"
      "mbarrier.try_wait.parity.shared::cta.b64 p, [%0], %1;\n@p bra DONE;\n"
      "mov.u32 c, %%clock;\n"
      "LAB_WAIT:\nmbarrier.try_wait.parity.shared::cta.b64 p, [%0], %1;\n@p bra DONE;\n"
      "mov.u32 t, %%clock;\nsub.u32 t, t, c;\nsetp.lt.u32 p, t, 0x40000000;\n@p bra LAB_WAIT;\ntrap;\nDONE:\n}" ::"r"(bar), "r"(parity) : "memory");
}
__device__ __forceinline__ void bar_sync(int id, int n) { asm volatile("bar.sync %0, %1;" ::"r"(id), "r"(n) : "memory"); }
__device__ __forceinline__ void bar_arrive(int id, int n) { asm volatile("bar.arrive %0, %1;" ::"r"(id), "r"(n) : "memory"); }
__device__ __forceinline__ void wg_fence() { asm volatile("wgmma.fence.sync.aligned;" ::: "memory"); }
__device__ __forceinline__ void wg_commit() { asm volatile("wgmma.commit_group.sync.aligned;" ::: "memory"); }
template <int N> __device__ __forceinline__ void wg_wait() { asm volatile("wgmma.wait_group.sync.aligned %0;" ::"n"(N) : "memory"); }
__device__ __forceinline__ void tma2d(uint32_t dst, const CUtensorMap* tm, uint32_t bar, int c0, int c1) {
  asm volatile("cp.async.bulk.tensor.2d.shared::cluster.global.mbarrier::complete_tx::bytes [%0], [%1,{%3,%4}], [%2];" ::"r"(dst), "l"(tm), "r"(bar), "r"(c0), "r"(c1) : "memory");
}
__device__ __forceinline__ void tma2d_mc(uint32_t dst, const CUtensorMap* tm, uint32_t bar, int c0, int c1) {
  asm volatile("cp.async.bulk.tensor.2d.shared::cluster.global.mbarrier::complete_tx::bytes.multicast::cluster [%0], [%1,{%3,%4}], [%2], %5;" ::"r"(dst), "l"(tm), "r"(bar), "r"(c0), "r"(c1), "h"((uint16_t)3) : "memory");
}
__device__ __forceinline__ void l2_prefetch(const void* p, uint32_t bytes) {
  asm volatile("cp.async.bulk.prefetch.L2.global [%0], %1;" ::"l"(p), "r"(bytes) : "memory");
}
__device__ __forceinline__ void l2_prefetch_line(const void* p) { asm volatile("prefetch.global.L2 [%0];" ::"l"(p)); }
__device__ __forceinline__ void tma_prefetch2d(const CUtensorMap* tm, int c0, int c1) {
  asm volatile("cp.async.bulk.prefetch.tensor.2d.L2.global.tile [%0,{%1,%2}];" ::"l"(tm), "r"(c0), "r"(c1) : "memory");
}
__device__ __forceinline__ uint64_t desc(uint32_t lo, uint32_t hi) { return ((uint64_t)hi << 32) | lo; }
constexpr uint32_t DHI_SW128 = (1024 >> 4) | (1u << 30);
constexpr uint32_t DHI_NONE = (128 >> 4);
constexpr uint32_t DLO_HS = (HS_LBO >> 4) << 16;
constexpr uint32_t DLO_MN = (8192 >> 4) << 16;
constexpr uint32_t DLO_K = 1u << 16;
__device__ __forceinline__ float tanh_fast(float x) { float y; asm("tanh.approx.f32 %0, %1;" : "=f"(y) : "f"(x)); return y; }
__device__ __forceinline__ uint32_t pack_bf16(float lo, float hi) { uint32_t r; asm("cvt.rn.bf16x2.f32 %0, %1, %2;" : "=r"(r) : "f"(hi), "f"(lo)); return r; }
__device__ __forceinline__ float rbf(float x) { return __bfloat162float(__float2bfloat16_rn(x)); }
__device__ __forceinline__ void mma16816(float (&c)[4], uint32_t a0, uint32_t a1, uint32_t a2, uint32_t a3, uint32_t b0, uint32_t b1) {
  asm volatile("mma.sync.aligned.m16n8k16.row.col.f32.bf16.bf16.f32 {%0,%1,%2,%3}, {%4,%5,%6,%7}, {%8,%9}, {%0,%1,%2,%3};"
               : "+f"(c[0]), "+f"(c[1]), "+f"(c[2]), "+f"(c[3]) : "r"(a0), "r"(a1), "r"(a2), "r"(a3), "r"(b0), "r"(b1));
}
__device__ __forceinline__ void sts128(uint32_t a, uint32_t x, uint32_t y, uint32_t z, uint32_t w) {
  asm volatile("st.shared.v4.b32 [%0], {%1,%2,%3,%4};" ::"r"(a), "r"(x), "r"(y), "r"(z), "r"(w) : "memory");
}
__device__ __forceinline__ void sts64f(uint32_t a, float x, float y) { asm volatile("st.shared.v2.f32 [%0], {%1,%2};" ::"r"(a), "f"(x), "f"(y) : "memory"); }
__device__ __forceinline__ float2 lds64f(uint32_t a) { float2 v; asm volatile("ld.shared.v2.f32 {%0,%1}, [%2];" : "=f"(v.x), "=f"(v.y) : "r"(a) : "memory"); return v; }
__device__ __forceinline__ uint32_t lds32(uint32_t a) { uint32_t v; asm volatile("ld.shared.b32 %0, [%1];" : "=r"(v) : "r"(a) : "memory"); return v; }
__device__ __forceinline__ void lds128(uint32_t a, uint32_t& x, uint32_t& y, uint32_t& z, uint32_t& w) {
  asm volatile("ld.shared.v4.b32 {%0,%1,%2,%3}, [%4];" : "=r"(x), "=r"(y), "=r"(z), "=r"(w) : "r"(a) : "memory");
}
__device__ __forceinline__ float bflo(uint32_t v) { return __uint_as_float(v << 16); }
__device__ __forceinline__ float bfhi(uint32_t v) { return __uint_as_float(v & 0xffff0000u); }
__device__ __forceinline__ uint32_t lds32v(uint32_t a) { uint32_t v; asm volatile("ld.volatile.shared.b32 %0, [%1];" : "=r"(v) : "r"(a) : "memory"); return v; }
__device__ __forceinline__ float lds32f(uint32_t a) { float v; asm volatile("ld.shared.f32 %0, [%1];" : "=f"(v) : "r"(a) : "memory"); return v; }
template <int N> __device__ __forceinline__ void keep(float (&a)[N]) {
#pragma unroll
  for (int i = 0; i < N; i++) asm volatile("" : "+f"(a[i])::"memory");
}

__global__ void __cluster_dims__(2, 1, 1) __launch_bounds__(384, 1) fused_kernel(const __grid_constant__ Params prm) {
  extern __shared__ __align__(1024) uint8_t smem[];
  const int warp = __shfl_sync(0xffffffffu, threadIdx.x >> 5, 0);
  const uint32_t sb0 = (uint32_t)__cvta_generic_to_shared(smem);
  const int j = blockIdx.x & 7, m = blockIdx.x >> 3, rank = j & 1;
  auto smem_base = [&]() { return __shfl_sync(0xffffffffu, sb0 + (threadIdx.x & 31), 0); };
  STAMP(0, 31);

  if (XPF && threadIdx.x < 144) l2_prefetch_line((const char*)prm.x + (size_t)(m * 128 + j * 16) * 1152 + threadIdx.x * 128);
  if (threadIdx.x == 320) asm volatile("prefetch.tensormap [%0];" ::"l"(&prm.tx) : "memory");
  if (warp == 8 || warp == 9) {
    if (elect()) {
      if (warp == 8) {
#pragma unroll
        for (int i = 0; i < B_COUNT / 2; i++) mbar_init(sb0 + OFF_BAR + 8 * i, (i >= B_EMPTY && i < B_X) ? 2 : 1);
      } else {
#pragma unroll
        for (int i = B_COUNT / 2; i < B_COUNT; i++) mbar_init(sb0 + OFF_BAR + 8 * i, (i >= B_SFULL && i < B_SFULL + 2) ? 4 : i == B_RING ? 2 : 1);
        if (sb0 & 1023) __trap();
      }
      asm volatile("fence.mbarrier_init.release.cluster;" ::: "memory");
    }
    __syncwarp();
  }
  STAMPP(0);
  asm volatile("barrier.cluster.arrive.relaxed.aligned;\nbarrier.cluster.wait.aligned;" ::: "memory");
  STAMPP(1);

  if (warp == 0) {
    const uint32_t xb = sb0 + OFF_BAR;
    const bool e = elect();
    if (e) { mbar_expect(xb + 8 * B_X8, 16384); tma2d_mc(sb0 + rank * 8192, &prm.tx, xb + 8 * B_X8, 512, m * 128 + rank * 64); }
#pragma unroll
    for (int i = 0; i < 8; i++) {
      const int w = i >> 2, kb = (i & 3) * 2 + rank;
      if (e) { mbar_expect(xb + 8 * (B_X + i), 16384); tma2d_mc(sb0 + OFF_H + w * 65536 + kb * 8192, &prm.tx, xb + 8 * (B_X + i), kb * 64, m * 128 + w * 64); }
    }
    if (BEARLY) {
#pragma unroll
      for (int kb = 0; kb < 8; kb++)
        if (e) { if ((kb & 3) == 0) mbar_expect(xb + 8 * (B_BU + (kb >> 2)), 4 * 9216); tma2d(sb0 + OFF_BU0 + kb * 9216, &prm.tBre, xb + 8 * (B_BU + (kb >> 2)), kb * 64, j * 72); }
    }
    __syncwarp();
    STAMP(0, 20);
  }

  if (warp >= 8) {
    asm volatile("setmaxnreg.dec.sync.aligned.u32 24;");
    if (warp == 8) {
      const uint32_t sb = smem_base(), bars = sb + OFF_BAR;
      bool e;
      int s = 0, nst = NST; uint32_t ph = 1;
      uint32_t dst, fb;
      auto acquire = [&](uint32_t bytes) {
        mbar_wait(bars + 8 * (B_EMPTY + s), ph);
        fb = bars + 8 * (B_FULL + s); dst = sb + s * SLOT;
        e = elect();
        if (e) mbar_expect(fb, bytes);
        if (++s == nst) { s = 0; ph ^= 1; }
      };
      auto box = [&](const CUtensorMap* t, uint32_t o, int a, int b) { if (e) tma2d(dst + o, t, fb, a, b); };
      const int lane = threadIdx.x & 31;
      const char* pf = lane < 8 ? (const char*)(lane & 4 ? prm.wu : prm.wg) + ((size_t)(m * 4 + (lane & 3)) * kF + j * 576) * 2
                     : lane < 12 ? (const char*)prm.wd + (size_t)j * 576 * 1152 + (m * 324 + (lane & 3)) * 128
                                 : (const char*)(lane & 1 ? prm.cim : prm.cre) + (size_t)blockIdx.x * 5184;
      int pk = 0, pleft = 81;
      auto prefetch = [&]() {
        if (pleft > 0) {
          if (lane < 14 && !(NOPF & 2)) l2_prefetch_line(pf);
          pf += lane < 8 ? (pk == 8 ? 128 - 8 * 64 * kF * 2 : 64 * kF * 2) : lane < 12 ? 512 : 64;
          pk = pk == 8 ? 0 : pk + 1;
          pleft--;
        }
      };
      STAMPP(3);
      e = elect();
#pragma unroll 1
      for (int kb = 0; kb < (BEARLY ? 0 : 8); kb++) {
        fb = bars + 8 * (B_BU + (kb >> 2));
        if (e) { if ((kb & 3) == 0) mbar_expect(fb, 4 * 9216); tma2d(sb + OFF_BU0 + kb * 9216, &prm.tBre, fb, kb * 64, j * 72); }
      }
      STAMPP(4);
      bar_sync(NB_XDONE, 160);
      fb = bars + 8 * (B_BU + 2);
      if (e) { mbar_expect(fb, 5 * 9216); tma2d(sb + OFF_BU1, &prm.tBre, fb, 512, j * 72); }
#pragma unroll 1
      for (int kb = 0; kb < 4; kb++) if (e) tma2d(sb + OFF_BU1 + (kb + 1) * 9216, &prm.tBim, fb, kb * 64, j * 72);
      for (int i = 0; i < PFD / 2; i++) prefetch();
      bar_sync(NB_XDONE + 1, 160);
      fb = bars + 8 * (B_BU + 3);
      if (e) mbar_expect(fb, 5 * 9216);
#pragma unroll 1
      for (int kb = 4; kb < 9; kb++) if (e) tma2d(sb + OFF_BU2 + (kb - 4) * 9216, &prm.tBim, fb, kb * 64, j * 72);
      for (int i = PFD / 2; i < PFD; i++) prefetch();
      STAMPP(5);
      mbar_wait(bars + 8 * B_RING, 0);
      STAMPP(6);
      for (int c = 0; c < 9; c++) {
        const int col = j * 576 + c * 64;
#pragma unroll 1
        for (int kb = 0; kb < 9; kb++) { acquire(16384); box(&prm.tWg, 0, col, kb * 64); box(&prm.tWu, 8192, col, kb * 64); prefetch(); }
      }
      auto half_tile = [&](int n0) {
#pragma unroll 1
        for (int kp = 0; kp < 4; kp++) { acquire(16384); box(&prm.tWd, 0, n0, j * 576 + kp * 128); box(&prm.tWd, 8192, n0, j * 576 + kp * 128 + 64); }
        nst = NST + 1;
        acquire(8192 + 2048); box(&prm.tWd, 0, n0, j * 576 + 512); box(&prm.tCre8, 8192, j * 72 + 64, n0); box(&prm.tCim8, 9216, j * 72 + 64, n0);
        acquire(16384); box(&prm.tCre, 0, j * 72, n0); box(&prm.tCim, 8192, j * 72, n0);
      };
      if (rank) half_tile(512);
#pragma unroll 1
      for (int t = 0; t < 4 - (SPLIT & rank); t++) {
        const int n0 = ((rank ^ t ^ 1) & 1) * 256 + (((t >> 1) ^ (j >> 1)) & 1) * 128;
#pragma unroll 1
        for (int kb = 0; kb < 9; kb++) {
          if (kb == 4) nst = NST + 1;
          if (kb == 3 && t == 0 && rank) mbar_wait(bars + 8 * B_HFREE, 0);
          acquire(16384); box(&prm.tWd, 0, n0, j * 576 + kb * 64); box(&prm.tWd, 8192, n0 + 64, j * 576 + kb * 64);
        }
        if (t == 0) mbar_wait(bars + 8 * B_HFREE, 0);
        acquire(16384); box(&prm.tCre, 0, j * 72, n0); box(&prm.tCre, 8192, j * 72, n0 + 64);
        acquire(16384); box(&prm.tCim, 0, j * 72, n0); box(&prm.tCim, 8192, j * 72, n0 + 64);
        acquire(4096);
        box(&prm.tCre8, 0, j * 72 + 64, n0); box(&prm.tCre8, 1024, j * 72 + 64, n0 + 64);
        box(&prm.tCim8, 2048, j * 72 + 64, n0); box(&prm.tCim8, 3072, j * 72 + 64, n0 + 64);
      }
      if (!rank) half_tile(512);
      else if (SPLIT) {
#pragma unroll 1
        for (int hh = 0; hh < 2; hh++) half_tile(256 + (((j >> 1) ^ 1) & 1) * 128 + hh * 64);
      }
    } else {
      const uint32_t sb = smem_base(), bars = sb + OFF_BAR;
      const int p = min((int)threadIdx.x - 288, 71);
      if (threadIdx.x < 288 + 10) asm volatile("prefetch.tensormap [%0];" ::"l"(&prm.tBre + (threadIdx.x - 288)) : "memory");
      if (warp == 10 && !(NOPF & 1)) {
        const int l = threadIdx.x & 31;
        const char* q = (const char*)(l & 1 ? prm.bim : prm.bre) + (size_t)blockIdx.x * 5184;
        mbar_wait(bars + 8 * B_X8, 0);
#pragma unroll
        for (int i = 0; i < 3; i++) if (i * 16 + (l >> 1) < 42) l2_prefetch_line(q + min((i * 16 + (l >> 1)) * 128, 5183));
      }
      const unsigned epoch = *(volatile unsigned*)&g_epoch[blockIdx.x];
      {
        const int pg = j * 72 + p;
        const float lr = __bfloat162float(prm.lre[pg]), li = __bfloat162float(prm.lim[pg]);
        const float dt = rbf(expf(__bfloat162float(prm.ldt[pg])));
        const float ea = expf(dt * lr);
        float sn, cs;
        sincosf(dt * li, &sn, &cs);
        const float ar = ea * cs, ai = ea * sn;
        float br = ar, bi = ai;
#pragma unroll
        for (int k = 0; k < 6; k++) { const float t = br * br - bi * bi; bi = 2.f * br * bi; br = t; }
        const float nr = ar - 1.f, den = 4.f / (lr * lr + li * li);
        sts64f(sb + OFF_CONST + p * 8, ar, ai);
        sts64f(sb + OFF_CONST + 576 + p * 8, br, bi);
        sts64f(sb + OFF_CONST + 1152 + p * 8, (nr * lr + ai * li) * den, (ai * lr - nr * li) * den);
      }
      STAMP(2, 0);
      bar_sync(NB_DUMP, 352);
      {
        const int lane = threadIdx.x & 31;
        const int half = warp == 11 ? (lane >> 2) & 1 : warp - 9;
        const uint32_t cu = sb + OFF_CONST + (warp == 11 ? 32 + (lane & 3) : lane) * 16;
        uint32_t a0 = sb + OFF_DUMP + half * HS_BYTES + (warp == 11 ? 16 : lane >> 2) * HS_LBO + (lane & 3) * 4;
        asm volatile("" : "+r"(a0));
        const uint32_t di = warp == 11 ? HS_LBO : 8 * HS_LBO;
        float a[4], h[4] = {0.f, 0.f, 0.f, 0.f};
        auto ld4 = [&](uint32_t ad, float (&v)[4]) { asm volatile("ld.shared.v4.f32 {%0,%1,%2,%3}, [%4];" : "=f"(v[0]), "=f"(v[1]), "=f"(v[2]), "=f"(v[3]) : "r"(ad) : "memory"); };
        auto cfma = [&](const float (&c)[4], float r0, float i0, float r1, float i1) {
          const float n0 = fmaf(c[0], h[0], fmaf(-c[1], h[1], r0)), n1 = fmaf(c[2], h[2], fmaf(-c[3], h[3], r1));
          h[1] = fmaf(c[0], h[1], fmaf(c[1], h[0], i0)); h[3] = fmaf(c[2], h[3], fmaf(c[3], h[2], i1));
          h[0] = n0; h[2] = n1;
        };
        ld4(cu, a);
#pragma unroll 1
        for (uint32_t ad = a0; ad != a0 + 1024; ad += 64) {
          uint32_t wr[4], wi[4];
#pragma unroll
          for (int k = 0; k < 4; k++) { wr[k] = lds32(ad + k * 16); wi[k] = lds32(ad + di + k * 16); }
#pragma unroll
          for (int k = 0; k < 4; k++) cfma(a, bflo(wr[k]), bflo(wi[k]), bfhi(wr[k]), bfhi(wi[k]));
        }
        if (half == 0) sts128(cu + 1728, __float_as_uint(h[0]), __float_as_uint(h[1]), __float_as_uint(h[2]), __float_as_uint(h[3]));
        bar_sync(NB_SCAN, 96);
        if (half == 1 && m < 15) {
          float b[4], s1[4] = {h[0], h[1], h[2], h[3]};
          ld4(cu + 576, b); ld4(cu + 1728, h);
          cfma(b, s1[0], s1[1], s1[2], s1[3]);
          uint2* gp = &g_S[epoch & 1][m][j][(cu - sb - OFF_CONST) >> 3];
          asm volatile("st.relaxed.gpu.global.v2.b64 [%0], {%1,%2};" ::"l"(gp), "l"(~(((uint64_t)__float_as_uint(h[1]) << 32) | __float_as_uint(h[0]))),
                       "l"(~(((uint64_t)__float_as_uint(h[3]) << 32) | __float_as_uint(h[2]))) : "memory");
        }
        __syncwarp();
        g_S[(epoch & 1) ^ 1][m][j][p] = make_uint2(0u, 0u);
        STAMP(2, 4);
        {
          const float2 b = lds64f(sb + OFF_CONST + 576 + p * 8);
          const float br = b.x * b.x - b.y * b.y, bi = 2.f * b.x * b.y;
          float hr = 0.f, hi = 0.f;
          const uint2* sp = &g_S[epoch & 1][0][j][p];
#pragma unroll 1
          for (int left = m; left > 0; left -= 3, sp += 3 * 768) {
            uint32_t v[3][2];
            int spins = 0;
            uint32_t ok;
            do {
#pragma unroll
              for (int k = 0; k < 3; k++) {
                v[k][0] = v[k][1] = 0xffffffffu;
                if (k < left) asm volatile("ld.relaxed.gpu.global.v2.b32 {%0,%1}, [%2];" : "=r"(v[k][0]), "=r"(v[k][1]) : "l"(sp + k * 768) : "memory");
              }
              ok = min(min(min(v[0][0], v[0][1]), min(v[1][0], v[1][1])), min(v[2][0], v[2][1]));
              if (++spins > (1 << 22)) __trap();
            } while (ok == 0u);
#pragma unroll
            for (int k = 0; k < 3; k++)
              if (k < left) { const float nr = fmaf(br, hr, fmaf(-bi, hi, __uint_as_float(~v[k][0]))); hi = fmaf(br, hi, fmaf(bi, hr, __uint_as_float(~v[k][1]))); hr = nr; }
          }
          sts64f(sb + OFF_CONST + p * 8, hr, hi);
        }
        __syncwarp();
        bar_sync(NB_SCAN, 96);
        STAMP(2, 5);
        ld4(cu, h);
        uint32_t cr, ci, cn;
        {
          float b[4], s0[4];
          ld4(cu + 576, b); ld4(cu + 1728, s0);
          if (half == 1) cfma(b, s0[0], s0[1], s0[2], s0[3]);
          ld4(cu + 1152, b);
          cr = pack_bf16(b[0], b[2]); ci = pack_bf16(b[1], b[3]); cn = ci ^ 0x80008000u;
        }
        __syncwarp();
#pragma unroll 1
        for (uint32_t ad = a0; ad != a0 + 1024; ad += 32) {
          uint32_t wr[2], wi[2];
#pragma unroll
          for (int k = 0; k < 2; k++) { wr[k] = lds32(ad + k * 16); wi[k] = lds32(ad + di + k * 16); }
#pragma unroll
          for (int k = 0; k < 2; k++) {
            cfma(a, bflo(wr[k]), bflo(wi[k]), bfhi(wr[k]), bfhi(wi[k]));
            const uint32_t hr = pack_bf16(h[0], h[2]), hn = pack_bf16(-h[1], -h[3]);
            uint32_t o0, o1;
            asm("{.reg .b32 t; mul.rn.bf16x2 t, %2, %4; fma.rn.bf16x2 %0, %1, %3, t;}" : "=r"(o0) : "r"(hr), "r"(hn), "r"(cr), "r"(ci));
            asm("{.reg .b32 t; mul.rn.bf16x2 t, %1, %4; fma.rn.bf16x2 %0, %2, %3, t;}" : "=r"(o1) : "r"(hr), "r"(hn), "r"(cr), "r"(cn));
            asm volatile("st.shared.b32 [%0], %1;" ::"r"(ad + k * 16), "r"(o0) : "memory");
            asm volatile("st.shared.b32 [%0], %1;" ::"r"(ad + di + k * 16), "r"(o1) : "memory");
          }
        }
        asm volatile("fence.proxy.async.shared::cta;" ::: "memory");
      }
      STAMP(2, 6);
      bar_sync(NB_SCAN, 96);
      if (warp == 9) {
        if (elect()) {
#pragma unroll 1
          for (uint32_t o = 0; o < 2 * HS_BYTES; o += 4 * HS_LBO) {
            asm volatile("cp.async.bulk.global.shared::cta.bulk_group [%0], [%1], %2;" ::"l"(&g_hs[blockIdx.x][o]), "r"(sb + OFF_DUMP + o), "r"(4 * HS_LBO) : "memory");
            asm volatile("cp.async.bulk.commit_group;\ncp.async.bulk.wait_group.read 0;" ::: "memory");
            if (PACEP) __nanosleep(PACEP);
          }
          mbar_arrive(bars + 8 * B_SCAN);
        }
        __syncwarp();
        STAMP(2, 2);
      }
      if (warp == 9) {
        if (elect()) {
          __threadfence();
          asm volatile("red.release.gpu.global.add.u32 [%0], 1;" ::"l"(&g_ready[m]) : "memory");
          g_epoch[blockIdx.x] = epoch + 1u;
          asm volatile("cp.async.bulk.wait_group 0;" ::: "memory");
        }
        __syncwarp();
        STAMP(2, 7);
        bar_sync(NB_HFREE, 288);
        if (elect()) {
          mbar_arrive(bars + 8 * B_HFREE);
          mbar_expect(bars + 8 * B_HSFULL, 2 * HS_BYTES);
          asm volatile("cp.async.bulk.shared::cluster.global.mbarrier::complete_tx::bytes [%0], [%1], %2, [%3];" ::"r"(sb + OFF_HS),
                       "l"(&g_hs[blockIdx.x][0]), "r"(2 * HS_BYTES), "r"(bars + 8 * B_HSFULL) : "memory");
          for (int w = 0; w < 2; w++) mbar_arrive_cta(bars + 8 * (B_RFREE + w), rank ^ 1);
        }
        __syncwarp();
        STAMP_DUMP(2);
      } else {
        const int w = warp - 10;
        {
          const unsigned target = 8u * (epoch + 1u);
          int spins = 0;
          unsigned v;
          do {
            asm volatile("ld.acquire.gpu.global.u32 %0, [%1];" : "=r"(v) : "l"(&g_ready[m]) : "memory");
            if (++spins > (1 << 22)) __trap();
          } while ((int)(v - target) < 0);
          asm volatile("fence.proxy.async.global;" ::: "memory");
        }
        const uint32_t stg = sb + OFF_STG + w * 32768;
        const int nu = 5 + (SPLIT & rank);
#pragma unroll 1
        for (int u = 0; u < nu; u++) {
          const int t = u - rank;
          if (t == 0 || t == 2) {
            if (elect()) mbar_expect(bars + 8 * (B_RFULL + w), 16384);
            mbar_wait(bars + 8 * (B_SFULL + w), u & 1);
            mbar_wait(bars + 8 * (B_RFREE + w), t >> 1);
            if (elect())
              asm volatile("{.reg .b32 ra, rb; mapa.shared::cluster.u32 ra, %0, %3; mapa.shared::cluster.u32 rb, %2, %3;\n"
                           "cp.async.bulk.shared::cluster.shared::cta.mbarrier::complete_tx::bytes [ra], [%1], 16384, [rb];}" ::"r"(stg + 16384),
                           "r"(stg), "r"(bars + 8 * (B_RFULL + w)), "r"(rank ^ 1) : "memory");
            mbar_wait(bars + 8 * (B_RFULL + w), t >> 1);
            if (elect()) mbar_arrive_cta(bars + 8 * (B_SFREE + w), rank ^ 1);
          } else {
            mbar_wait(bars + 8 * (B_SFULL + w), u & 1);
            const bool d = u == (rank ? 0 : 4), hf = SPLIT && rank && u >= 4;
            const int n0 = d ? 512 : rank * 256 + (((min(t, 3) >> 1) ^ (j >> 1)) & 1) * 128 + (u == 5 ? 64 : 0);
            const uint32_t src = d && !rank ? sb + (3 + w) * SLOT : stg + (u == 5 ? 16384 : 0);
            if (elect()) {
#pragma unroll 1
              for (int b = 0; b < (d || hf ? 2 : 4); b++) {
                asm volatile("cp.reduce.async.bulk.tensor.4d.global.shared::cta.add.tile.bulk_group [%0, {%1,%2,%2,%3}], [%4];" ::"l"(&prm.tOut), "r"(n0 + b * 32), "r"(0),
                             "r"(m * 16 + w * 8), "r"(src + b * 8192) : "memory");
                asm volatile("cp.async.bulk.commit_group;" ::: "memory");
                if (PACE && u < nu - 1) { asm volatile("cp.async.bulk.wait_group.read 0;" ::: "memory"); if (PACE > 1) __nanosleep(PACE); }
              }
              if (u < 3) {
                asm volatile("cp.async.bulk.wait_group.read 0;" ::: "memory");
                mbar_arrive(bars + 8 * (B_SFREE + w));
                if (t == 1) mbar_arrive_cta(bars + 8 * (B_RFREE + w), rank ^ 1);
              }
              if (u == nu - 1) asm volatile("cp.async.bulk.wait_group.read 0;" ::: "memory");
            }
          }
          __syncwarp();
        }
      }
    }
  } else {
    asm volatile("setmaxnreg.inc.sync.aligned.u32 240;");
    const uint32_t sb = smem_base(), bars = sb + OFF_BAR;
    const int wg = warp >> 2, w4 = warp & 3;
    const int lane = threadIdx.x & 31, g = lane >> 2, q = lane & 3;
    const uint32_t hw = sb + OFF_H + wg * 65536;
    STAMP(wg, 0);

    int s = 0, nst = NST; uint32_t ph = 0;
    auto release = [&](int st) { if (w4 == 0) { if (elect()) mbar_arrive(bars + 8 * (B_EMPTY + st)); } };
    const uint32_t dring = (sb & 0x3FFFF) >> 4;
    uint32_t dlo; int prev = 0;
    auto stage_begin = [&]() { mbar_wait(bars + 8 * (B_FULL + s), ph); dlo = dring + s * (SLOT >> 4); wg_fence(); };
    auto advance = [&]() { if (++s == nst) { s = 0; ph ^= 1; } };
    auto stage_end = [&](bool rel) {
      wg_commit();
      if (rel) { wg_wait<1>(); release(prev); }
      prev = s;
      advance();
    };

    uint32_t xa[144];
    uint32_t xr[18], dk[9];
    uint32_t rh[2], cc[2];
#pragma unroll
    for (int i = 0; i < 9; i++) {
      dk[i] = __ldg((const uint32_t*)(prm.dskip + j * 72 + i * 8 + q * 2));
      asm("add.rn.bf16x2 %0, %0, %0;" : "+r"(dk[i]));
    }
    {
      const int r = w4 * 16 + (lane & 7) + ((lane >> 3) & 1) * 8;
      const uint32_t ro = r * 128, cx = ((lane >> 4) ^ (lane & 7)) << 4;
      float s1[2][4] = {};
      auto load = [&](int kb, uint32_t base) {
#pragma unroll
        for (int kk = 0; kk < 4; kk++) {
          const int i = (kb * 4 + kk) * 4;
          asm volatile("ldmatrix.sync.aligned.m8n8.x4.shared.b16 {%0,%1,%2,%3}, [%4];"
                       : "=r"(xa[i]), "=r"(xa[i + 1]), "=r"(xa[i + 2]), "=r"(xa[i + 3]) : "r"(base + ro + (cx ^ (kk << 5))) : "memory");
        }
      };
      const uint32_t b0 = (g & 1) ? 0u : 0x3f803f80u, b1 = b0 ^ 0x3f803f80u;
      auto sums = [&](int kb) {
#pragma unroll
        for (int kk = 0; kk < 4; kk += GRP) {
          const int i = (kb * 4 + kk) * 4;
          uint32_t a[4];
#pragma unroll
          for (int e = 0; e < 2; e++) {
            asm("mul.rn.bf16x2 %0, %1, %1;" : "=r"(a[e]) : "r"(xa[i + e]));
            asm("add.rn.bf16x2 %0, %1, %2;" : "=r"(a[2 + e]) : "r"(xa[i + e]), "r"(xa[i + 2 + e]));
            asm("fma.rn.bf16x2 %0, %1, %1, %0;" : "+r"(a[e]) : "r"(xa[i + 2 + e]));
            if (GRP == 2) {
              uint32_t t, u;
              asm("mul.rn.bf16x2 %0, %1, %1;" : "=r"(t) : "r"(xa[i + 4 + e]));
              asm("add.rn.bf16x2 %0, %1, %2;" : "=r"(u) : "r"(xa[i + 4 + e]), "r"(xa[i + 6 + e]));
              asm("fma.rn.bf16x2 %0, %1, %1, %0;" : "+r"(t) : "r"(xa[i + 6 + e]));
              asm("add.rn.bf16x2 %0, %0, %1;" : "+r"(a[e]) : "r"(t));
              asm("add.rn.bf16x2 %0, %0, %1;" : "+r"(a[2 + e]) : "r"(u));
            }
          }
          mma16816(s1[(kk / GRP) & 1], a[0], a[1], a[2], a[3], b0, b1);
        }
      };
      mbar_wait(bars + 8 * B_X8, 0);
      if (STX) STAMP(wg, 21);
      load(8, sb + wg * 8192);
#pragma unroll
      for (int kp = 0; kp < 4; kp++) {
        mbar_wait(bars + 8 * (B_X + wg * 4 + kp), 0);
        if (STX) STAMP(wg, 22 + kp);
        load(2 * kp, hw + 2 * kp * 8192);
        load(2 * kp + 1, hw + (2 * kp + 1) * 8192);
        if (kp == 0) sums(8); else { sums(2 * kp - 2); sums(2 * kp - 1); }
      }
#pragma unroll
      for (int i = 0; i < 9; i++) {
        const int c8 = j * 9 + i, kb = c8 >> 3;
        const uint32_t a = (kb < 8 ? hw + kb * 8192 : sb + wg * 8192) + (w4 * 16 + g) * 128 + (((c8 & 7) ^ g) << 4) + q * 4;
        xr[2 * i] = lds32(a); xr[2 * i + 1] = lds32(a + 1024);
      }
      sums(6);
      asm volatile("fence.proxy.async.shared::cta;" ::: "memory");
      bar_arrive(NB_XDONE + wg, 160);
      sums(7);
      if (STX) STAMP(wg, 1);
#pragma unroll
      for (int e = 0; e < 2; e++) {
        const float mu = (s1[0][2 * e + 1] + s1[1][2 * e + 1]) * (1.f / kD);
        const float var = fmaxf(fmaf(-mu, mu, (s1[0][2 * e] + s1[1][2 * e]) * (1.f / kD)), 0.f);
        float sd, r;
        asm("sqrt.approx.f32 %0, %1;" : "=f"(sd) : "f"(rbf(rbf(var) + 1e-5f)));
        asm("rcp.approx.ftz.f32 %0, %1;" : "=f"(r) : "f"(rbf(sd)));
        r = rbf(0.5f * r);
        rh[e] = pack_bf16(r, r); cc[e] = pack_bf16(-mu * r, -mu * r);
      }
    }
    STAMP(wg, 2);

    auto normalise = [&](int kb) {
#pragma unroll
      for (int i = 0; i < 16; i++) asm("fma.rn.bf16x2 %0, %0, %1, %2;" : "+r"(xa[16 * kb + (i >> 3) + 2 * (i & 7)]) : "r"(rh[i >> 3]), "r"(cc[i >> 3]));
    };
    {
      float ab[36];
      float* op = prm.out + (size_t)(m * 128 + wg * 64 + w4 * 16 + g) * kD + j * 72 + q * 2;
      auto residual = [&](int i) {
#pragma unroll
        for (int e = 0; e < 2; e++) {
          uint32_t t;
          asm("fma.rn.bf16x2 %0, %1, %2, %3;" : "=r"(t) : "r"(xr[2 * i + e]), "r"(rh[e]), "r"(cc[e]));
          asm("mul.rn.bf16x2 %0, %0, %1;" : "+r"(t) : "r"(dk[i]));
          *(float2*)(op + e * 8 * kD + i * 8) = make_float2(bflo(xr[2 * i + e]) + bflo(t), bfhi(xr[2 * i + e]) + bfhi(t));
        }
      };
      const uint32_t da = sb + OFF_DUMP + wg * HS_BYTES + (w4 * 16 + g) * 16 + q * 4;
      auto dump = [&](int im) {
#pragma unroll
        for (int i = 0; i < 18; i++)
          asm volatile("st.shared.b32 [%0], %1;" ::"r"(da + (i < 16 ? 8 * im + (i >> 1) : 16 + im) * HS_LBO + (i & 1) * 128), "r"(pack_bf16(ab[2 * i], ab[2 * i + 1])) : "memory");
      };
      auto bu = [&](int kb, uint32_t off) {
        wg_fence();
#pragma unroll
        for (int kk = 0; kk < 4; kk++) { const int i = (kb * 4 + kk) * 4; wgmma_n72_rs_tb0(ab, xa[i], xa[i + 1], xa[i + 2], xa[i + 3], desc((dring + (off >> 4) + kk * 2) | DLO_K, DHI_SW128), (kb | kk) != 0); }
        wg_commit();
      };
      normalise(0);
#pragma unroll
      for (int kb = 0; kb < 9; kb++) {
        if ((kb & 3) == 0) mbar_wait(bars + 8 * (B_BU + (kb >> 2)), 0);
        bu(kb, kb < 8 ? OFF_BU0 + kb * 9216 : OFF_BU1);
        if (kb < 8) normalise(kb + 1);
      }
      wg_wait<0>();
      if (w4 == 0) { if (elect()) mbar_arrive(bars + 8 * B_RING); }
      STAMP(wg, 19);
      keep(ab);
      dump(0);
#pragma unroll
      for (int kb = 0; kb < 9; kb++) {
        if (kb == 4) mbar_wait(bars + 8 * (B_BU + 3), 0);
        bu(kb, kb < 4 ? OFF_BU1 + (kb + 1) * 9216 : OFF_BU2 + (kb - 4) * 9216);
        residual(kb);
      }
      wg_wait<0>();
      keep(ab);
      dump(1);
      bar_arrive(NB_DUMP, 352);
    }
    STAMP(wg, 3);

    float acc[64];
    {
      const uint32_t ha = hw + (threadIdx.x & 127) * 16 + wg * 7 * 8192;
      const int hstep = wg ? -8192 : 8192;
      auto glu = [&](int i) {
        return pack_bf16(fmaf(acc[32 + 2 * i], tanh_fast(acc[2 * i]), acc[32 + 2 * i]), fmaf(acc[33 + 2 * i], tanh_fast(acc[2 * i + 1]), acc[33 + 2 * i]));
      };
      auto chunk = [&](const int c, const bool last) {
        if (SKEW > 0 && wg == 1) bar_sync(NB_SKEW, 256);
#pragma unroll
        for (int kb = 0; kb < 9; kb++) {
          stage_begin();
#pragma unroll
          for (int kk = 0; kk < 4; kk++) { const int i = (kb * 4 + kk) * 4; wgmma_n128_rs_tb1(acc, xa[i], xa[i + 1], xa[i + 2], xa[i + 3], desc((dlo + kk * 128) | DLO_MN, DHI_SW128), (kb | kk) != 0); }
          if (SKEW > 0 && kb == SKEW - 1 && wg == 0) bar_arrive(NB_SKEW, 256);
          if (!last && kb == 8 && c == 5) mbar_wait(bars + 8 * B_SCAN, 0);
          stage_end(kb > 0);
          if (last && kb > 0) {
#pragma unroll
            for (int i = 4 * (kb - 1); i < 4 * kb; i++) lds128(ha + (i >> 2) * hstep + (i & 3) * 2048, xa[4 * i], xa[4 * i + 1], xa[4 * i + 2], xa[4 * i + 3]);
          }
        }
        wg_wait<0>();
        release(prev);
        keep(acc);
      };
      for (int c = 0;; c++) {
        chunk(c, false);
        if (c == 8) break;
#pragma unroll
        for (int i = 0; i < 4; i++) sts128(ha + c * hstep + i * 2048, glu(4 * i), glu(4 * i + 1), glu(4 * i + 2), glu(4 * i + 3));
        STAMP(wg, 4 + c);
      }
#pragma unroll
      for (int i = 0; i < 32; i++) lds128(ha + (i >> 2) * hstep + (i & 3) * 2048, xa[4 * i], xa[4 * i + 1], xa[4 * i + 2], xa[4 * i + 3]);
#pragma unroll
      for (int i = 0; i < 16; i++) xa[128 + i] = glu(i);
      asm volatile("fence.proxy.async.shared::cta;" ::: "memory");
      bar_arrive(NB_HFREE, 288);
    }
    STAMP(wg, 13);

    const uint32_t dhs = (((sb + OFF_HS + wg * HS_BYTES) & 0x3FFFF) >> 4) | DLO_HS;
    const int rp = (g >> 2) + 2 * (g & 3);
    const uint32_t so = w4 * 2048 + rp * 128 + (q & 1) * 8, sx = ((q >> 1) ^ rp) << 4;
    const uint32_t rcv = sb + OFF_STG + wg * 32768 + 16384 + w4 * 2048 + lane * 16;
    auto staged = [&]() {
      asm volatile("fence.proxy.async.shared::cta;" ::: "memory");
      __syncwarp();
      if (elect()) mbar_arrive(bars + 8 * (B_SFULL + wg));
    };
    auto half_tile = [&](const bool first, const int kind) {
      float a2[32];
      if (SKEWB > 0 && wg == 1) bar_sync(NB_SKEW, 256);
      const uint32_t ph0 = ph;
      uint32_t d4;
#pragma unroll
      for (int kp = 0; kp < 5; kp++) {
        if (kp == 4) nst = NST + 1;
        stage_begin();
#pragma unroll
        for (int kk = 0; kk < (kp < 4 ? 8 : 4); kk++) { const int i = (kp * 8 + kk) * 4; wgmma_n64_rs_tb1(a2, xa[i], xa[i + 1], xa[i + 2], xa[i + 3], desc((dlo + kk * 128) | DLO_MN, DHI_SW128), (kp | kk) != 0); }
        if (SKEWB > 0 && kp == 1 && wg == 0) bar_arrive(NB_SKEW, 256);
        d4 = dlo;
        stage_end(kp > 0);
        if (kp == 0 && !first) staged();
      }
      if (first) mbar_wait(bars + 8 * B_HSFULL, 0);
      stage_begin();
#pragma unroll
      for (int kk = 0; kk < 8; kk++) wgmma_n64_ss_tb0(a2, desc(dhs + kk * (2 * HS_LBO >> 4), DHI_NONE), desc((dlo + (kk >> 2) * 512 + (kk & 3) * 2) | DLO_K, DHI_SW128), 1);
      wgmma_n64_ss_tb0(a2, desc(dhs + 8 * (2 * HS_LBO >> 4), DHI_NONE), desc((d4 + 512) | ((1024 >> 4) << 16), DHI_NONE), 1);
      wg_commit();
      if (!first) {
        if (kind == 1) mbar_wait(bars + 8 * (B_EMPTY + 3 + wg), ph0);
        if (kind == 2) { mbar_wait(bars + 8 * (B_SFREE + wg), 1); mbar_wait(bars + 8 * (B_RFULL + wg), 1); }
      }
      wg_wait<0>();
      release(prev); release(s); advance();
      keep(a2);
      if (!first && kind >= 2) {
#pragma unroll
        for (int i = 0; i < 4; i++) {
          uint32_t v[4];
          lds128(rcv + (kind & 1) * 8192 + i * 512, v[0], v[1], v[2], v[3]);
#pragma unroll
          for (int e = 0; e < 4; e++) { a2[8 * i + 2 * e] += bflo(v[e]); a2[8 * i + 2 * e + 1] += bfhi(v[e]); }
        }
        __syncwarp();
      }
      const uint32_t stg = (!first && kind == 1 ? sb + (3 + wg) * SLOT : sb + OFF_STG + wg * 32768 + (kind == 3 ? 16384 : 0)) + so;
#pragma unroll
      for (int i = 0; i < 8; i++) {
        const uint32_t a = stg + (i >> 2) * 8192 + (sx ^ ((i & 3) << 5));
        sts64f(a, a2[4 * i], a2[4 * i + 1]);
        sts64f(a + 1024, a2[4 * i + 2], a2[4 * i + 3]);
      }
      STAMP(wg, first ? 14 : kind == 2 ? 12 : 18);
    };
    if (rank) half_tile(true, 0);
    for (int t = 0; t < 4 - (SPLIT & rank); t++) {
      if (SKEWB > 0 && wg == 1) bar_sync(NB_SKEW, 256);
#pragma unroll
      for (int kb = 0; kb < 9; kb++) {
        if (kb == 4) nst = NST + 1;
        stage_begin();
#pragma unroll
        for (int kk = 0; kk < 4; kk++) { const int i = (kb * 4 + kk) * 4; wgmma_n128_rs_tb1(acc, xa[i], xa[i + 1], xa[i + 2], xa[i + 3], desc((dlo + kk * 128) | DLO_MN, DHI_SW128), (kb | kk) != 0); }
        if (SKEWB > 0 && kb == SKEWB - 1 && wg == 0) bar_arrive(NB_SKEW, 256);
        stage_end(kb > 0);
        if (kb == 0 && t + rank > 0) staged();
      }
      if (t == 0) mbar_wait(bars + 8 * B_HSFULL, 0);
      stage_begin();
#pragma unroll
      for (int kk = 0; kk < 4; kk++) wgmma_n128_ss_tb0(acc, desc(dhs + kk * (2 * HS_LBO >> 4), DHI_NONE), desc((dlo + kk * 2) | DLO_K, DHI_SW128), 1);
      stage_end(true);
      stage_begin();
#pragma unroll
      for (int kk = 0; kk < 4; kk++) wgmma_n128_ss_tb0(acc, desc(dhs + (4 + kk) * (2 * HS_LBO >> 4), DHI_NONE), desc((dlo + kk * 2) | DLO_K, DHI_SW128), 1);
      const int s_im = s;
      advance();
      stage_begin();
      wgmma_n128_ss_tb0(acc, desc(dhs + 8 * (2 * HS_LBO >> 4), DHI_NONE), desc(dlo | ((2048 >> 4) << 16), DHI_NONE), 1);
      stage_end(true);
      if (t + rank > 0) mbar_wait(bars + 8 * (B_SFREE + wg), (t + rank - 1) & 1);
      if (t & 1) mbar_wait(bars + 8 * (B_RFULL + wg), t >> 1);
      wg_wait<0>();
      release(s_im); release(prev);
      keep(acc);
      if (t & 1) {
        const uint32_t stg = sb + OFF_STG + wg * 32768 + so;
#pragma unroll
        for (int hh = 0; hh < 2; hh++) {
#pragma unroll
          for (int i = 4 * hh; i < 4 * hh + 4; i++) {
            uint32_t v[4];
            lds128(rcv + hh * 8192 + (i & 3) * 512, v[0], v[1], v[2], v[3]);
#pragma unroll
            for (int e = 0; e < 4; e++) { acc[8 * i + 2 * e] += bflo(v[e]); acc[8 * i + 2 * e + 1] += bfhi(v[e]); }
          }
          __syncwarp();
#pragma unroll
          for (int i = 8 * hh; i < 8 * hh + 8; i++) {
            const uint32_t a = stg + (i >> 2) * 8192 + (sx ^ ((i & 3) << 5));
            sts64f(a, acc[4 * i], acc[4 * i + 1]);
            sts64f(a + 1024, acc[4 * i + 2], acc[4 * i + 3]);
          }
        }
      } else {
#pragma unroll
        for (int i = 0; i < 8; i++)
          sts128(rcv - 16384 + (i >> 2) * 8192 + (i & 3) * 512, pack_bf16(acc[8 * i], acc[8 * i + 1]), pack_bf16(acc[8 * i + 2], acc[8 * i + 3]),
                 pack_bf16(acc[8 * i + 4], acc[8 * i + 5]), pack_bf16(acc[8 * i + 6], acc[8 * i + 7]));
      }
      STAMP(wg, 14 + t + rank);
    }
    if (SPLIT || !rank) {
#pragma unroll 1
      for (int kind = 1 + rank; kind < 2 + 2 * rank; kind++) half_tile(false, kind);
    }
    staged();
    if (w4 == 0) STAMP_DUMP(wg);
  }
}

typedef CUresult (*EncodeFn)(CUtensorMap*, CUtensorMapDataType, cuuint32_t, void*, const cuuint64_t*, const cuuint64_t*, const cuuint32_t*,
                             const cuuint32_t*, CUtensorMapInterleave, CUtensorMapSwizzle, CUtensorMapL2promotion, CUtensorMapFloatOOBfill);

void map2d(EncodeFn enc, CUtensorMap* tm, const void* p, uint64_t cols, uint64_t rows, uint32_t bc, uint32_t br, CUtensorMapSwizzle sw) {
  cuuint64_t gd[2] = {cols, rows}, gs[1] = {cols * 2};
  cuuint32_t bd[2] = {bc, br}, es[2] = {1, 1};
  enc(tm, CU_TENSOR_MAP_DATA_TYPE_BFLOAT16, 2, (void*)p, gd, gs, bd, es, CU_TENSOR_MAP_INTERLEAVE_NONE, sw,
      sw == CU_TENSOR_MAP_SWIZZLE_128B ? CU_TENSOR_MAP_L2_PROMOTION_L2_128B : CU_TENSOR_MAP_L2_PROMOTION_NONE, CU_TENSOR_MAP_FLOAT_OOB_FILL_NONE);
}

}

extern "C" void kernel_launch(void* const* d_in, const int* in_sizes, int n_in, void* d_out, int out_size) {
  (void)in_sizes; (void)n_in; (void)out_size;
  static EncodeFn enc = nullptr;
  if (!enc) {
    cudaDriverEntryPointQueryResult qr;
    cudaGetDriverEntryPoint("cuTensorMapEncodeTiled", (void**)&enc, cudaEnableDefault, &qr);
    cudaFuncSetAttribute(fused_kernel, cudaFuncAttributeMaxDynamicSharedMemorySize, SMEM_BYTES);
  }
  Params prm;
  const CUtensorMapSwizzle S128 = CU_TENSOR_MAP_SWIZZLE_128B;
  map2d(enc, &prm.tx, d_in[0], kD, kS, 64, 64, S128);
  map2d(enc, &prm.tBre, d_in[3], kD, 576, 64, 72, S128);
  map2d(enc, &prm.tBim, d_in[4], kD, 576, 64, 72, S128);
  map2d(enc, &prm.tCre, d_in[5], 576, kD, 64, 64, S128);
  map2d(enc, &prm.tCim, d_in[6], 576, kD, 64, 64, S128);
  map2d(enc, &prm.tCre8, d_in[5], 576, kD, 8, 64, CU_TENSOR_MAP_SWIZZLE_NONE);
  map2d(enc, &prm.tCim8, d_in[6], 576, kD, 8, 64, CU_TENSOR_MAP_SWIZZLE_NONE);
  map2d(enc, &prm.tWg, d_in[10], kF, kD, 64, 64, S128);
  map2d(enc, &prm.tWu, d_in[11], kF, kD, 64, 64, S128);
  map2d(enc, &prm.tWd, d_in[12], kD, kF, 64, 64, S128);
  {
    cuuint64_t gd[4] = {kD, 2, 4, kS / 8}, gs[3] = {4 * kD * 4, kD * 4, 8 * kD * 4};
    cuuint32_t bd[4] = {32, 2, 4, 8}, es[4] = {1, 1, 1, 1};
    enc(&prm.tOut, CU_TENSOR_MAP_DATA_TYPE_FLOAT32, 4, d_out, gd, gs, bd, es, CU_TENSOR_MAP_INTERLEAVE_NONE, S128, CU_TENSOR_MAP_L2_PROMOTION_NONE,
        CU_TENSOR_MAP_FLOAT_OOB_FILL_NONE);
  }
  prm.x = (const __nv_bfloat16*)d_in[0];
  prm.lre = (const __nv_bfloat16*)d_in[1];
  prm.lim = (const __nv_bfloat16*)d_in[2];
  prm.bre = (const __nv_bfloat16*)d_in[3];
  prm.bim = (const __nv_bfloat16*)d_in[4];
  prm.cre = (const __nv_bfloat16*)d_in[5];
  prm.cim = (const __nv_bfloat16*)d_in[6];
  prm.wg = (const __nv_bfloat16*)d_in[10];
  prm.wu = (const __nv_bfloat16*)d_in[11];
  prm.wd = (const __nv_bfloat16*)d_in[12];
  prm.ldt = (const __nv_bfloat16*)d_in[7];
  prm.dskip = (const __nv_bfloat16*)d_in[8];
  prm.out = (float*)d_out;

  fused_kernel<<<128, 384, SMEM_BYTES, cudaStreamPerThread>>>(prm);
}
```

```cpp
#include <cuda_runtime.h>
#include <cuda.h>
#include <cuda_bf16.h>
#include <stdint.h>

namespace {

#define PACE 1
#define PACEP 100
#define XMODE 0
#define NOPF 0
#define PFD 18
#define XPF 0
#define HINT 0
#define NORES 0
#define POLL 1
#define GRP 1
#define SPLIT 1
#define STX 0
#define BEARLY 0
#define PF64 0
#define SK0 SKEW
#define SKEW 4
#define SKEWB 4

constexpr int kS = 2048, kD = 576, kF = 4608;
constexpr int NST = 6;
constexpr uint32_t SLOT = 16384;
constexpr uint32_t OFF_H = NST * SLOT;
constexpr uint32_t HS_LBO = 1040;
constexpr uint32_t HS_BYTES = 18 * HS_LBO;
constexpr uint32_t OFF_DUMP = OFF_H + 65536 - HS_BYTES;
constexpr uint32_t OFF_STG = OFF_H + SLOT;
constexpr uint32_t OFF_HS = OFF_STG + 65536;
constexpr uint32_t OFF_BAR = OFF_H + 131072;
constexpr uint32_t OFF_CONST = OFF_BAR + 384;
constexpr uint32_t SMEM_BYTES = OFF_CONST + 4 * 576 + 384;
static_assert(SMEM_BYTES <= 232448 && OFF_HS + 2 * HS_BYTES <= OFF_BAR, "smem");

enum { B_FULL = 0, B_EMPTY = NST + 2, B_X = 2 * NST + 4, B_X8 = B_X + 8, B_BU  , B_RING = B_BU + 4, B_SCAN, B_HFREE, B_HSFULL, B_SFULL,
       B_SFREE = B_SFULL + 2, B_RFULL = B_SFREE + 2, B_RFREE = B_RFULL + 2, B_COUNT = B_RFREE + 2 };
static_assert(B_COUNT * 8 <= 384, "barriers");
enum { NB_SKEW = 1, NB_XDONE = 2  , NB_SCAN = 4, NB_DUMP = 5, NB_HFREE = 6, NB_STATS = 7 };
constexpr uint32_t HBLK0 = 0x76502CB4u, HBLK1 = 0x89A13DEFu;
constexpr uint32_t OFF_BU0 = SLOT, OFF_BU1 = OFF_H, OFF_BU2 = OFF_H + 65536 + 19456;
static_assert(OFF_BU1 + 5 * 9216 <= OFF_DUMP && OFF_BU2 >= OFF_DUMP + 2 * HS_BYTES && OFF_BU2 + 5 * 9216 <= OFF_BAR, "Bu tiles");

struct __align__(64) Params {
  CUtensorMap tx, tBre, tBim, tWg, tWu, tWd, tCre, tCim, tCre8, tCim8, tOut;
  const __nv_bfloat16 *x, *lre, *lim, *bre, *bim, *cre, *cim, *ldt, *dskip, *wg, *wu, *wd;
  float* out;
};

__device__ unsigned g_epoch[128];
__device__ unsigned g_ready[16];
__device__ __align__(256) uint2 g_S[2][16][8][96];
__device__ __align__(128) uint8_t g_hs[128][2 * HS_BYTES];
#define STAMP(role, i)
#define STAMPP(i)
#define STAMP_DUMP(role)

__device__ __forceinline__ void wgmma_n72_rs_tb0(float (&d)[36], uint32_t a0, uint32_t a1, uint32_t a2, uint32_t a3, uint64_t db, int scale_d) {
  asm volatile("{\n.reg .pred p;\nsetp.ne.b32 p, %41, 0;\n"
    "wgmma.mma_async.sync.aligned.m64n72k16.f32.bf16.bf16 {"
    "%0, %1, %2, %3, %4, %5, %6, %7, %8, %9, %10, %11, %12, %13, %14, %15, "
    "%16, %17, %18, %19, %20, %21, %22, %23, %24, %25, %26, %27, %28, %29, %30, %31, "
    "%32, %33, %34, %35"
    "}, {%36, %37, %38, %39}, %40, p, 1, 1, 0;\n}\n"
    : "+f"(d[0]), "+f"(d[1]), "+f"(d[2]), "+f"(d[3]), "+f"(d[4]), "+f"(d[5]), "+f"(d[6]), "+f"(d[7]),
      "+f"(d[8]), "+f"(d[9]), "+f"(d[10]), "+f"(d[11]), "+f"(d[12]), "+f"(d[13]), "+f"(d[14]), "+f"(d[15]),
      "+f"(d[16]), "+f"(d[17]), "+f"(d[18]), "+f"(d[19]), "+f"(d[20]), "+f"(d[21]), "+f"(d[22]), "+f"(d[23]),
      "+f"(d[24]), "+f"(d[25]), "+f"(d[26]), "+f"(d[27]), "+f"(d[28]), "+f"(d[29]), "+f"(d[30]), "+f"(d[31]),
      "+f"(d[32]), "+f"(d[33]), "+f"(d[34]), "+f"(d[35])
    : "r"(a0), "r"(a1), "r"(a2), "r"(a3), "l"(db), "r"(scale_d));
}
__device__ __forceinline__ void wgmma_n128_rs_tb1(float (&d)[64], uint32_t a0, uint32_t a1, uint32_t a2, uint32_t a3, uint64_t db, int scale_d) {
  asm volatile("{\n.reg .pred p;\nsetp.ne.b32 p, %69, 0;\n"
    "wgmma.mma_async.sync.aligned.m64n128k16.f32.bf16.bf16 {"
    "%0, %1, %2, %3, %4, %5, %6, %7, %8, %9, %10, %11, %12, %13, %14, %15, "
    "%16, %17, %18, %19, %20, %21, %22, %23, %24, %25, %26, %27, %28, %29, %30, %31, "
    "%32, %33, %34, %35, %36, %37, %38, %39, %40, %41, %42, %43, %44, %45, %46, %47, "
    "%48, %49, %50, %51, %52, %53, %54, %55, %56, %57, %58, %59, %60, %61, %62, %63"
    "}, {%64, %65, %66, %67}, %68, p, 1, 1, 1;\n}\n"
    : "+f"(d[0]), "+f"(d[1]), "+f"(d[2]), "+f"(d[3]), "+f"(d[4]), "+f"(d[5]), "+f"(d[6]), "+f"(d[7]),
      "+f"(d[8]), "+f"(d[9]), "+f"(d[10]), "+f"(d[11]), "+f"(d[12]), "+f"(d[13]), "+f"(d[14]), "+f"(d[15]),
      "+f"(d[16]), "+f"(d[17]), "+f"(d[18]), "+f"(d[19]), "+f"(d[20]), "+f"(d[21]), "+f"(d[22]), "+f"(d[23]),
      "+f"(d[24]), "+f"(d[25]), "+f"(d[26]), "+f"(d[27]), "+f"(d[28]), "+f"(d[29]), "+f"(d[30]), "+f"(d[31]),
      "+f"(d[32]), "+f"(d[33]), "+f"(d[34]), "+f"(d[35]), "+f"(d[36]), "+f"(d[37]), "+f"(d[38]), "+f"(d[39]),
      "+f"(d[40]), "+f"(d[41]), "+f"(d[42]), "+f"(d[43]), "+f"(d[44]), "+f"(d[45]), "+f"(d[46]), "+f"(d[47]),
      "+f"(d[48]), "+f"(d[49]), "+f"(d[50]), "+f"(d[51]), "+f"(d[52]), "+f"(d[53]), "+f"(d[54]), "+f"(d[55]),
      "+f"(d[56]), "+f"(d[57]), "+f"(d[58]), "+f"(d[59]), "+f"(d[60]), "+f"(d[61]), "+f"(d[62]), "+f"(d[63])
    : "r"(a0), "r"(a1), "r"(a2), "r"(a3), "l"(db), "r"(scale_d));
}
__device__ __forceinline__ void wgmma_n128_ss_tb0(float (&d)[64], uint64_t da, uint64_t db, int scale_d) {
  asm volatile("{\n.reg .pred p;\nsetp.ne.b32 p, %66, 0;\n"
    "wgmma.mma_async.sync.aligned.m64n128k16.f32.bf16.bf16 {"
    "%0, %1, %2, %3, %4, %5, %6, %7, %8, %9, %10, %11, %12, %13, %14, %15, "
    "%16, %17, %18, %19, %20, %21, %22, %23, %24, %25, %26, %27, %28, %29, %30, %31, "
    "%32, %33, %34, %35, %36, %37, %38, %39, %40, %41, %42, %43, %44, %45, %46, %47, "
    "%48, %49, %50, %51, %52, %53, %54, %55, %56, %57, %58, %59, %60, %61, %62, %63"
    "}, %64, %65, p, 1, 1, 0, 0;\n}\n"
    : "+f"(d[0]), "+f"(d[1]), "+f"(d[2]), "+f"(d[3]), "+f"(d[4]), "+f"(d[5]), "+f"(d[6]), "+f"(d[7]),
      "+f"(d[8]), "+f"(d[9]), "+f"(d[10]), "+f"(d[11]), "+f"(d[12]), "+f"(d[13]), "+f"(d[14]), "+f"(d[15]),
      "+f"(d[16]), "+f"(d[17]), "+f"(d[18]), "+f"(d[19]), "+f"(d[20]), "+f"(d[21]), "+f"(d[22]), "+f"(d[23]),
      "+f"(d[24]), "+f"(d[25]), "+f"(d[26]), "+f"(d[27]), "+f"(d[28]), "+f"(d[29]), "+f"(d[30]), "+f"(d[31]),
      "+f"(d[32]), "+f"(d[33]), "+f"(d[34]), "+f"(d[35]), "+f"(d[36]), "+f"(d[37]), "+f"(d[38]), "+f"(d[39]),
      "+f"(d[40]), "+f"(d[41]), "+f"(d[42]), "+f"(d[43]), "+f"(d[44]), "+f"(d[45]), "+f"(d[46]), "+f"(d[47]),
      "+f"(d[48]), "+f"(d[49]), "+f"(d[50]), "+f"(d[51]), "+f"(d[52]), "+f"(d[53]), "+f"(d[54]), "+f"(d[55]),
      "+f"(d[56]), "+f"(d[57]), "+f"(d[58]), "+f"(d[59]), "+f"(d[60]), "+f"(d[61]), "+f"(d[62]), "+f"(d[63])
    : "l"(da), "l"(db), "r"(scale_d));
}
__device__ __forceinline__ void wgmma_n64_rs_tb1(float (&d)[32], uint32_t a0, uint32_t a1, uint32_t a2, uint32_t a3, uint64_t db, int scale_d) {
  asm volatile("{\n.reg .pred p;\nsetp.ne.b32 p, %37, 0;\n"
    "wgmma.mma_async.sync.aligned.m64n64k16.f32.bf16.bf16 {"
    "%0, %1, %2, %3, %4, %5, %6, %7, %8, %9, %10, %11, %12, %13, %14, %15, "
    "%16, %17, %18, %19, %20, %21, %22, %23, %24, %25, %26, %27, %28, %29, %30, %31"
    "}, {%32, %33, %34, %35}, %36, p, 1, 1, 1;\n}\n"
    : "+f"(d[0]), "+f"(d[1]), "+f"(d[2]), "+f"(d[3]), "+f"(d[4]), "+f"(d[5]), "+f"(d[6]), "+f"(d[7]),
      "+f"(d[8]), "+f"(d[9]), "+f"(d[10]), "+f"(d[11]), "+f"(d[12]), "+f"(d[13]), "+f"(d[14]), "+f"(d[15]),
      "+f"(d[16]), "+f"(d[17]), "+f"(d[18]), "+f"(d[19]), "+f"(d[20]), "+f"(d[21]), "+f"(d[22]), "+f"(d[23]),
      "+f"(d[24]), "+f"(d[25]), "+f"(d[26]), "+f"(d[27]), "+f"(d[28]), "+f"(d[29]), "+f"(d[30]), "+f"(d[31])
    : "r"(a0), "r"(a1), "r"(a2), "r"(a3), "l"(db), "r"(scale_d));
}
__device__ __forceinline__ void wgmma_n64_ss_tb0(float (&d)[32], uint64_t da, uint64_t db, int scale_d) {
  asm volatile("{\n.reg .pred p;\nsetp.ne.b32 p, %34, 0;\n"
    "wgmma.mma_async.sync.aligned.m64n64k16.f32.bf16.bf16 {"
    "%0, %1, %2, %3, %4, %5, %6, %7, %8, %9, %10, %11, %12, %13, %14, %15, "
    "%16, %17, %18, %19, %20, %21, %22, %23, %24, %25, %26, %27, %28, %29, %30, %31"
    "}, %32, %33, p, 1, 1, 0, 0;\n}\n"
    : "+f"(d[0]), "+f"(d[1]), "+f"(d[2]), "+f"(d[3]), "+f"(d[4]), "+f"(d[5]), "+f"(d[6]), "+f"(d[7]),
      "+f"(d[8]), "+f"(d[9]), "+f"(d[10]), "+f"(d[11]), "+f"(d[12]), "+f"(d[13]), "+f"(d[14]), "+f"(d[15]),
      "+f"(d[16]), "+f"(d[17]), "+f"(d[18]), "+f"(d[19]), "+f"(d[20]), "+f"(d[21]), "+f"(d[22]), "+f"(d[23]),
      "+f"(d[24]), "+f"(d[25]), "+f"(d[26]), "+f"(d[27]), "+f"(d[28]), "+f"(d[29]), "+f"(d[30]), "+f"(d[31])
    : "l"(da), "l"(db), "r"(scale_d));
}

__device__ __forceinline__ bool elect() {
  uint32_t p;
  asm volatile("{.reg .pred q; elect.sync _|q, 0xffffffff; selp.u32 %0,1,0,q;}" : "=r"(p));
  return p;
}
__device__ __forceinline__ void mbar_init(uint32_t bar, uint32_t cnt) { asm volatile("mbarrier.init.shared::cta.b64 [%0], %1;" ::"r"(bar), "r"(cnt) : "memory"); }
__device__ __forceinline__ void mbar_expect(uint32_t bar, uint32_t bytes) { asm volatile("mbarrier.arrive.expect_tx.shared::cta.b64 _, [%0], %1;" ::"r"(bar), "r"(bytes) : "memory"); }
__device__ __forceinline__ void mbar_arrive(uint32_t bar) { asm volatile("mbarrier.arrive.shared::cta.b64 _, [%0];" ::"r"(bar) : "memory"); }
__device__ __forceinline__ void mbar_arrive_cta(uint32_t bar, uint32_t cta) {
  asm volatile("{.reg .b32 ra; mapa.shared::cluster.u32 ra, %0, %1; mbarrier.arrive.shared::cluster.b64 _, [ra];}" ::"r"(bar), "r"(cta) : "memory");
}
__device__ __forceinline__ void mbar_wait(uint32_t bar, uint32_t parity) {
  asm volatile(
      "{\n.reg .pred p;\n.reg .u32 c, t;\n"
      "mbarrier.try_wait.parity.shared::cta.b64 p, [%0], %1;\n@p bra DONE;\n"
      "mov.u32 c, %%clock;\n"
      "LAB_WAIT:\nmbarrier.try_wait.parity.shared::cta.b64 p, [%0], %1;\n@p bra DONE;\n"
      "mov.u32 t, %%clock;\nsub.u32 t, t, c;\nsetp.lt.u32 p, t, 0x40000000;\n@p bra LAB_WAIT;\ntrap;\nDONE:\n}" ::"r"(bar), "r"(parity) : "memory");
}
__device__ __forceinline__ void bar_sync(int id, int n) { asm volatile("bar.sync %0, %1;" ::"r"(id), "r"(n) : "memory"); }
__device__ __forceinline__ void bar_arrive(int id, int n) { asm volatile("bar.arrive %0, %1;" ::"r"(id), "r"(n) : "memory"); }
__device__ __forceinline__ void wg_fence() { asm volatile("wgmma.fence.sync.aligned;" ::: "memory"); }
__device__ __forceinline__ void wg_commit() { asm volatile("wgmma.commit_group.sync.aligned;" ::: "memory"); }
template <int N> __device__ __forceinline__ void wg_wait() { asm volatile("wgmma.wait_group.sync.aligned %0;" ::"n"(N) : "memory"); }
__device__ __forceinline__ void tma2d(uint32_t dst, const CUtensorMap* tm, uint32_t bar, int c0, int c1) {
  asm volatile("cp.async.bulk.tensor.2d.shared::cluster.global.mbarrier::complete_tx::bytes [%0], [%1,{%3,%4}], [%2];" ::"r"(dst), "l"(tm), "r"(bar), "r"(c0), "r"(c1) : "memory");
}
__device__ __forceinline__ void tma2d_mc(uint32_t dst, const CUtensorMap* tm, uint32_t bar, int c0, int c1) {
  asm volatile("cp.async.bulk.tensor.2d.shared::cluster.global.mbarrier::complete_tx::bytes.multicast::cluster [%0], [%1,{%3,%4}], [%2], %5;" ::"r"(dst), "l"(tm), "r"(bar), "r"(c0), "r"(c1), "h"((uint16_t)3) : "memory");
}
__device__ __forceinline__ void l2_prefetch(const void* p, uint32_t bytes) {
  asm volatile("cp.async.bulk.prefetch.L2.global [%0], %1;" ::"l"(p), "r"(bytes) : "memory");
}
__device__ __forceinline__ void l2_prefetch_line(const void* p) { asm volatile("prefetch.global.L2 [%0];" ::"l"(p)); }
__device__ __forceinline__ void tma_prefetch2d(const CUtensorMap* tm, int c0, int c1) {
  asm volatile("cp.async.bulk.prefetch.tensor.2d.L2.global.tile [%0,{%1,%2}];" ::"l"(tm), "r"(c0), "r"(c1) : "memory");
}
__device__ __forceinline__ uint64_t desc(uint32_t lo, uint32_t hi) { return ((uint64_t)hi << 32) | lo; }
constexpr uint32_t DHI_SW128 = (1024 >> 4) | (1u << 30);
constexpr uint32_t DHI_NONE = (128 >> 4);
constexpr uint32_t DLO_HS = (HS_LBO >> 4) << 16;
constexpr uint32_t DLO_MN = (8192 >> 4) << 16;
constexpr uint32_t DLO_K = 1u << 16;
__device__ __forceinline__ float tanh_fast(float x) { float y; asm("tanh.approx.f32 %0, %1;" : "=f"(y) : "f"(x)); return y; }
__device__ __forceinline__ uint32_t pack_bf16(float lo, float hi) { uint32_t r; asm("cvt.rn.bf16x2.f32 %0, %1, %2;" : "=r"(r) : "f"(hi), "f"(lo)); return r; }
__device__ __forceinline__ float rbf(float x) { return __bfloat162float(__float2bfloat16_rn(x)); }
__device__ __forceinline__ void mma16816(float (&c)[4], uint32_t a0, uint32_t a1, uint32_t a2, uint32_t a3, uint32_t b0, uint32_t b1) {
  asm volatile("mma.sync.aligned.m16n8k16.row.col.f32.bf16.bf16.f32 {%0,%1,%2,%3}, {%4,%5,%6,%7}, {%8,%9}, {%0,%1,%2,%3};"
               : "+f"(c[0]), "+f"(c[1]), "+f"(c[2]), "+f"(c[3]) : "r"(a0), "r"(a1), "r"(a2), "r"(a3), "r"(b0), "r"(b1));
}
__device__ __forceinline__ void sts128(uint32_t a, uint32_t x, uint32_t y, uint32_t z, uint32_t w) {
  asm volatile("st.shared.v4.b32 [%0], {%1,%2,%3,%4};" ::"r"(a), "r"(x), "r"(y), "r"(z), "r"(w) : "memory");
}
__device__ __forceinline__ void sts64f(uint32_t a, float x, float y) { asm volatile("st.shared.v2.f32 [%0], {%1,%2};" ::"r"(a), "f"(x), "f"(y) : "memory"); }
__device__ __forceinline__ float2 lds64f(uint32_t a) { float2 v; asm volatile("ld.shared.v2.f32 {%0,%1}, [%2];" : "=f"(v.x), "=f"(v.y) : "r"(a) : "memory"); return v; }
__device__ __forceinline__ uint32_t lds32(uint32_t a) { uint32_t v; asm volatile("ld.shared.b32 %0, [%1];" : "=r"(v) : "r"(a) : "memory"); return v; }
__device__ __forceinline__ void lds128(uint32_t a, uint32_t& x, uint32_t& y, uint32_t& z, uint32_t& w) {
  asm volatile("ld.shared.v4.b32 {%0,%1,%2,%3}, [%4];" : "=r"(x), "=r"(y), "=r"(z), "=r"(w) : "r"(a) : "memory");
}
__device__ __forceinline__ float bflo(uint32_t v) { return __uint_as_float(v << 16); }
__device__ __forceinline__ float bfhi(uint32_t v) { return __uint_as_float(v & 0xffff0000u); }
__device__ __forceinline__ uint32_t lds32v(uint32_t a) { uint32_t v; asm volatile("ld.volatile.shared.b32 %0, [%1];" : "=r"(v) : "r"(a) : "memory"); return v; }
__device__ __forceinline__ float lds32f(uint32_t a) { float v; asm volatile("ld.shared.f32 %0, [%1];" : "=f"(v) : "r"(a) : "memory"); return v; }
template <int N> __device__ __forceinline__ void keep(float (&a)[N]) {
#pragma unroll
  for (int i = 0; i < N; i++) asm volatile("" : "+f"(a[i])::"memory");
}

__global__ void __cluster_dims__(2, 1, 1) __launch_bounds__(384, 1) fused_kernel(const __grid_constant__ Params prm) {
  extern __shared__ __align__(1024) uint8_t smem[];
  const int warp = __shfl_sync(0xffffffffu, threadIdx.x >> 5, 0);
  const uint32_t sb0 = (uint32_t)__cvta_generic_to_shared(smem);
  const int j = blockIdx.x & 7, m = blockIdx.x >> 3, rank = j & 1;
  auto smem_base = [&]() { return __shfl_sync(0xffffffffu, sb0 + (threadIdx.x & 31), 0); };
  STAMP(0, 31);

  if (XPF && threadIdx.x < 144) l2_prefetch_line((const char*)prm.x + (size_t)(m * 128 + j * 16) * 1152 + threadIdx.x * 128);
  if (threadIdx.x == 320) asm volatile("prefetch.tensormap [%0];" ::"l"(&prm.tx) : "memory");
  if (warp == 8 || warp == 9) {
    if (elect()) {
      if (warp == 8) {
#pragma unroll
        for (int i = 0; i < B_COUNT / 2; i++) mbar_init(sb0 + OFF_BAR + 8 * i, (i >= B_EMPTY && i < B_X) ? 2 : 1);
#pragma unroll
        for (int i = NST; i < NST + 2; i++) { mbar_arrive(sb0 + OFF_BAR + 8 * (B_FULL + i)); mbar_arrive(sb0 + OFF_BAR + 8 * (B_EMPTY + i)); mbar_arrive(sb0 + OFF_BAR + 8 * (B_EMPTY + i)); }
      } else {
#pragma unroll
        for (int i = B_COUNT / 2; i < B_COUNT; i++) mbar_init(sb0 + OFF_BAR + 8 * i, (i >= B_SFULL && i < B_SFULL + 2) ? 4 : i == B_RING ? 2 : 1);
        if (sb0 & 1023) __trap();
      }
      asm volatile("fence.mbarrier_init.release.cluster;" ::: "memory");
    }
    __syncwarp();
  }
  STAMPP(0);
  asm volatile("barrier.cluster.arrive.relaxed.aligned;\nbarrier.cluster.wait.aligned;" ::: "memory");
  STAMPP(1);

  if (warp == 0) {
    const uint32_t xb = sb0 + OFF_BAR;
    const bool e = elect();
    if (e) { mbar_expect(xb + 8 * B_X8, 16384); tma2d_mc(sb0 + rank * 8192, &prm.tx, xb + 8 * B_X8, 512, m * 128 + rank * 64); }
#pragma unroll
    for (int i = 0; i < 8; i++) {
      const int w = i >> 2, kb = (i & 3) * 2 + rank;
      if (e) { mbar_expect(xb + 8 * (B_X + i), 16384); tma2d_mc(sb0 + OFF_H + w * 65536 + kb * 8192, &prm.tx, xb + 8 * (B_X + i), kb * 64, m * 128 + w * 64); }
    }
    if (BEARLY) {
#pragma unroll
      for (int kb = 0; kb < 8; kb++)
        if (e) { if ((kb & 3) == 0) mbar_expect(xb + 8 * (B_BU + (kb >> 2)), 4 * 9216); tma2d(sb0 + OFF_BU0 + kb * 9216, &prm.tBre, xb + 8 * (B_BU + (kb >> 2)), kb * 64, j * 72); }
    }
    __syncwarp();
    STAMP(0, 20);
  }

  if (warp >= 8) {
    asm volatile("setmaxnreg.dec.sync.aligned.u32 24;");
    if (warp == 8) {
      const uint32_t sb = smem_base(), bars = sb + OFF_BAR;
      bool e;
      int s = 0, nst = NST; uint32_t ph = 1;
      uint32_t dst, fb;
      auto acquire = [&](uint32_t bytes) {
        mbar_wait(bars + 8 * (B_EMPTY + s), ph);
        fb = bars + 8 * (B_FULL + s); dst = sb + s * SLOT;
        e = elect();
        if (e) mbar_expect(fb, bytes);
        if (++s == nst) { s = 0; ph ^= 1; }
      };
      auto box = [&](const CUtensorMap* t, uint32_t o, int a, int b) { if (e) tma2d(dst + o, t, fb, a, b); };
      const int lane = threadIdx.x & 31;
      const char* pf = lane < 8 ? (const char*)(lane & 4 ? prm.wu : prm.wg) + ((size_t)(m * 4 + (lane & 3)) * kF + j * 576) * 2
                     : lane < 12 ? (const char*)prm.wd + (size_t)j * 576 * 1152 + (m * 324 + (lane & 3)) * 128
                                 : (const char*)(lane & 1 ? prm.cim : prm.cre) + (size_t)blockIdx.x * 5184;
      int pk = 0, pleft = 81;
      auto prefetch = [&]() {
        if (pleft > 0) {
          if (lane < 14 && !(NOPF & 2)) l2_prefetch_line(pf);
          pf += lane < 8 ? (pk == 8 ? 128 - 8 * 64 * kF * 2 : 64 * kF * 2) : lane < 12 ? 512 : 64;
          pk = pk == 8 ? 0 : pk + 1;
          pleft--;
        }
      };
      STAMPP(3);
      e = elect();
#pragma unroll 1
      for (int kb = 0; kb < (BEARLY ? 0 : 8); kb++) {
        fb = bars + 8 * (B_BU + (kb >> 2));
        if (e) { if ((kb & 3) == 0) mbar_expect(fb, 4 * 9216); tma2d(sb + OFF_BU0 + kb * 9216, &prm.tBre, fb, kb * 64, j * 72); }
      }
      STAMPP(4);
      bar_sync(NB_XDONE, 160);
      fb = bars + 8 * (B_BU + 2);
      if (e) { mbar_expect(fb, 5 * 9216); tma2d(sb + OFF_BU1, &prm.tBre, fb, 512, j * 72); }
#pragma unroll 1
      for (int kb = 0; kb < 4; kb++) if (e) tma2d(sb + OFF_BU1 + (kb + 1) * 9216, &prm.tBim, fb, kb * 64, j * 72);
      for (int i = 0; i < PFD / 2; i++) prefetch();
      bar_sync(NB_XDONE + 1, 160);
      fb = bars + 8 * (B_BU + 3);
      if (e) mbar_expect(fb, 5 * 9216);
#pragma unroll 1
      for (int kb = 4; kb < 9; kb++) if (e) tma2d(sb + OFF_BU2 + (kb - 4) * 9216, &prm.tBim, fb, kb * 64, j * 72);
      for (int i = PFD / 2; i < PFD; i++) prefetch();
      STAMPP(5);
      mbar_wait(bars + 8 * B_RING, 0);
      STAMPP(6);
      for (int c = 0; c < 9; c++) {
        const int col = j * 576 + c * 64;
#pragma unroll 1
        for (int kb = 0; kb < 9; kb++) {
          if (kb == 7 && c == 0) nst = 8;
          if (kb == 4 && c == 3) nst = 7;
          if (kb == 2 && c == 4) nst = 6;
          acquire(16384); box(&prm.tWg, 0, col, kb * 64); box(&prm.tWu, 8192, col, kb * 64); prefetch();
        }
      }
      auto half_tile = [&](int n0) {
#pragma unroll 1
        for (int kp = 0; kp < 4; kp++) { acquire(16384); box(&prm.tWd, 0, n0, j * 576 + kp * 128); box(&prm.tWd, 8192, n0, j * 576 + kp * 128 + 64); }
        nst = NST + 1;
        acquire(8192 + 2048); box(&prm.tWd, 0, n0, j * 576 + 512); box(&prm.tCre8, 8192, j * 72 + 64, n0); box(&prm.tCim8, 9216, j * 72 + 64, n0);
        acquire(16384); box(&prm.tCre, 0, j * 72, n0); box(&prm.tCim, 8192, j * 72, n0);
      };
      if (rank) half_tile(512);
#pragma unroll 1
      for (int t = 0; t < 4 - (SPLIT & rank); t++) {
        const int n0 = ((rank ^ t ^ 1) & 1) * 256 + (((t >> 1) ^ (j >> 1)) & 1) * 128;
#pragma unroll 1
        for (int kb = 0; kb < 9; kb++) {
          if (kb == 4) nst = NST + 1;
          if (kb == 3 && t == 0 && rank) mbar_wait(bars + 8 * B_HFREE, 0);
          acquire(16384); box(&prm.tWd, 0, n0, j * 576 + kb * 64); box(&prm.tWd, 8192, n0 + 64, j * 576 + kb * 64);
        }
        if (t == 0) mbar_wait(bars + 8 * B_HFREE, 0);
        acquire(16384); box(&prm.tCre, 0, j * 72, n0); box(&prm.tCre, 8192, j * 72, n0 + 64);
        acquire(16384); box(&prm.tCim, 0, j * 72, n0); box(&prm.tCim, 8192, j * 72, n0 + 64);
        acquire(4096);
        box(&prm.tCre8, 0, j * 72 + 64, n0); box(&prm.tCre8, 1024, j * 72 + 64, n0 + 64);
        box(&prm.tCim8, 2048, j * 72 + 64, n0); box(&prm.tCim8, 3072, j * 72 + 64, n0 + 64);
      }
      if (!rank) half_tile(512);
      else if (SPLIT) {
#pragma unroll 1
        for (int hh = 0; hh < 2; hh++) half_tile(256 + (((j >> 1) ^ 1) & 1) * 128 + hh * 64);
      }
    } else {
      const uint32_t sb = smem_base(), bars = sb + OFF_BAR;
      const int p = min((int)threadIdx.x - 288, 71);
      if (threadIdx.x < 288 + 10) asm volatile("prefetch.tensormap [%0];" ::"l"(&prm.tBre + (threadIdx.x - 288)) : "memory");
      if (warp == 10 && !(NOPF & 1)) {
        const int l = threadIdx.x & 31;
        const char* q = (const char*)(l & 1 ? prm.bim : prm.bre) + (size_t)blockIdx.x * 5184;
        mbar_wait(bars + 8 * B_X8, 0);
#pragma unroll
        for (int i = 0; i < 3; i++) if (i * 16 + (l >> 1) < 42) l2_prefetch_line(q + min((i * 16 + (l >> 1)) * 128, 5183));
      }
      const unsigned epoch = *(volatile unsigned*)&g_epoch[blockIdx.x];
      {
        const int pg = j * 72 + p;
        const float lr = __bfloat162float(prm.lre[pg]), li = __bfloat162float(prm.lim[pg]);
        const float dt = rbf(expf(__bfloat162float(prm.ldt[pg])));
        const float ea = expf(dt * lr);
        float sn, cs;
        sincosf(dt * li, &sn, &cs);
        const float ar = ea * cs, ai = ea * sn;
        float br = ar, bi = ai;
#pragma unroll
        for (int k = 0; k < 6; k++) { const float t = br * br - bi * bi; bi = 2.f * br * bi; br = t; }
        const float nr = ar - 1.f, den = 4.f / (lr * lr + li * li);
        sts64f(sb + OFF_CONST + p * 8, ar, ai);
        sts64f(sb + OFF_CONST + 576 + p * 8, br, bi);
        sts64f(sb + OFF_CONST + 1152 + p * 8, (nr * lr + ai * li) * den, (ai * lr - nr * li) * den);
      }
      STAMP(2, 0);
      bar_sync(NB_DUMP, 352);
      {
        const int lane = threadIdx.x & 31;
        const int half = warp == 11 ? (lane >> 2) & 1 : warp - 9;
        const uint32_t cu = sb + OFF_CONST + (warp == 11 ? 32 + (lane & 3) : lane) * 16;
        uint32_t a0 = sb + OFF_DUMP + half * HS_BYTES + (warp == 11 ? 16 : lane >> 2) * HS_LBO + (lane & 3) * 4;
        asm volatile("" : "+r"(a0));
        const uint32_t di = warp == 11 ? HS_LBO : 8 * HS_LBO;
        float a[4], h[4] = {0.f, 0.f, 0.f, 0.f};
        auto ld4 = [&](uint32_t ad, float (&v)[4]) { asm volatile("ld.shared.v4.f32 {%0,%1,%2,%3}, [%4];" : "=f"(v[0]), "=f"(v[1]), "=f"(v[2]), "=f"(v[3]) : "r"(ad) : "memory"); };
        auto cfma = [&](const float (&c)[4], float r0, float i0, float r1, float i1) {
          const float n0 = fmaf(c[0], h[0], fmaf(-c[1], h[1], r0)), n1 = fmaf(c[2], h[2], fmaf(-c[3], h[3], r1));
          h[1] = fmaf(c[0], h[1], fmaf(c[1], h[0], i0)); h[3] = fmaf(c[2], h[3], fmaf(c[3], h[2], i1));
          h[0] = n0; h[2] = n1;
        };
        ld4(cu, a);
#pragma unroll 1
        for (uint32_t ad = a0; ad != a0 + 1024; ad += 64) {
          uint32_t wr[4], wi[4];
#pragma unroll
          for (int k = 0; k < 4; k++) { wr[k] = lds32(ad + k * 16); wi[k] = lds32(ad + di + k * 16); }
#pragma unroll
          for (int k = 0; k < 4; k++) cfma(a, bflo(wr[k]), bflo(wi[k]), bfhi(wr[k]), bfhi(wi[k]));
        }
        if (half == 0) sts128(cu + 1728, __float_as_uint(h[0]), __float_as_uint(h[1]), __float_as_uint(h[2]), __float_as_uint(h[3]));
        bar_sync(NB_SCAN, 96);
        if (half == 1 && m < 15) {
          float b[4], s1[4] = {h[0], h[1], h[2], h[3]};
          ld4(cu + 576, b); ld4(cu + 1728, h);
          cfma(b, s1[0], s1[1], s1[2], s1[3]);
          uint2* gp = &g_S[epoch & 1][m][j][(cu - sb - OFF_CONST) >> 3];
          asm volatile("st.relaxed.gpu.global.v2.b64 [%0], {%1,%2};" ::"l"(gp), "l"(~(((uint64_t)__float_as_uint(h[1]) << 32) | __float_as_uint(h[0]))),
                       "l"(~(((uint64_t)__float_as_uint(h[3]) << 32) | __float_as_uint(h[2]))) : "memory");
        }
        __syncwarp();
        g_S[(epoch & 1) ^ 1][m][j][p] = make_uint2(0u, 0u);
        STAMP(2, 4);
        {
          const float2 b = lds64f(sb + OFF_CONST + 576 + p * 8);
          const float br = b.x * b.x - b.y * b.y, bi = 2.f * b.x * b.y;
          float hr = 0.f, hi = 0.f;
          const uint2* sp = &g_S[epoch & 1][0][j][p];
#pragma unroll 1
          for (int left = m; left > 0; left -= 3, sp += 3 * 768) {
            uint32_t v[3][2];
            int spins = 0;
            uint32_t ok;
            do {
#pragma unroll
              for (int k = 0; k < 3; k++) {
                v[k][0] = v[k][1] = 0xffffffffu;
                if (k < left) asm volatile("ld.relaxed.gpu.global.v2.b32 {%0,%1}, [%2];" : "=r"(v[k][0]), "=r"(v[k][1]) : "l"(sp + k * 768) : "memory");
              }
              ok = min(min(min(v[0][0], v[0][1]), min(v[1][0], v[1][1])), min(v[2][0], v[2][1]));
              if (++spins > (1 << 22)) __trap();
            } while (ok == 0u);
#pragma unroll
            for (int k = 0; k < 3; k++)
              if (k < left) { const float nr = fmaf(br, hr, fmaf(-bi, hi, __uint_as_float(~v[k][0]))); hi = fmaf(br, hi, fmaf(bi, hr, __uint_as_float(~v[k][1]))); hr = nr; }
          }
          sts64f(sb + OFF_CONST + p * 8, hr, hi);
        }
        __syncwarp();
        bar_sync(NB_SCAN, 96);
        STAMP(2, 5);
        ld4(cu, h);
        uint32_t cr, ci, cn;
        {
          float b[4], s0[4];
          ld4(cu + 576, b); ld4(cu + 1728, s0);
          if (half == 1) cfma(b, s0[0], s0[1], s0[2], s0[3]);
          ld4(cu + 1152, b);
          cr = pack_bf16(b[0], b[2]); ci = pack_bf16(b[1], b[3]); cn = ci ^ 0x80008000u;
        }
        __syncwarp();
#pragma unroll 1
        for (uint32_t ad = a0; ad != a0 + 1024; ad += 32) {
          uint32_t wr[2], wi[2];
#pragma unroll
          for (int k = 0; k < 2; k++) { wr[k] = lds32(ad + k * 16); wi[k] = lds32(ad + di + k * 16); }
#pragma unroll
          for (int k = 0; k < 2; k++) {
            cfma(a, bflo(wr[k]), bflo(wi[k]), bfhi(wr[k]), bfhi(wi[k]));
            const uint32_t hr = pack_bf16(h[0], h[2]), hn = pack_bf16(-h[1], -h[3]);
            uint32_t o0, o1;
            asm("{.reg .b32 t; mul.rn.bf16x2 t, %2, %4; fma.rn.bf16x2 %0, %1, %3, t;}" : "=r"(o0) : "r"(hr), "r"(hn), "r"(cr), "r"(ci));
            asm("{.reg .b32 t; mul.rn.bf16x2 t, %1, %4; fma.rn.bf16x2 %0, %2, %3, t;}" : "=r"(o1) : "r"(hr), "r"(hn), "r"(cr), "r"(cn));
            asm volatile("st.shared.b32 [%0], %1;" ::"r"(ad + k * 16), "r"(o0) : "memory");
            asm volatile("st.shared.b32 [%0], %1;" ::"r"(ad + di + k * 16), "r"(o1) : "memory");
          }
        }
        asm volatile("fence.proxy.async.shared::cta;" ::: "memory");
      }
      STAMP(2, 6);
      bar_sync(NB_SCAN, 96);
      if (warp == 9) {
        if (elect()) {
#pragma unroll 1
          for (uint32_t o = 0; o < 2 * HS_BYTES; o += 4 * HS_LBO) {
            asm volatile("cp.async.bulk.global.shared::cta.bulk_group [%0], [%1], %2;" ::"l"(&g_hs[blockIdx.x][o]), "r"(sb + OFF_DUMP + o), "r"(4 * HS_LBO) : "memory");
            asm volatile("cp.async.bulk.commit_group;\ncp.async.bulk.wait_group.read 0;" ::: "memory");
            if (PACEP) __nanosleep(PACEP);
          }
          mbar_arrive(bars + 8 * B_SCAN);
        }
        __syncwarp();
        STAMP(2, 2);
      }
      if (warp == 9) {
        if (elect()) {
          __threadfence();
          asm volatile("red.release.gpu.global.add.u32 [%0], 1;" ::"l"(&g_ready[m]) : "memory");
          g_epoch[blockIdx.x] = epoch + 1u;
          asm volatile("cp.async.bulk.wait_group 0;" ::: "memory");
        }
        __syncwarp();
        STAMP(2, 7);
        bar_sync(NB_HFREE, 288);
        if (elect()) {
          mbar_arrive(bars + 8 * B_HFREE);
          mbar_expect(bars + 8 * B_HSFULL, 2 * HS_BYTES);
          asm volatile("cp.async.bulk.shared::cluster.global.mbarrier::complete_tx::bytes [%0], [%1], %2, [%3];" ::"r"(sb + OFF_HS),
                       "l"(&g_hs[blockIdx.x][0]), "r"(2 * HS_BYTES), "r"(bars + 8 * B_HSFULL) : "memory");
          for (int w = 0; w < 2; w++) mbar_arrive_cta(bars + 8 * (B_RFREE + w), rank ^ 1);
        }
        __syncwarp();
        STAMP_DUMP(2);
      } else {
        const int w = warp - 10;
        {
          const unsigned target = 8u * (epoch + 1u);
          int spins = 0;
          unsigned v;
          do {
            if (POLL && spins) __nanosleep(500);
            asm volatile("ld.relaxed.gpu.global.u32 %0, [%1];" : "=r"(v) : "l"(&g_ready[m]) : "memory");
            if (++spins > (1 << 21)) __trap();
          } while ((int)(v - target) < 0);
          asm volatile("fence.acq_rel.gpu;" ::: "memory");
          asm volatile("fence.proxy.async.global;" ::: "memory");
        }
        const uint32_t stg = sb + OFF_STG + w * 32768;
        const int nu = 5 + (SPLIT & rank);
#pragma unroll 1
        for (int u = 0; u < nu; u++) {
          const int t = u - rank;
          if (t == 0 || t == 2) {
            if (elect()) mbar_expect(bars + 8 * (B_RFULL + w), 16384);
            mbar_wait(bars + 8 * (B_SFULL + w), u & 1);
            mbar_wait(bars + 8 * (B_RFREE + w), t >> 1);
            if (elect())
              asm volatile("{.reg .b32 ra, rb; mapa.shared::cluster.u32 ra, %0, %3; mapa.shared::cluster.u32 rb, %2, %3;\n"
                           "cp.async.bulk.shared::cluster.shared::cta.mbarrier::complete_tx::bytes [ra], [%1], 16384, [rb];}" ::"r"(stg + 16384),
                           "r"(stg), "r"(bars + 8 * (B_RFULL + w)), "r"(rank ^ 1) : "memory");
            mbar_wait(bars + 8 * (B_RFULL + w), t >> 1);
            if (elect()) mbar_arrive_cta(bars + 8 * (B_SFREE + w), rank ^ 1);
          } else {
            mbar_wait(bars + 8 * (B_SFULL + w), u & 1);
            const bool d = u == (rank ? 0 : 4), hf = SPLIT && rank && u >= 4;
            const int n0 = d ? 512 : rank * 256 + (((min(t, 3) >> 1) ^ (j >> 1)) & 1) * 128 + (u == 5 ? 64 : 0);
            const uint32_t src = d && !rank ? sb + (2 + w) * SLOT : stg + (u == 5 ? 16384 : 0);
            if (elect()) {
#pragma unroll 1
              for (int b = 0; b < (d || hf ? 2 : 4); b++) {
                asm volatile("cp.reduce.async.bulk.tensor.4d.global.shared::cta.add.tile.bulk_group [%0, {%1,%2,%2,%3}], [%4];" ::"l"(&prm.tOut), "r"(n0 + b * 32), "r"(0),
                             "r"(m * 16 + w * 8), "r"(src + b * 8192) : "memory");
                asm volatile("cp.async.bulk.commit_group;" ::: "memory");
                if (PACE && u < nu - 1) { asm volatile("cp.async.bulk.wait_group.read 0;" ::: "memory"); if (PACE > 1) __nanosleep(PACE); }
              }
              if (u < 3) {
                asm volatile("cp.async.bulk.wait_group.read 0;" ::: "memory");
                mbar_arrive(bars + 8 * (B_SFREE + w));
                if (t == 1) mbar_arrive_cta(bars + 8 * (B_RFREE + w), rank ^ 1);
              }
              if (u == nu - 1) asm volatile("cp.async.bulk.wait_group.read 0;" ::: "memory");
            }
          }
          __syncwarp();
        }
      }
    }
  } else {
    asm volatile("setmaxnreg.inc.sync.aligned.u32 240;");
    const uint32_t sb = smem_base(), bars = sb + OFF_BAR;
    const int wg = warp >> 2, w4 = warp & 3;
    const int lane = threadIdx.x & 31, g = lane >> 2, q = lane & 3;
    const uint32_t hw = sb + OFF_H + wg * 65536;
    STAMP(wg, 0);

    int s = 0, nst = NST; uint32_t ph = 0;
    auto release = [&](int st) { if (w4 == 0) { if (elect()) mbar_arrive(bars + 8 * (B_EMPTY + st)); } };
    const uint32_t dring = (sb & 0x3FFFF) >> 4;
    uint32_t dlo; int prev = 0;
    auto stage_begin = [&]() { mbar_wait(bars + 8 * (B_FULL + s), ph); dlo = dring + s * (SLOT >> 4); wg_fence(); };
    auto advance = [&]() { if (++s == nst) { s = 0; ph ^= 1; } };
    auto stage_end = [&](bool rel) {
      wg_commit();
      if (rel) { wg_wait<1>(); release(prev); }
      prev = s;
      advance();
    };

    uint32_t xa[144];
    uint32_t xr[18], dk[9];
    uint32_t rh[2], cc[2];
#pragma unroll
    for (int i = 0; i < 9; i++) dk[i] = __ldg((const uint32_t*)(prm.dskip + j * 72 + i * 8 + q * 2));
    {
      const int r = w4 * 16 + (lane & 7) + ((lane >> 3) & 1) * 8;
      const uint32_t ro = r * 128, cx = ((lane >> 4) ^ (lane & 7)) << 4;
      float s1[2][4] = {};
      auto load = [&](int kb, uint32_t base) {
#pragma unroll
        for (int kk = 0; kk < 4; kk++) {
          const int i = (kb * 4 + kk) * 4;
          asm volatile("ldmatrix.sync.aligned.m8n8.x4.shared.b16 {%0,%1,%2,%3}, [%4];"
                       : "=r"(xa[i]), "=r"(xa[i + 1]), "=r"(xa[i + 2]), "=r"(xa[i + 3]) : "r"(base + ro + (cx ^ (kk << 5))) : "memory");
        }
      };
      const uint32_t b0 = (g & 1) ? 0u : 0x3f803f80u, b1 = b0 ^ 0x3f803f80u;
      auto sums = [&](int kb) {
#pragma unroll
        for (int kk = 0; kk < 4; kk += GRP) {
          const int i = (kb * 4 + kk) * 4;
          uint32_t a[4];
#pragma unroll
          for (int e = 0; e < 2; e++) {
            asm("mul.rn.bf16x2 %0, %1, %1;" : "=r"(a[e]) : "r"(xa[i + e]));
            asm("add.rn.bf16x2 %0, %1, %2;" : "=r"(a[2 + e]) : "r"(xa[i + e]), "r"(xa[i + 2 + e]));
            asm("fma.rn.bf16x2 %0, %1, %1, %0;" : "+r"(a[e]) : "r"(xa[i + 2 + e]));
            if (GRP == 2) {
              uint32_t t, u;
              asm("mul.rn.bf16x2 %0, %1, %1;" : "=r"(t) : "r"(xa[i + 4 + e]));
              asm("add.rn.bf16x2 %0, %1, %2;" : "=r"(u) : "r"(xa[i + 4 + e]), "r"(xa[i + 6 + e]));
              asm("fma.rn.bf16x2 %0, %1, %1, %0;" : "+r"(t) : "r"(xa[i + 6 + e]));
              asm("add.rn.bf16x2 %0, %0, %1;" : "+r"(a[e]) : "r"(t));
              asm("add.rn.bf16x2 %0, %0, %1;" : "+r"(a[2 + e]) : "r"(u));
            }
          }
          mma16816(s1[(kk / GRP) & 1], a[0], a[1], a[2], a[3], b0, b1);
        }
      };
#pragma unroll
      for (int i = 0; i < 9; i++) {
        const int c8 = j * 9 + i, kb = c8 >> 3;
        xr[2 * i] = (kb < 8 ? hw + kb * 8192 : sb + wg * 8192) + (w4 * 16 + g) * 128 + (((c8 & 7) ^ g) << 4) + q * 4;
        asm volatile("" : "+r"(xr[2 * i]));
      }
      mbar_wait(bars + 8 * B_X8, 0);
      if (STX) STAMP(wg, 21);
      load(8, sb + wg * 8192);
#pragma unroll
      for (int kp = 0; kp < 4; kp++) {
        mbar_wait(bars + 8 * (B_X + wg * 4 + kp), 0);
        if (STX) STAMP(wg, 22 + kp);
        load(2 * kp, hw + 2 * kp * 8192);
        load(2 * kp + 1, hw + (2 * kp + 1) * 8192);
        if (kp == 0) sums(8); else { sums(2 * kp - 2); sums(2 * kp - 1); }
      }
#pragma unroll
      for (int i = 0; i < 9; i++) if (!NORES) { xr[2 * i + 1] = lds32(xr[2 * i] + 1024); xr[2 * i] = lds32(xr[2 * i]); }
      sums(6);
      asm volatile("fence.proxy.async.shared::cta;" ::: "memory");
      bar_arrive(NB_XDONE + wg, 160);
      sums(7);
      if (wg == 1) bar_arrive(NB_STATS, 256);
      if (STX) STAMP(wg, 1);
#pragma unroll
      for (int e = 0; e < 2; e++) {
        const float mu = (s1[0][2 * e + 1] + s1[1][2 * e + 1]) * (1.f / kD);
        const float var = fmaxf(fmaf(-mu, mu, (s1[0][2 * e] + s1[1][2 * e]) * (1.f / kD)), 0.f);
        float sd, r;
        asm("sqrt.approx.f32 %0, %1;" : "=f"(sd) : "f"(rbf(rbf(var) + 1e-5f)));
        asm("rcp.approx.ftz.f32 %0, %1;" : "=f"(r) : "f"(rbf(sd)));
        r = rbf(0.5f * r);
        rh[e] = pack_bf16(r, r); cc[e] = pack_bf16(-mu * r, -mu * r);
      }
    }
    STAMP(wg, 2);

    auto normalise = [&](int kb) {
#pragma unroll
      for (int i = 0; i < 16; i++) asm("fma.rn.bf16x2 %0, %0, %1, %2;" : "+r"(xa[16 * kb + (i >> 3) + 2 * (i & 7)]) : "r"(rh[i >> 3]), "r"(cc[i >> 3]));
    };
    {
      float ab[36];
      float* op = prm.out + (size_t)(m * 128 + wg * 64 + w4 * 16 + g) * kD + j * 72 + q * 2;
      auto residual = [&](int i) {
        asm volatile("add.rn.bf16x2 %0, %0, %0;" : "+r"(dk[i]));
#pragma unroll
        for (int e = 0; e < 2; e++) {
          uint32_t t;
          asm("fma.rn.bf16x2 %0, %1, %2, %3;" : "=r"(t) : "r"(xr[2 * i + e]), "r"(rh[e]), "r"(cc[e]));
          asm("fma.rn.bf16x2 %0, %0, %1, %2;" : "+r"(t) : "r"(dk[i]), "r"(xr[2 * i + e]));
          *(float2*)(op + e * 8 * kD + i * 8) = make_float2(bflo(t), bfhi(t));
        }
      };
      const uint32_t da = sb + OFF_DUMP + wg * HS_BYTES + (w4 * 16 + g) * 16 + q * 4;
      auto dump = [&](int im) {
#pragma unroll
        for (int i = 0; i < 18; i++)
          asm volatile("st.shared.b32 [%0], %1;" ::"r"(da + (i < 16 ? 8 * im + (i >> 1) : 16 + im) * HS_LBO + (i & 1) * 128), "r"(pack_bf16(ab[2 * i], ab[2 * i + 1])) : "memory");
      };
      auto bu = [&](int kb, uint32_t off) {
        wg_fence();
#pragma unroll
        for (int kk = 0; kk < 4; kk++) { const int i = (kb * 4 + kk) * 4; wgmma_n72_rs_tb0(ab, xa[i], xa[i + 1], xa[i + 2], xa[i + 3], desc((dring + (off >> 4) + kk * 2) | DLO_K, DHI_SW128), (kb | kk) != 0); }
        wg_commit();
      };
      normalise(0);
      if (wg == 0) {
#pragma unroll
        for (int kb = 1; kb < 9; kb++) normalise(kb);
        bar_sync(NB_STATS, 256);
      }
#pragma unroll
      for (int kb = 0; kb < 9; kb++) {
        if ((kb & 3) == 0) mbar_wait(bars + 8 * (B_BU + (kb >> 2)), 0);
        bu(kb, kb < 8 ? OFF_BU0 + kb * 9216 : OFF_BU1);
        if (kb < 8 && wg == 1) normalise(kb + 1);
      }
      wg_wait<0>();
      if (w4 == 0) { if (elect()) mbar_arrive(bars + 8 * B_RING); }
      STAMP(wg, 19);
      keep(ab);
      dump(0);
#pragma unroll
      for (int kb = 0; kb < 9; kb++) {
        if (kb == 4) mbar_wait(bars + 8 * (B_BU + 3), 0);
        bu(kb, kb < 4 ? OFF_BU1 + (kb + 1) * 9216 : OFF_BU2 + (kb - 4) * 9216);
        if (!NORES) residual(kb);
      }
      wg_wait<0>();
      keep(ab);
      dump(1);
      bar_arrive(NB_DUMP, 352);
    }
    STAMP(wg, 3);

    float acc[64];
    {
      const uint32_t ha = sb + OFF_H + (threadIdx.x & 127) * 16, hblk = wg ? HBLK1 : HBLK0;
      auto glu = [&](int i) {
        return pack_bf16(fmaf(acc[32 + 2 * i], tanh_fast(acc[2 * i]), acc[32 + 2 * i]), fmaf(acc[33 + 2 * i], tanh_fast(acc[2 * i + 1]), acc[33 + 2 * i]));
      };
      for (int c = 0;; c++) {
        if (wg == 1) bar_sync(NB_SKEW, 256);
#pragma unroll
        for (int kb = 0; kb < 9; kb++) {
          if (kb == 7 && c == 0) nst = 8;
          if (kb == 4 && c == 3) nst = 7;
          if (kb == 2 && c == 4) nst = 6;
          stage_begin();
#pragma unroll
          for (int kk = 0; kk < 4; kk++) { const int i = (kb * 4 + kk) * 4; wgmma_n128_rs_tb1(acc, xa[i], xa[i + 1], xa[i + 2], xa[i + 3], desc((dlo + kk * 128) | DLO_MN, DHI_SW128), (kb | kk) != 0); }
          if (kb == SKEW - 1 && wg == 0 && (c > 0 || SK0 == SKEW)) bar_arrive(NB_SKEW, 256);
          if (SK0 != SKEW && kb == SK0 - 1 && wg == 0 && c == 0) bar_arrive(NB_SKEW, 256);
          if (kb == 8 && c >= 3 && c <= 5) mbar_wait(bars + 8 * (c == 5 ? B_SCAN : B_EMPTY + 10 - c), c == 3);
          stage_end(kb > 0);
        }
        wg_wait<0>();
        release(prev);
        keep(acc);
        if (c == 8) break;
        const uint32_t hc = ha + ((hblk >> (4 * c)) & 15) * 8192;
#pragma unroll
        for (int i = 0; i < 4; i++) sts128(hc + i * 2048, glu(4 * i), glu(4 * i + 1), glu(4 * i + 2), glu(4 * i + 3));
        STAMP(wg, 4 + c);
      }
#pragma unroll
      for (int i = 0; i < 32; i++) lds128(ha + ((hblk >> (4 * (i >> 2))) & 15) * 8192 + (i & 3) * 2048, xa[4 * i], xa[4 * i + 1], xa[4 * i + 2], xa[4 * i + 3]);
#pragma unroll
      for (int i = 0; i < 16; i++) xa[128 + i] = glu(i);
      asm volatile("fence.proxy.async.shared::cta;" ::: "memory");
      bar_arrive(NB_HFREE, 288);
    }
    STAMP(wg, 13);

    const uint32_t dhs = (((sb + OFF_HS + wg * HS_BYTES) & 0x3FFFF) >> 4) | DLO_HS;
    const int rp = (g >> 2) + 2 * (g & 3);
    const uint32_t so = w4 * 2048 + rp * 128 + (q & 1) * 8, sx = ((q >> 1) ^ rp) << 4;
    const uint32_t rcv = sb + OFF_STG + wg * 32768 + 16384 + w4 * 2048 + lane * 16;
    auto staged = [&]() {
      asm volatile("fence.proxy.async.shared::cta;" ::: "memory");
      __syncwarp();
      if (elect()) mbar_arrive(bars + 8 * (B_SFULL + wg));
    };
    auto half_tile = [&](const bool first, const int kind) {
      float a2[32];
      if (SKEWB > 0 && wg == 1) bar_sync(NB_SKEW, 256);
      const uint32_t ph0 = ph;
      uint32_t d4;
#pragma unroll
      for (int kp = 0; kp < 5; kp++) {
        if (kp == 4) nst = NST + 1;
        stage_begin();
#pragma unroll
        for (int kk = 0; kk < (kp < 4 ? 8 : 4); kk++) { const int i = (kp * 8 + kk) * 4; wgmma_n64_rs_tb1(a2, xa[i], xa[i + 1], xa[i + 2], xa[i + 3], desc((dlo + kk * 128) | DLO_MN, DHI_SW128), (kp | kk) != 0); }
        if (SKEWB > 0 && kp == 1 && wg == 0) bar_arrive(NB_SKEW, 256);
        d4 = dlo;
        stage_end(kp > 0);
        if (kp == 0 && !first) staged();
      }
      if (first) mbar_wait(bars + 8 * B_HSFULL, 0);
      stage_begin();
#pragma unroll
      for (int kk = 0; kk < 8; kk++) wgmma_n64_ss_tb0(a2, desc(dhs + kk * (2 * HS_LBO >> 4), DHI_NONE), desc((dlo + (kk >> 2) * 512 + (kk & 3) * 2) | DLO_K, DHI_SW128), 1);
      wgmma_n64_ss_tb0(a2, desc(dhs + 8 * (2 * HS_LBO >> 4), DHI_NONE), desc((d4 + 512) | ((1024 >> 4) << 16), DHI_NONE), 1);
      wg_commit();
      if (!first) {
        if (kind == 1) mbar_wait(bars + 8 * (B_EMPTY + 2 + wg), ph0);
        if (kind == 2) { mbar_wait(bars + 8 * (B_SFREE + wg), 1); mbar_wait(bars + 8 * (B_RFULL + wg), 1); }
      }
      wg_wait<0>();
      release(prev); release(s); advance();
      keep(a2);
      if (!first && kind >= 2) {
#pragma unroll
        for (int i = 0; i < 4; i++) {
          uint32_t v[4];
          lds128(rcv + (kind & 1) * 8192 + i * 512, v[0], v[1], v[2], v[3]);
#pragma unroll
          for (int e = 0; e < 4; e++) { a2[8 * i + 2 * e] += bflo(v[e]); a2[8 * i + 2 * e + 1] += bfhi(v[e]); }
        }
        __syncwarp();
      }
      const uint32_t stg = (!first && kind == 1 ? sb + (2 + wg) * SLOT : sb + OFF_STG + wg * 32768 + (kind == 3 ? 16384 : 0)) + so;
#pragma unroll
      for (int i = 0; i < 8; i++) {
        const uint32_t a = stg + (i >> 2) * 8192 + (sx ^ ((i & 3) << 5));
        sts64f(a, a2[4 * i], a2[4 * i + 1]);
        sts64f(a + 1024, a2[4 * i + 2], a2[4 * i + 3]);
      }
      STAMP(wg, first ? 14 : kind == 2 ? 12 : 18);
    };
    if (rank) half_tile(true, 0);
    for (int t = 0; t < 4 - (SPLIT & rank); t++) {
      if (SKEWB > 0 && wg == 1) bar_sync(NB_SKEW, 256);
#pragma unroll
      for (int kb = 0; kb < 9; kb++) {
        if (kb == 4) nst = NST + 1;
        stage_begin();
#pragma unroll
        for (int kk = 0; kk < 4; kk++) { const int i = (kb * 4 + kk) * 4; wgmma_n128_rs_tb1(acc, xa[i], xa[i + 1], xa[i + 2], xa[i + 3], desc((dlo + kk * 128) | DLO_MN, DHI_SW128), (kb | kk) != 0); }
        if (SKEWB > 0 && kb == SKEWB - 1 && wg == 0) bar_arrive(NB_SKEW, 256);
        stage_end(kb > 0);
        if (kb == 0 && t + rank > 0) staged();
      }
      if (t == 0) mbar_wait(bars + 8 * B_HSFULL, 0);
      stage_begin();
#pragma unroll
      for (int kk = 0; kk < 4; kk++) wgmma_n128_ss_tb0(acc, desc(dhs + kk * (2 * HS_LBO >> 4), DHI_NONE), desc((dlo + kk * 2) | DLO_K, DHI_SW128), 1);
      stage_end(true);
      stage_begin();
#pragma unroll
      for (int kk = 0; kk < 4; kk++) wgmma_n128_ss_tb0(acc, desc(dhs + (4 + kk) * (2 * HS_LBO >> 4), DHI_NONE), desc((dlo + kk * 2) | DLO_K, DHI_SW128), 1);
      const int s_im = s;
      advance();
      stage_begin();
      wgmma_n128_ss_tb0(acc, desc(dhs + 8 * (2 * HS_LBO >> 4), DHI_NONE), desc(dlo | ((2048 >> 4) << 16), DHI_NONE), 1);
      stage_end(true);
      if (t + rank > 0) mbar_wait(bars + 8 * (B_SFREE + wg), (t + rank - 1) & 1);
      if (t & 1) mbar_wait(bars + 8 * (B_RFULL + wg), t >> 1);
      wg_wait<0>();
      release(s_im); release(prev);
      keep(acc);
      if (t & 1) {
        const uint32_t stg = sb + OFF_STG + wg * 32768 + so;
#pragma unroll
        for (int hh = 0; hh < 2; hh++) {
#pragma unroll
          for (int i = 4 * hh; i < 4 * hh + 4; i++) {
            uint32_t v[4];
            lds128(rcv + hh * 8192 + (i & 3) * 512, v[0], v[1], v[2], v[3]);
#pragma unroll
            for (int e = 0; e < 4; e++) { acc[8 * i + 2 * e] += bflo(v[e]); acc[8 * i + 2 * e + 1] += bfhi(v[e]); }
          }
          __syncwarp();
#pragma unroll
          for (int i = 8 * hh; i < 8 * hh + 8; i++) {
            const uint32_t a = stg + (i >> 2) * 8192 + (sx ^ ((i & 3) << 5));
            sts64f(a, acc[4 * i], acc[4 * i + 1]);
            sts64f(a + 1024, acc[4 * i + 2], acc[4 * i + 3]);
          }
        }
      } else {
#pragma unroll
        for (int i = 0; i < 8; i++)
          sts128(rcv - 16384 + (i >> 2) * 8192 + (i & 3) * 512, pack_bf16(acc[8 * i], acc[8 * i + 1]), pack_bf16(acc[8 * i + 2], acc[8 * i + 3]),
                 pack_bf16(acc[8 * i + 4], acc[8 * i + 5]), pack_bf16(acc[8 * i + 6], acc[8 * i + 7]));
      }
      STAMP(wg, 14 + t + rank);
    }
    if (SPLIT || !rank) {
#pragma unroll 1
      for (int kind = 1 + rank; kind < 2 + 2 * rank; kind++) half_tile(false, kind);
    }
    staged();
    if (w4 == 0) STAMP_DUMP(wg);
  }
}

typedef CUresult (*EncodeFn)(CUtensorMap*, CUtensorMapDataType, cuuint32_t, void*, const cuuint64_t*, const cuuint64_t*, const cuuint32_t*,
                             const cuuint32_t*, CUtensorMapInterleave, CUtensorMapSwizzle, CUtensorMapL2promotion, CUtensorMapFloatOOBfill);

void map2d(EncodeFn enc, CUtensorMap* tm, const void* p, uint64_t cols, uint64_t rows, uint32_t bc, uint32_t br, CUtensorMapSwizzle sw) {
  cuuint64_t gd[2] = {cols, rows}, gs[1] = {cols * 2};
  cuuint32_t bd[2] = {bc, br}, es[2] = {1, 1};
  enc(tm, CU_TENSOR_MAP_DATA_TYPE_BFLOAT16, 2, (void*)p, gd, gs, bd, es, CU_TENSOR_MAP_INTERLEAVE_NONE, sw,
      sw == CU_TENSOR_MAP_SWIZZLE_128B ? CU_TENSOR_MAP_L2_PROMOTION_L2_128B : CU_TENSOR_MAP_L2_PROMOTION_NONE, CU_TENSOR_MAP_FLOAT_OOB_FILL_NONE);
}

}

extern "C" void kernel_launch(void* const* d_in, const int* in_sizes, int n_in, void* d_out, int out_size) {
  (void)in_sizes; (void)n_in; (void)out_size;
  static EncodeFn enc = nullptr;
  if (!enc) {
    cudaDriverEntryPointQueryResult qr;
    cudaGetDriverEntryPoint("cuTensorMapEncodeTiled", (void**)&enc, cudaEnableDefault, &qr);
    cudaFuncSetAttribute(fused_kernel, cudaFuncAttributeMaxDynamicSharedMemorySize, SMEM_BYTES);
  }
  Params prm;
  const CUtensorMapSwizzle S128 = CU_TENSOR_MAP_SWIZZLE_128B;
  map2d(enc, &prm.tx, d_in[0], kD, kS, 64, 64, S128);
  map2d(enc, &prm.tBre, d_in[3], kD, 576, 64, 72, S128);
  map2d(enc, &prm.tBim, d_in[4], kD, 576, 64, 72, S128);
  map2d(enc, &prm.tCre, d_in[5], 576, kD, 64, 64, S128);
  map2d(enc, &prm.tCim, d_in[6], 576, kD, 64, 64, S128);
  map2d(enc, &prm.tCre8, d_in[5], 576, kD, 8, 64, CU_TENSOR_MAP_SWIZZLE_NONE);
  map2d(enc, &prm.tCim8, d_in[6], 576, kD, 8, 64, CU_TENSOR_MAP_SWIZZLE_NONE);
  map2d(enc, &prm.tWg, d_in[10], kF, kD, 64, 64, S128);
  map2d(enc, &prm.tWu, d_in[11], kF, kD, 64, 64, S128);
  map2d(enc, &prm.tWd, d_in[12], kD, kF, 64, 64, S128);
  {
    cuuint64_t gd[4] = {kD, 2, 4, kS / 8}, gs[3] = {4 * kD * 4, kD * 4, 8 * kD * 4};
    cuuint32_t bd[4] = {32, 2, 4, 8}, es[4] = {1, 1, 1, 1};
    enc(&prm.tOut, CU_TENSOR_MAP_DATA_TYPE_FLOAT32, 4, d_out, gd, gs, bd, es, CU_TENSOR_MAP_INTERLEAVE_NONE, S128, CU_TENSOR_MAP_L2_PROMOTION_NONE,
        CU_TENSOR_MAP_FLOAT_OOB_FILL_NONE);
  }
  prm.x = (const __nv_bfloat16*)d_in[0];
  prm.lre = (const __nv_bfloat16*)d_in[1];
  prm.lim = (const __nv_bfloat16*)d_in[2];
  prm.bre = (const __nv_bfloat16*)d_in[3];
  prm.bim = (const __nv_bfloat16*)d_in[4];
  prm.cre = (const __nv_bfloat16*)d_in[5];
  prm.cim = (const __nv_bfloat16*)d_in[6];
  prm.wg = (const __nv_bfloat16*)d_in[10];
  prm.wu = (const __nv_bfloat16*)d_in[11];
  prm.wd = (const __nv_bfloat16*)d_in[12];
  prm.ldt = (const __nv_bfloat16*)d_in[7];
  prm.dskip = (const __nv_bfloat16*)d_in[8];
  prm.out = (float*)d_out;

  fused_kernel<<<128, 384, SMEM_BYTES, cudaStreamPerThread>>>(prm);
}
```

```cpp
#include <cuda_runtime.h>
#include <cuda.h>
#include <cuda_bf16.h>
#include <stdint.h>

namespace {

constexpr int kS = 2048, kD = 576, kF = 4608;
constexpr int SKEW = 4;
constexpr int PFD = 18;
constexpr int NST = 6;
constexpr uint32_t SLOT = 16384;
constexpr uint32_t OFF_H = NST * SLOT;
constexpr uint32_t HS_LBO = 1040;
constexpr uint32_t HS_BYTES = 18 * HS_LBO;
constexpr uint32_t OFF_DUMP = OFF_H + 65536 - HS_BYTES;
constexpr uint32_t OFF_STG = OFF_H + SLOT;
constexpr uint32_t OFF_HS = OFF_STG + 65536;
constexpr uint32_t OFF_BAR = OFF_H + 131072;
constexpr uint32_t OFF_CONST = OFF_BAR + 384;
constexpr uint32_t SMEM_BYTES = OFF_CONST + 4 * 576 + 384;
static_assert(SMEM_BYTES <= 232448 && OFF_HS + 2 * HS_BYTES <= OFF_BAR, "smem");

enum { B_FULL = 0, B_EMPTY = NST + 2, B_X = 2 * NST + 4, B_X8 = B_X + 8, B_BU  , B_RING = B_BU + 4, B_SCAN, B_HFREE, B_HSFULL, B_SFULL,
       B_SFREE = B_SFULL + 2, B_RFULL = B_SFREE + 2, B_RFREE = B_RFULL + 2, B_COUNT = B_RFREE + 2 };
static_assert(B_COUNT * 8 <= 384, "barriers");
enum { NB_SKEW = 1, NB_XDONE = 2  , NB_SCAN = 4, NB_DUMP = 5, NB_HFREE = 6, NB_STATS = 7 };
constexpr uint32_t HBLK0 = 0x76502CB4u, HBLK1 = 0x89A13DEFu;
constexpr uint32_t OFF_BU0 = SLOT, OFF_BU1 = OFF_H, OFF_BU2 = OFF_H + 65536 + 19456;
static_assert(OFF_BU1 + 5 * 9216 <= OFF_DUMP && OFF_BU2 >= OFF_DUMP + 2 * HS_BYTES && OFF_BU2 + 5 * 9216 <= OFF_BAR, "Bu tiles");

struct __align__(64) Params {
  CUtensorMap tx, tBre, tBim, tWg, tWu, tWd, tCre, tCim, tCre8, tCim8, tOut;
  const __nv_bfloat16 *x, *lre, *lim, *bre, *bim, *cre, *cim, *ldt, *dskip, *wg, *wu, *wd;
  float* out;
};

__device__ unsigned g_epoch[128];
__device__ unsigned g_ready[16];
__device__ __align__(256) uint2 g_S[2][16][8][96];
__device__ __align__(128) uint8_t g_hs[128][2 * HS_BYTES];

__device__ __forceinline__ void wgmma_n72_rs_tb0(float (&d)[36], uint32_t a0, uint32_t a1, uint32_t a2, uint32_t a3, uint64_t db, int scale_d) {
  asm volatile("{\n.reg .pred p;\nsetp.ne.b32 p, %41, 0;\n"
    "wgmma.mma_async.sync.aligned.m64n72k16.f32.bf16.bf16 {"
    "%0, %1, %2, %3, %4, %5, %6, %7, %8, %9, %10, %11, %12, %13, %14, %15, "
    "%16, %17, %18, %19, %20, %21, %22, %23, %24, %25, %26, %27, %28, %29, %30, %31, "
    "%32, %33, %34, %35"
    "}, {%36, %37, %38, %39}, %40, p, 1, 1, 0;\n}\n"
    : "+f"(d[0]), "+f"(d[1]), "+f"(d[2]), "+f"(d[3]), "+f"(d[4]), "+f"(d[5]), "+f"(d[6]), "+f"(d[7]),
      "+f"(d[8]), "+f"(d[9]), "+f"(d[10]), "+f"(d[11]), "+f"(d[12]), "+f"(d[13]), "+f"(d[14]), "+f"(d[15]),
      "+f"(d[16]), "+f"(d[17]), "+f"(d[18]), "+f"(d[19]), "+f"(d[20]), "+f"(d[21]), "+f"(d[22]), "+f"(d[23]),
      "+f"(d[24]), "+f"(d[25]), "+f"(d[26]), "+f"(d[27]), "+f"(d[28]), "+f"(d[29]), "+f"(d[30]), "+f"(d[31]),
      "+f"(d[32]), "+f"(d[33]), "+f"(d[34]), "+f"(d[35])
    : "r"(a0), "r"(a1), "r"(a2), "r"(a3), "l"(db), "r"(scale_d));
}
__device__ __forceinline__ void wgmma_n128_rs_tb1(float (&d)[64], uint32_t a0, uint32_t a1, uint32_t a2, uint32_t a3, uint64_t db, int scale_d) {
  asm volatile("{\n.reg .pred p;\nsetp.ne.b32 p, %69, 0;\n"
    "wgmma.mma_async.sync.aligned.m64n128k16.f32.bf16.bf16 {"
    "%0, %1, %2, %3, %4, %5, %6, %7, %8, %9, %10, %11, %12, %13, %14, %15, "
    "%16, %17, %18, %19, %20, %21, %22, %23, %24, %25, %26, %27, %28, %29, %30, %31, "
    "%32, %33, %34, %35, %36, %37, %38, %39, %40, %41, %42, %43, %44, %45, %46, %47, "
    "%48, %49, %50, %51, %52, %53, %54, %55, %56, %57, %58, %59, %60, %61, %62, %63"
    "}, {%64, %65, %66, %67}, %68, p, 1, 1, 1;\n}\n"
    : "+f"(d[0]), "+f"(d[1]), "+f"(d[2]), "+f"(d[3]), "+f"(d[4]), "+f"(d[5]), "+f"(d[6]), "+f"(d[7]),
      "+f"(d[8]), "+f"(d[9]), "+f"(d[10]), "+f"(d[11]), "+f"(d[12]), "+f"(d[13]), "+f"(d[14]), "+f"(d[15]),
      "+f"(d[16]), "+f"(d[17]), "+f"(d[18]), "+f"(d[19]), "+f"(d[20]), "+f"(d[21]), "+f"(d[22]), "+f"(d[23]),
      "+f"(d[24]), "+f"(d[25]), "+f"(d[26]), "+f"(d[27]), "+f"(d[28]), "+f"(d[29]), "+f"(d[30]), "+f"(d[31]),
      "+f"(d[32]), "+f"(d[33]), "+f"(d[34]), "+f"(d[35]), "+f"(d[36]), "+f"(d[37]), "+f"(d[38]), "+f"(d[39]),
      "+f"(d[40]), "+f"(d[41]), "+f"(d[42]), "+f"(d[43]), "+f"(d[44]), "+f"(d[45]), "+f"(d[46]), "+f"(d[47]),
      "+f"(d[48]), "+f"(d[49]), "+f"(d[50]), "+f"(d[51]), "+f"(d[52]), "+f"(d[53]), "+f"(d[54]), "+f"(d[55]),
      "+f"(d[56]), "+f"(d[57]), "+f"(d[58]), "+f"(d[59]), "+f"(d[60]), "+f"(d[61]), "+f"(d[62]), "+f"(d[63])
    : "r"(a0), "r"(a1), "r"(a2), "r"(a3), "l"(db), "r"(scale_d));
}
__device__ __forceinline__ void wgmma_n128_ss_tb0(float (&d)[64], uint64_t da, uint64_t db, int scale_d) {
  asm volatile("{\n.reg .pred p;\nsetp.ne.b32 p, %66, 0;\n"
    "wgmma.mma_async.sync.aligned.m64n128k16.f32.bf16.bf16 {"
    "%0, %1, %2, %3, %4, %5, %6, %7, %8, %9, %10, %11, %12, %13, %14, %15, "
    "%16, %17, %18, %19, %20, %21, %22, %23, %24, %25, %26, %27, %28, %29, %30, %31, "
    "%32, %33, %34, %35, %36, %37, %38, %39, %40, %41, %42, %43, %44, %45, %46, %47, "
    "%48, %49, %50, %51, %52, %53, %54, %55, %56, %57, %58, %59, %60, %61, %62, %63"
    "}, %64, %65, p, 1, 1, 0, 0;\n}\n"
    : "+f"(d[0]), "+f"(d[1]), "+f"(d[2]), "+f"(d[3]), "+f"(d[4]), "+f"(d[5]), "+f"(d[6]), "+f"(d[7]),
      "+f"(d[8]), "+f"(d[9]), "+f"(d[10]), "+f"(d[11]), "+f"(d[12]), "+f"(d[13]), "+f"(d[14]), "+f"(d[15]),
      "+f"(d[16]), "+f"(d[17]), "+f"(d[18]), "+f"(d[19]), "+f"(d[20]), "+f"(d[21]), "+f"(d[22]), "+f"(d[23]),
      "+f"(d[24]), "+f"(d[25]), "+f"(d[26]), "+f"(d[27]), "+f"(d[28]), "+f"(d[29]), "+f"(d[30]), "+f"(d[31]),
      "+f"(d[32]), "+f"(d[33]), "+f"(d[34]), "+f"(d[35]), "+f"(d[36]), "+f"(d[37]), "+f"(d[38]), "+f"(d[39]),
      "+f"(d[40]), "+f"(d[41]), "+f"(d[42]), "+f"(d[43]), "+f"(d[44]), "+f"(d[45]), "+f"(d[46]), "+f"(d[47]),
      "+f"(d[48]), "+f"(d[49]), "+f"(d[50]), "+f"(d[51]), "+f"(d[52]), "+f"(d[53]), "+f"(d[54]), "+f"(d[55]),
      "+f"(d[56]), "+f"(d[57]), "+f"(d[58]), "+f"(d[59]), "+f"(d[60]), "+f"(d[61]), "+f"(d[62]), "+f"(d[63])
    : "l"(da), "l"(db), "r"(scale_d));
}
__device__ __forceinline__ void wgmma_n64_rs_tb1(float (&d)[32], uint32_t a0, uint32_t a1, uint32_t a2, uint32_t a3, uint64_t db, int scale_d) {
  asm volatile("{\n.reg .pred p;\nsetp.ne.b32 p, %37, 0;\n"
    "wgmma.mma_async.sync.aligned.m64n64k16.f32.bf16.bf16 {"
    "%0, %1, %2, %3, %4, %5, %6, %7, %8, %9, %10, %11, %12, %13, %14, %15, "
    "%16, %17, %18, %19, %20, %21, %22, %23, %24, %25, %26, %27, %28, %29, %30, %31"
    "}, {%32, %33, %34, %35}, %36, p, 1, 1, 1;\n}\n"
    : "+f"(d[0]), "+f"(d[1]), "+f"(d[2]), "+f"(d[3]), "+f"(d[4]), "+f"(d[5]), "+f"(d[6]), "+f"(d[7]),
      "+f"(d[8]), "+f"(d[9]), "+f"(d[10]), "+f"(d[11]), "+f"(d[12]), "+f"(d[13]), "+f"(d[14]), "+f"(d[15]),
      "+f"(d[16]), "+f"(d[17]), "+f"(d[18]), "+f"(d[19]), "+f"(d[20]), "+f"(d[21]), "+f"(d[22]), "+f"(d[23]),
      "+f"(d[24]), "+f"(d[25]), "+f"(d[26]), "+f"(d[27]), "+f"(d[28]), "+f"(d[29]), "+f"(d[30]), "+f"(d[31])
    : "r"(a0), "r"(a1), "r"(a2), "r"(a3), "l"(db), "r"(scale_d));
}
__device__ __forceinline__ void wgmma_n64_ss_tb0(float (&d)[32], uint64_t da, uint64_t db, int scale_d) {
  asm volatile("{\n.reg .pred p;\nsetp.ne.b32 p, %34, 0;\n"
    "wgmma.mma_async.sync.aligned.m64n64k16.f32.bf16.bf16 {"
    "%0, %1, %2, %3, %4, %5, %6, %7, %8, %9, %10, %11, %12, %13, %14, %15, "
    "%16, %17, %18, %19, %20, %21, %22, %23, %24, %25, %26, %27, %28, %29, %30, %31"
    "}, %32, %33, p, 1, 1, 0, 0;\n}\n"
    : "+f"(d[0]), "+f"(d[1]), "+f"(d[2]), "+f"(d[3]), "+f"(d[4]), "+f"(d[5]), "+f"(d[6]), "+f"(d[7]),
      "+f"(d[8]), "+f"(d[9]), "+f"(d[10]), "+f"(d[11]), "+f"(d[12]), "+f"(d[13]), "+f"(d[14]), "+f"(d[15]),
      "+f"(d[16]), "+f"(d[17]), "+f"(d[18]), "+f"(d[19]), "+f"(d[20]), "+f"(d[21]), "+f"(d[22]), "+f"(d[23]),
      "+f"(d[24]), "+f"(d[25]), "+f"(d[26]), "+f"(d[27]), "+f"(d[28]), "+f"(d[29]), "+f"(d[30]), "+f"(d[31])
    : "l"(da), "l"(db), "r"(scale_d));
}

__device__ __forceinline__ bool elect() {
  uint32_t p;
  asm volatile("{.reg .pred q; elect.sync _|q, 0xffffffff; selp.u32 %0,1,0,q;}" : "=r"(p));
  return p;
}
__device__ __forceinline__ void mbar_init(uint32_t bar, uint32_t cnt) { asm volatile("mbarrier.init.shared::cta.b64 [%0], %1;" ::"r"(bar), "r"(cnt) : "memory"); }
__device__ __forceinline__ void mbar_expect(uint32_t bar, uint32_t bytes) { asm volatile("mbarrier.arrive.expect_tx.shared::cta.b64 _, [%0], %1;" ::"r"(bar), "r"(bytes) : "memory"); }
__device__ __forceinline__ void mbar_arrive(uint32_t bar) { asm volatile("mbarrier.arrive.shared::cta.b64 _, [%0];" ::"r"(bar) : "memory"); }
__device__ __forceinline__ void mbar_arrive_cta(uint32_t bar, uint32_t cta) {
  asm volatile("{.reg .b32 ra; mapa.shared::cluster.u32 ra, %0, %1; mbarrier.arrive.shared::cluster.b64 _, [ra];}" ::"r"(bar), "r"(cta) : "memory");
}
__device__ __forceinline__ void mbar_wait(uint32_t bar, uint32_t parity) {
  asm volatile(
      "{\n.reg .pred p;\n.reg .u32 c, t;\n"
      "mbarrier.try_wait.parity.shared::cta.b64 p, [%0], %1;\n@p bra DONE;\n"
      "mov.u32 c, %%clock;\n"
      "LAB_WAIT:\nmbarrier.try_wait.parity.shared::cta.b64 p, [%0], %1;\n@p bra DONE;\n"
      "mov.u32 t, %%clock;\nsub.u32 t, t, c;\nsetp.lt.u32 p, t, 0x40000000;\n@p bra LAB_WAIT;\ntrap;\nDONE:\n}" ::"r"(bar), "r"(parity) : "memory");
}
__device__ __forceinline__ void bar_sync(int id, int n) { asm volatile("bar.sync %0, %1;" ::"r"(id), "r"(n) : "memory"); }
__device__ __forceinline__ void bar_arrive(int id, int n) { asm volatile("bar.arrive %0, %1;" ::"r"(id), "r"(n) : "memory"); }
__device__ __forceinline__ void wg_fence() { asm volatile("wgmma.fence.sync.aligned;" ::: "memory"); }
__device__ __forceinline__ void wg_commit() { asm volatile("wgmma.commit_group.sync.aligned;" ::: "memory"); }
template <int N> __device__ __forceinline__ void wg_wait() { asm volatile("wgmma.wait_group.sync.aligned %0;" ::"n"(N) : "memory"); }
__device__ __forceinline__ void tma2d(uint32_t dst, const CUtensorMap* tm, uint32_t bar, int c0, int c1) {
  asm volatile("cp.async.bulk.tensor.2d.shared::cluster.global.mbarrier::complete_tx::bytes [%0], [%1,{%3,%4}], [%2];" ::"r"(dst), "l"(tm), "r"(bar), "r"(c0), "r"(c1) : "memory");
}
__device__ __forceinline__ void tma2d_mc(uint32_t dst, const CUtensorMap* tm, uint32_t bar, int c0, int c1) {
  asm volatile("cp.async.bulk.tensor.2d.shared::cluster.global.mbarrier::complete_tx::bytes.multicast::cluster [%0], [%1,{%3,%4}], [%2], %5;" ::"r"(dst), "l"(tm), "r"(bar), "r"(c0), "r"(c1), "h"((uint16_t)3) : "memory");
}
__device__ __forceinline__ void l2_prefetch_line(const void* p) { asm volatile("prefetch.global.L2 [%0];" ::"l"(p)); }
__device__ __forceinline__ uint64_t desc(uint32_t lo, uint32_t hi) { return ((uint64_t)hi << 32) | lo; }
constexpr uint32_t DHI_SW128 = (1024 >> 4) | (1u << 30);
constexpr uint32_t DHI_NONE = (128 >> 4);
constexpr uint32_t DLO_HS = (HS_LBO >> 4) << 16;
constexpr uint32_t DLO_MN = (8192 >> 4) << 16;
constexpr uint32_t DLO_K = 1u << 16;
__device__ __forceinline__ float tanh_fast(float x) { float y; asm("tanh.approx.f32 %0, %1;" : "=f"(y) : "f"(x)); return y; }
__device__ __forceinline__ uint32_t pack_bf16(float lo, float hi) { uint32_t r; asm("cvt.rn.bf16x2.f32 %0, %1, %2;" : "=r"(r) : "f"(hi), "f"(lo)); return r; }
__device__ __forceinline__ float rbf(float x) { return __bfloat162float(__float2bfloat16_rn(x)); }
__device__ __forceinline__ void mma16816(float (&c)[4], uint32_t a0, uint32_t a1, uint32_t a2, uint32_t a3, uint32_t b0, uint32_t b1) {
  asm volatile("mma.sync.aligned.m16n8k16.row.col.f32.bf16.bf16.f32 {%0,%1,%2,%3}, {%4,%5,%6,%7}, {%8,%9}, {%0,%1,%2,%3};"
               : "+f"(c[0]), "+f"(c[1]), "+f"(c[2]), "+f"(c[3]) : "r"(a0), "r"(a1), "r"(a2), "r"(a3), "r"(b0), "r"(b1));
}
__device__ __forceinline__ void sts128(uint32_t a, uint32_t x, uint32_t y, uint32_t z, uint32_t w) {
  asm volatile("st.shared.v4.b32 [%0], {%1,%2,%3,%4};" ::"r"(a), "r"(x), "r"(y), "r"(z), "r"(w) : "memory");
}
__device__ __forceinline__ void sts64f(uint32_t a, float x, float y) { asm volatile("st.shared.v2.f32 [%0], {%1,%2};" ::"r"(a), "f"(x), "f"(y) : "memory"); }
__device__ __forceinline__ float2 lds64f(uint32_t a) { float2 v; asm volatile("ld.shared.v2.f32 {%0,%1}, [%2];" : "=f"(v.x), "=f"(v.y) : "r"(a) : "memory"); return v; }
__device__ __forceinline__ uint32_t lds32(uint32_t a) { uint32_t v; asm volatile("ld.shared.b32 %0, [%1];" : "=r"(v) : "r"(a) : "memory"); return v; }
__device__ __forceinline__ void lds128(uint32_t a, uint32_t& x, uint32_t& y, uint32_t& z, uint32_t& w) {
  asm volatile("ld.shared.v4.b32 {%0,%1,%2,%3}, [%4];" : "=r"(x), "=r"(y), "=r"(z), "=r"(w) : "r"(a) : "memory");
}
__device__ __forceinline__ float bflo(uint32_t v) { return __uint_as_float(v << 16); }
__device__ __forceinline__ float bfhi(uint32_t v) { return __uint_as_float(v & 0xffff0000u); }
template <int N> __device__ __forceinline__ void keep(float (&a)[N]) {
#pragma unroll
  for (int i = 0; i < N; i++) asm volatile("" : "+f"(a[i])::"memory");
}

__global__ void __cluster_dims__(2, 1, 1) __launch_bounds__(384, 1) fused_kernel(const __grid_constant__ Params prm) {
  extern __shared__ __align__(1024) uint8_t smem[];
  const int warp = __shfl_sync(0xffffffffu, threadIdx.x >> 5, 0);
  const uint32_t sb0 = (uint32_t)__cvta_generic_to_shared(smem);
  const int j = blockIdx.x & 7, m = blockIdx.x >> 3, rank = j & 1;
  auto smem_base = [&]() { return __shfl_sync(0xffffffffu, sb0 + (threadIdx.x & 31), 0); };

  if (threadIdx.x == 320) asm volatile("prefetch.tensormap [%0];" ::"l"(&prm.tx) : "memory");
  if (warp == 8 || warp == 9) {
    if (elect()) {
      if (warp == 8) {
#pragma unroll
        for (int i = 0; i < B_COUNT / 2; i++) mbar_init(sb0 + OFF_BAR + 8 * i, (i >= B_EMPTY && i < B_X) ? 2 : 1);
#pragma unroll
        for (int i = NST; i < NST + 2; i++) { mbar_arrive(sb0 + OFF_BAR + 8 * (B_FULL + i)); mbar_arrive(sb0 + OFF_BAR + 8 * (B_EMPTY + i)); mbar_arrive(sb0 + OFF_BAR + 8 * (B_EMPTY + i)); }
        __threadfence_block();
      } else {
#pragma unroll
        for (int i = B_COUNT / 2; i < B_COUNT; i++) mbar_init(sb0 + OFF_BAR + 8 * i, (i >= B_SFULL && i < B_SFULL + 2) ? 4 : i == B_RING ? 2 : 1);
        if (sb0 & 1023) __trap();
      }
      asm volatile("fence.mbarrier_init.release.cluster;" ::: "memory");
    }
    __syncwarp();
  }
  asm volatile("barrier.cluster.arrive.relaxed.aligned;\nbarrier.cluster.wait.aligned;" ::: "memory");

  if (warp == 0) {
    const uint32_t xb = sb0 + OFF_BAR;
    const bool e = elect();
    if (e) { mbar_expect(xb + 8 * B_X8, 16384); tma2d_mc(sb0 + rank * 8192, &prm.tx, xb + 8 * B_X8, 512, m * 128 + rank * 64); }
#pragma unroll
    for (int i = 0; i < 8; i++) {
      const int w = i >> 2, kb = (i & 3) * 2 + rank;
      if (e) { mbar_expect(xb + 8 * (B_X + i), 16384); tma2d_mc(sb0 + OFF_H + w * 65536 + kb * 8192, &prm.tx, xb + 8 * (B_X + i), kb * 64, m * 128 + w * 64); }
    }
    __syncwarp();
  }

  if (warp >= 8) {
    asm volatile("setmaxnreg.dec.sync.aligned.u32 24;");
    if (warp == 8) {
      const uint32_t sb = smem_base(), bars = sb + OFF_BAR;
      bool e;
      int s = 0, nst = NST; uint32_t ph = 1;
      uint32_t dst, fb;
      auto acquire = [&](uint32_t bytes) {
        mbar_wait(bars + 8 * (B_EMPTY + s), ph);
        fb = bars + 8 * (B_FULL + s); dst = sb + s * SLOT;
        e = elect();
        if (e) mbar_expect(fb, bytes);
        if (++s == nst) { s = 0; ph ^= 1; }
      };
      auto box = [&](const CUtensorMap* t, uint32_t o, int a, int b) { if (e) tma2d(dst + o, t, fb, a, b); };
      const int lane = threadIdx.x & 31;
      const char* pf = lane < 8 ? (const char*)(lane & 4 ? prm.wu : prm.wg) + ((size_t)(m * 4 + (lane & 3)) * kF + j * 576) * 2
                     : lane < 12 ? (const char*)prm.wd + (size_t)j * 576 * 1152 + (m * 324 + (lane & 3)) * 128
                                 : (const char*)(lane & 1 ? prm.cim : prm.cre) + (size_t)blockIdx.x * 5184;
      int pk = 0, pleft = 81;
      auto prefetch = [&]() {
        if (pleft > 0) {
          if (lane < 14) l2_prefetch_line(pf);
          pf += lane < 8 ? (pk == 8 ? 128 - 8 * 64 * kF * 2 : 64 * kF * 2) : lane < 12 ? 512 : 64;
          pk = pk == 8 ? 0 : pk + 1;
          pleft--;
        }
      };
      mbar_wait(bars + 8 * B_X8, 0);
      e = elect();
#pragma unroll 1
      for (int kb = 0; kb < 8; kb++) {
        fb = bars + 8 * (B_BU + (kb >> 2));
        if (e) { if ((kb & 3) == 0) mbar_expect(fb, 4 * 9216); tma2d(sb + OFF_BU0 + kb * 9216, &prm.tBre, fb, kb * 64, j * 72); }
      }
      bar_sync(NB_XDONE, 160);
      fb = bars + 8 * (B_BU + 2);
      if (e) { mbar_expect(fb, 5 * 9216); tma2d(sb + OFF_BU1, &prm.tBre, fb, 512, j * 72); }
#pragma unroll 1
      for (int kb = 0; kb < 4; kb++) if (e) tma2d(sb + OFF_BU1 + (kb + 1) * 9216, &prm.tBim, fb, kb * 64, j * 72);
      for (int i = 0; i < PFD / 2; i++) prefetch();
      bar_sync(NB_XDONE + 1, 160);
      fb = bars + 8 * (B_BU + 3);
      if (e) mbar_expect(fb, 5 * 9216);
#pragma unroll 1
      for (int kb = 4; kb < 9; kb++) if (e) tma2d(sb + OFF_BU2 + (kb - 4) * 9216, &prm.tBim, fb, kb * 64, j * 72);
      for (int i = PFD / 2; i < PFD; i++) prefetch();
      mbar_wait(bars + 8 * B_RING, 0);
      for (int c = 0; c < 9; c++) {
        const int col = j * 576 + c * 64;
#pragma unroll 1
        for (int kb = 0; kb < 9; kb++) {
          if (kb == 7 && c == 0) nst = 8;
          if (kb == 4 && c == 3) nst = 7;
          if (kb == 2 && c == 4) nst = 6;
          acquire(16384); box(&prm.tWg, 0, col, kb * 64); box(&prm.tWu, 8192, col, kb * 64); prefetch();
        }
      }
      auto half_tile = [&](int n0) {
#pragma unroll 1
        for (int kp = 0; kp < 4; kp++) { acquire(16384); box(&prm.tWd, 0, n0, j * 576 + kp * 128); box(&prm.tWd, 8192, n0, j * 576 + kp * 128 + 64); }
        nst = NST + 1;
        acquire(8192 + 2048); box(&prm.tWd, 0, n0, j * 576 + 512); box(&prm.tCre8, 8192, j * 72 + 64, n0); box(&prm.tCim8, 9216, j * 72 + 64, n0);
        acquire(16384); box(&prm.tCre, 0, j * 72, n0); box(&prm.tCim, 8192, j * 72, n0);
      };
      if (rank) half_tile(512);
#pragma unroll 1
      for (int t = 0; t < 4 - rank; t++) {
        const int n0 = ((rank ^ t ^ 1) & 1) * 256 + (((t >> 1) ^ (j >> 1)) & 1) * 128;
#pragma unroll 1
        for (int kb = 0; kb < 9; kb++) {
          if (kb == 4) nst = NST + 1;
          if (kb == 3 && t == 0 && rank) mbar_wait(bars + 8 * B_HFREE, 0);
          acquire(16384); box(&prm.tWd, 0, n0, j * 576 + kb * 64); box(&prm.tWd, 8192, n0 + 64, j * 576 + kb * 64);
        }
        if (t == 0) mbar_wait(bars + 8 * B_HFREE, 0);
        acquire(16384); box(&prm.tCre, 0, j * 72, n0); box(&prm.tCre, 8192, j * 72, n0 + 64);
        acquire(16384); box(&prm.tCim, 0, j * 72, n0); box(&prm.tCim, 8192, j * 72, n0 + 64);
        acquire(4096);
        box(&prm.tCre8, 0, j * 72 + 64, n0); box(&prm.tCre8, 1024, j * 72 + 64, n0 + 64);
        box(&prm.tCim8, 2048, j * 72 + 64, n0); box(&prm.tCim8, 3072, j * 72 + 64, n0 + 64);
      }
      if (!rank) half_tile(512);
      else {
#pragma unroll 1
        for (int hh = 0; hh < 2; hh++) half_tile(256 + (((j >> 1) ^ 1) & 1) * 128 + hh * 64);
      }
    } else {
      const uint32_t sb = smem_base(), bars = sb + OFF_BAR;
      const int p = min((int)threadIdx.x - 288, 71);
      if (threadIdx.x < 288 + 10) asm volatile("prefetch.tensormap [%0];" ::"l"(&prm.tBre + (threadIdx.x - 288)) : "memory");
      if (warp == 10) {
        const int l = threadIdx.x & 31;
        const char* q = (const char*)(l & 1 ? prm.bim : prm.bre) + (size_t)blockIdx.x * 5184;
        mbar_wait(bars + 8 * B_X8, 0);
#pragma unroll
        for (int i = 0; i < 3; i++) if (i * 16 + (l >> 1) < 42) l2_prefetch_line(q + min((i * 16 + (l >> 1)) * 128, 5183));
      }
      const unsigned epoch = *(volatile unsigned*)&g_epoch[blockIdx.x];
      {
        const int pg = j * 72 + p;
        const float lr = __bfloat162float(prm.lre[pg]), li = __bfloat162float(prm.lim[pg]);
        const float dt = rbf(expf(__bfloat162float(prm.ldt[pg])));
        const float ea = expf(dt * lr);
        float sn, cs;
        sincosf(dt * li, &sn, &cs);
        const float ar = ea * cs, ai = ea * sn;
        float br = ar, bi = ai;
#pragma unroll
        for (int k = 0; k < 6; k++) { const float t = br * br - bi * bi; bi = 2.f * br * bi; br = t; }
        const float nr = ar - 1.f, den = 4.f / (lr * lr + li * li);
        sts64f(sb + OFF_CONST + p * 8, ar, ai);
        sts64f(sb + OFF_CONST + 576 + p * 8, br, bi);
        sts64f(sb + OFF_CONST + 1152 + p * 8, (nr * lr + ai * li) * den, (ai * lr - nr * li) * den);
      }
      bar_sync(NB_DUMP, 352);
      {
        const int lane = threadIdx.x & 31;
        const int half = warp == 11 ? (lane >> 2) & 1 : warp - 9;
        const uint32_t cu = sb + OFF_CONST + (warp == 11 ? 32 + (lane & 3) : lane) * 16;
        uint32_t a0 = sb + OFF_DUMP + half * HS_BYTES + (warp == 11 ? 16 : lane >> 2) * HS_LBO + (lane & 3) * 4;
        asm volatile("" : "+r"(a0));
        const uint32_t di = warp == 11 ? HS_LBO : 8 * HS_LBO;
        float a[4], h[4] = {0.f, 0.f, 0.f, 0.f};
        auto ld4 = [&](uint32_t ad, float (&v)[4]) { asm volatile("ld.shared.v4.f32 {%0,%1,%2,%3}, [%4];" : "=f"(v[0]), "=f"(v[1]), "=f"(v[2]), "=f"(v[3]) : "r"(ad) : "memory"); };
        auto cfma = [&](const float (&c)[4], float r0, float i0, float r1, float i1) {
          const float n0 = fmaf(c[0], h[0], fmaf(-c[1], h[1], r0)), n1 = fmaf(c[2], h[2], fmaf(-c[3], h[3], r1));
          h[1] = fmaf(c[0], h[1], fmaf(c[1], h[0], i0)); h[3] = fmaf(c[2], h[3], fmaf(c[3], h[2], i1));
          h[0] = n0; h[2] = n1;
        };
        ld4(cu, a);
#pragma unroll 1
        for (uint32_t ad = a0; ad != a0 + 1024; ad += 64) {
          uint32_t wr[4], wi[4];
#pragma unroll
          for (int k = 0; k < 4; k++) { wr[k] = lds32(ad + k * 16); wi[k] = lds32(ad + di + k * 16); }
#pragma unroll
          for (int k = 0; k < 4; k++) cfma(a, bflo(wr[k]), bflo(wi[k]), bfhi(wr[k]), bfhi(wi[k]));
        }
        if (half == 0) sts128(cu + 1728, __float_as_uint(h[0]), __float_as_uint(h[1]), __float_as_uint(h[2]), __float_as_uint(h[3]));
        bar_sync(NB_SCAN, 96);
        if (half == 1 && m < 15) {
          float b[4], s1[4] = {h[0], h[1], h[2], h[3]};
          ld4(cu + 576, b); ld4(cu + 1728, h);
          cfma(b, s1[0], s1[1], s1[2], s1[3]);
          uint2* gp = &g_S[epoch & 1][m][j][(cu - sb - OFF_CONST) >> 3];
          asm volatile("st.relaxed.gpu.global.v2.b64 [%0], {%1,%2};" ::"l"(gp), "l"(~(((uint64_t)__float_as_uint(h[1]) << 32) | __float_as_uint(h[0]))),
                       "l"(~(((uint64_t)__float_as_uint(h[3]) << 32) | __float_as_uint(h[2]))) : "memory");
        }
        __syncwarp();
        g_S[(epoch & 1) ^ 1][m][j][p] = make_uint2(0u, 0u);
        {
          const float2 b = lds64f(sb + OFF_CONST + 576 + p * 8);
          const float br = b.x * b.x - b.y * b.y, bi = 2.f * b.x * b.y;
          float hr = 0.f, hi = 0.f;
          const uint2* sp = &g_S[epoch & 1][0][j][p];
#pragma unroll 1
          for (int left = m; left > 0; left -= 3, sp += 3 * 768) {
            uint32_t v[3][2];
            int spins = 0;
            uint32_t ok;
            do {
#pragma unroll
              for (int k = 0; k < 3; k++) {
                v[k][0] = v[k][1] = 0xffffffffu;
                if (k < left) asm volatile("ld.relaxed.gpu.global.v2.b32 {%0,%1}, [%2];" : "=r"(v[k][0]), "=r"(v[k][1]) : "l"(sp + k * 768) : "memory");
              }
              ok = min(min(min(v[0][0], v[0][1]), min(v[1][0], v[1][1])), min(v[2][0], v[2][1]));
              if (++spins > (1 << 22)) __trap();
            } while (ok == 0u);
#pragma unroll
            for (int k = 0; k < 3; k++)
              if (k < left) { const float nr = fmaf(br, hr, fmaf(-bi, hi, __uint_as_float(~v[k][0]))); hi = fmaf(br, hi, fmaf(bi, hr, __uint_as_float(~v[k][1]))); hr = nr; }
          }
          sts64f(sb + OFF_CONST + p * 8, hr, hi);
        }
        __syncwarp();
        bar_sync(NB_SCAN, 96);
        ld4(cu, h);
        uint32_t cr, ci, cn;
        {
          float b[4], s0[4];
          ld4(cu + 576, b); ld4(cu + 1728, s0);
          if (half == 1) cfma(b, s0[0], s0[1], s0[2], s0[3]);
          ld4(cu + 1152, b);
          cr = pack_bf16(b[0], b[2]); ci = pack_bf16(b[1], b[3]); cn = ci ^ 0x80008000u;
        }
        __syncwarp();
#pragma unroll 1
        for (uint32_t ad = a0; ad != a0 + 1024; ad += 32) {
          uint32_t wr[2], wi[2];
#pragma unroll
          for (int k = 0; k < 2; k++) { wr[k] = lds32(ad + k * 16); wi[k] = lds32(ad + di + k * 16); }
#pragma unroll
          for (int k = 0; k < 2; k++) {
            cfma(a, bflo(wr[k]), bflo(wi[k]), bfhi(wr[k]), bfhi(wi[k]));
            const uint32_t hr = pack_bf16(h[0], h[2]), hn = pack_bf16(-h[1], -h[3]);
            uint32_t o0, o1;
            asm("{.reg .b32 t; mul.rn.bf16x2 t, %2, %4; fma.rn.bf16x2 %0, %1, %3, t;}" : "=r"(o0) : "r"(hr), "r"(hn), "r"(cr), "r"(ci));
            asm("{.reg .b32 t; mul.rn.bf16x2 t, %1, %4; fma.rn.bf16x2 %0, %2, %3, t;}" : "=r"(o1) : "r"(hr), "r"(hn), "r"(cr), "r"(cn));
            asm volatile("st.shared.b32 [%0], %1;" ::"r"(ad + k * 16), "r"(o0) : "memory");
            asm volatile("st.shared.b32 [%0], %1;" ::"r"(ad + di + k * 16), "r"(o1) : "memory");
          }
        }
        asm volatile("fence.proxy.async.shared::cta;" ::: "memory");
      }
      bar_sync(NB_SCAN, 96);
      const bool lead = elect();
      if (warp == 9) {
        if (lead) {
#pragma unroll 1
          for (uint32_t o = 0; o < 2 * HS_BYTES; o += 4 * HS_LBO) {
            asm volatile("cp.async.bulk.global.shared::cta.bulk_group [%0], [%1], %2;" ::"l"(&g_hs[blockIdx.x][o]), "r"(sb + OFF_DUMP + o), "r"(4 * HS_LBO) : "memory");
            asm volatile("cp.async.bulk.commit_group;\ncp.async.bulk.wait_group.read 0;" ::: "memory");
          }
          mbar_arrive(bars + 8 * B_SCAN);
        }
        __syncwarp();
      }
      if (warp == 9) {
        if (lead) {
          __threadfence();
          asm volatile("red.release.gpu.global.add.u32 [%0], 1;" ::"l"(&g_ready[m]) : "memory");
          g_epoch[blockIdx.x] = epoch + 1u;
          asm volatile("cp.async.bulk.wait_group 0;" ::: "memory");
        }
        __syncwarp();
        bar_sync(NB_HFREE, 288);
        if (lead) {
          mbar_arrive(bars + 8 * B_HFREE);
          mbar_expect(bars + 8 * B_HSFULL, 2 * HS_BYTES);
          asm volatile("cp.async.bulk.shared::cluster.global.mbarrier::complete_tx::bytes [%0], [%1], %2, [%3];" ::"r"(sb + OFF_HS),
                       "l"(&g_hs[blockIdx.x][0]), "r"(2 * HS_BYTES), "r"(bars + 8 * B_HSFULL) : "memory");
          for (int w = 0; w < 2; w++) mbar_arrive_cta(bars + 8 * (B_RFREE + w), rank ^ 1);
        }
        __syncwarp();
      } else {
        const int w = warp - 10;
        {
          const unsigned target = 8u * (epoch + 1u);
          int spins = 0;
          unsigned v;
          do {
            if (spins) __nanosleep(500);
            asm volatile("ld.relaxed.gpu.global.u32 %0, [%1];" : "=r"(v) : "l"(&g_ready[m]) : "memory");
            if (++spins > (1 << 21)) __trap();
          } while ((int)(v - target) < 0);
          asm volatile("fence.acq_rel.gpu;" ::: "memory");
          asm volatile("fence.proxy.async.global;" ::: "memory");
        }
        const uint32_t stg = sb + OFF_STG + w * 32768;
        const int nu = 5 + rank;
#pragma unroll 1
        for (int u = 0; u < nu; u++) {
          const int t = u - rank;
          if (t == 0 || t == 2) {
            if (elect()) mbar_expect(bars + 8 * (B_RFULL + w), 16384);
            mbar_wait(bars + 8 * (B_SFULL + w), u & 1);
            mbar_wait(bars + 8 * (B_RFREE + w), t >> 1);
            if (elect())
              asm volatile("{.reg .b32 ra, rb; mapa.shared::cluster.u32 ra, %0, %3; mapa.shared::cluster.u32 rb, %2, %3;\n"
                           "cp.async.bulk.shared::cluster.shared::cta.mbarrier::complete_tx::bytes [ra], [%1], 16384, [rb];}" ::"r"(stg + 16384),
                           "r"(stg), "r"(bars + 8 * (B_RFULL + w)), "r"(rank ^ 1) : "memory");
            mbar_wait(bars + 8 * (B_RFULL + w), t >> 1);
            if (elect()) mbar_arrive_cta(bars + 8 * (B_SFREE + w), rank ^ 1);
          } else {
            mbar_wait(bars + 8 * (B_SFULL + w), u & 1);
            const bool d = u == (rank ? 0 : 4), hf = rank && u >= 4;
            const int n0 = d ? 512 : rank * 256 + (((min(t, 3) >> 1) ^ (j >> 1)) & 1) * 128 + (u == 5 ? 64 : 0);
            const uint32_t src = d && !rank ? sb + (2 + w) * SLOT : stg + (u == 5 ? 16384 : 0);
            if (elect()) {
#pragma unroll 1
              for (int b = 0; b < (d || hf ? 2 : 4); b++) {
                asm volatile("cp.reduce.async.bulk.tensor.4d.global.shared::cta.add.tile.bulk_group [%0, {%1,%2,%2,%3}], [%4];" ::"l"(&prm.tOut), "r"(n0 + b * 32), "r"(0),
                             "r"(m * 16 + w * 8), "r"(src + b * 8192) : "memory");
                asm volatile("cp.async.bulk.commit_group;" ::: "memory");
                if (u < nu - 1) asm volatile("cp.async.bulk.wait_group.read 0;" ::: "memory");
              }
              if (u < 3) {
                asm volatile("cp.async.bulk.wait_group.read 0;" ::: "memory");
                mbar_arrive(bars + 8 * (B_SFREE + w));
                if (t == 1) mbar_arrive_cta(bars + 8 * (B_RFREE + w), rank ^ 1);
              }
              if (u == nu - 1) asm volatile("cp.async.bulk.wait_group.read 0;" ::: "memory");
            }
          }
          __syncwarp();
        }
      }
    }
  } else {
    asm volatile("setmaxnreg.inc.sync.aligned.u32 240;");
    const uint32_t sb = smem_base(), bars = sb + OFF_BAR;
    const int wg = warp >> 2, w4 = warp & 3;
    const int lane = threadIdx.x & 31, g = lane >> 2, q = lane & 3;
    const uint32_t hw = sb + OFF_H + wg * 65536;

    int s = 0, nst = NST; uint32_t ph = 0;
    auto release = [&](int st) { if (w4 == 0) { if (elect()) mbar_arrive(bars + 8 * (B_EMPTY + st)); } };
    const uint32_t dring = (sb & 0x3FFFF) >> 4;
    uint32_t dlo; int prev = 0;
    auto stage_begin = [&]() { mbar_wait(bars + 8 * (B_FULL + s), ph); dlo = dring + s * (SLOT >> 4); wg_fence(); };
    auto advance = [&]() { if (++s == nst) { s = 0; ph ^= 1; } };
    auto stage_end = [&](bool rel) {
      wg_commit();
      if (rel) { wg_wait<1>(); release(prev); }
      prev = s;
      advance();
    };

    uint32_t xa[144];
    uint32_t xr[18], dk[9];
    uint32_t rh[2], cc[2];
#pragma unroll
    for (int i = 0; i < 9; i++) dk[i] = __ldg((const uint32_t*)(prm.dskip + j * 72 + i * 8 + q * 2));
    {
      const int r = w4 * 16 + (lane & 7) + ((lane >> 3) & 1) * 8;
      const uint32_t ro = r * 128, cx = ((lane >> 4) ^ (lane & 7)) << 4;
      float s1[2][4] = {};
      auto load = [&](int kb, uint32_t base) {
#pragma unroll
        for (int kk = 0; kk < 4; kk++) {
          const int i = (kb * 4 + kk) * 4;
          asm volatile("ldmatrix.sync.aligned.m8n8.x4.shared.b16 {%0,%1,%2,%3}, [%4];"
                       : "=r"(xa[i]), "=r"(xa[i + 1]), "=r"(xa[i + 2]), "=r"(xa[i + 3]) : "r"(base + ro + (cx ^ (kk << 5))) : "memory");
        }
      };
      const uint32_t b0 = (g & 1) ? 0u : 0x3f803f80u, b1 = b0 ^ 0x3f803f80u;
      auto sums = [&](int kb) {
#pragma unroll
        for (int kk = 0; kk < 4; kk++) {
          const int i = (kb * 4 + kk) * 4;
          uint32_t a[4];
#pragma unroll
          for (int e = 0; e < 2; e++) {
            asm("mul.rn.bf16x2 %0, %1, %1;" : "=r"(a[e]) : "r"(xa[i + e]));
            asm("add.rn.bf16x2 %0, %1, %2;" : "=r"(a[2 + e]) : "r"(xa[i + e]), "r"(xa[i + 2 + e]));
            asm("fma.rn.bf16x2 %0, %1, %1, %0;" : "+r"(a[e]) : "r"(xa[i + 2 + e]));
          }
          mma16816(s1[kk & 1], a[0], a[1], a[2], a[3], b0, b1);
        }
      };
#pragma unroll
      for (int i = 0; i < 9; i++) {
        const int c8 = j * 9 + i, kb = c8 >> 3;
        xr[2 * i] = (kb < 8 ? hw + kb * 8192 : sb + wg * 8192) + (w4 * 16 + g) * 128 + (((c8 & 7) ^ g) << 4) + q * 4;
        asm volatile("" : "+r"(xr[2 * i]));
      }
      mbar_wait(bars + 8 * B_X8, 0);
      load(8, sb + wg * 8192);
      auto pin = [&]() { asm volatile("{.reg .pred p; .reg .u32 c, z; mov.u32 c, %clock; mov.u32 z, %ntid.y; setp.eq.u32 p, z, 0; @p st.shared.u32 [c], c;}" ::: "memory"); };
#pragma unroll
      for (int kp = 0; kp < 4; kp++) {
        mbar_wait(bars + 8 * (B_X + wg * 4 + kp), 0);
        load(2 * kp, hw + 2 * kp * 8192);
        load(2 * kp + 1, hw + (2 * kp + 1) * 8192);
        if (kp == 3) {
#pragma unroll
          for (int i = 0; i < 9; i++) { xr[2 * i + 1] = lds32(xr[2 * i] + 1024); xr[2 * i] = lds32(xr[2 * i]); }
        }
        if (kp == 0) sums(8); else { sums(2 * kp - 2); sums(2 * kp - 1); }
      }
      asm volatile("fence.proxy.async.shared::cta;" ::: "memory");
      bar_arrive(NB_XDONE + wg, 160);
      if (wg == 1) bar_arrive(NB_STATS, 256);
      pin();
      sums(6);
      sums(7);
      pin();
#pragma unroll
      for (int e = 0; e < 2; e++) {
        const float mu = (s1[0][2 * e + 1] + s1[1][2 * e + 1]) * (1.f / kD);
        const float var = fmaxf(fmaf(-mu, mu, (s1[0][2 * e] + s1[1][2 * e]) * (1.f / kD)), 0.f);
        float sd, r;
        asm("sqrt.approx.f32 %0, %1;" : "=f"(sd) : "f"(rbf(rbf(var) + 1e-5f)));
        asm("rcp.approx.ftz.f32 %0, %1;" : "=f"(r) : "f"(rbf(sd)));
        r = rbf(0.5f * r);
        rh[e] = pack_bf16(r, r); cc[e] = pack_bf16(-mu * r, -mu * r);
      }
    }

    auto normalise = [&](int kb) {
#pragma unroll
      for (int i = 0; i < 16; i++) asm("fma.rn.bf16x2 %0, %0, %1, %2;" : "+r"(xa[16 * kb + (i >> 3) + 2 * (i & 7)]) : "r"(rh[i >> 3]), "r"(cc[i >> 3]));
    };
    {
      float ab[36];
      float* op = prm.out + (size_t)(m * 128 + wg * 64 + w4 * 16 + g) * kD + j * 72 + q * 2;
      auto residual = [&](int i) {
        asm volatile("add.rn.bf16x2 %0, %0, %0;" : "+r"(dk[i]));
#pragma unroll
        for (int e = 0; e < 2; e++) {
          uint32_t t;
          asm("fma.rn.bf16x2 %0, %1, %2, %3;" : "=r"(t) : "r"(xr[2 * i + e]), "r"(rh[e]), "r"(cc[e]));
          asm("fma.rn.bf16x2 %0, %0, %1, %2;" : "+r"(t) : "r"(dk[i]), "r"(xr[2 * i + e]));
          *(float2*)(op + e * 8 * kD + i * 8) = make_float2(bflo(t), bfhi(t));
        }
      };
      const uint32_t da = sb + OFF_DUMP + wg * HS_BYTES + (w4 * 16 + g) * 16 + q * 4;
      auto dump = [&](int im) {
#pragma unroll
        for (int i = 0; i < 18; i++)
          asm volatile("st.shared.b32 [%0], %1;" ::"r"(da + (i < 16 ? 8 * im + (i >> 1) : 16 + im) * HS_LBO + (i & 1) * 128), "r"(pack_bf16(ab[2 * i], ab[2 * i + 1])) : "memory");
      };
      auto bu = [&](int kb, uint32_t off) {
        wg_fence();
#pragma unroll
        for (int kk = 0; kk < 4; kk++) { const int i = (kb * 4 + kk) * 4; wgmma_n72_rs_tb0(ab, xa[i], xa[i + 1], xa[i + 2], xa[i + 3], desc((dring + (off >> 4) + kk * 2) | DLO_K, DHI_SW128), (kb | kk) != 0); }
        wg_commit();
      };
      normalise(0);
      if (wg == 0) {
#pragma unroll
        for (int kb = 1; kb < 9; kb++) normalise(kb);
        bar_sync(NB_STATS, 256);
      }
#pragma unroll
      for (int kb = 0; kb < 9; kb++) {
        if ((kb & 3) == 0) mbar_wait(bars + 8 * (B_BU + (kb >> 2)), 0);
        bu(kb, kb < 8 ? OFF_BU0 + kb * 9216 : OFF_BU1);
        if (kb < 8 && wg == 1) normalise(kb + 1);
      }
      wg_wait<0>();
      if (w4 == 0) { if (elect()) mbar_arrive(bars + 8 * B_RING); }
      keep(ab);
      dump(0);
#pragma unroll
      for (int kb = 0; kb < 9; kb++) {
        if (kb == 4) mbar_wait(bars + 8 * (B_BU + 3), 0);
        bu(kb, kb < 4 ? OFF_BU1 + (kb + 1) * 9216 : OFF_BU2 + (kb - 4) * 9216);
        residual(kb);
      }
      wg_wait<0>();
      keep(ab);
      dump(1);
      bar_arrive(NB_DUMP, 352);
    }

    float acc[64];
    {
      const uint32_t ha = sb + OFF_H + (threadIdx.x & 127) * 16, hblk = wg ? HBLK1 : HBLK0;
      auto glu = [&](int i) {
        return pack_bf16(fmaf(acc[32 + 2 * i], tanh_fast(acc[2 * i]), acc[32 + 2 * i]), fmaf(acc[33 + 2 * i], tanh_fast(acc[2 * i + 1]), acc[33 + 2 * i]));
      };
      for (int c = 0;; c++) {
        if (wg == 1) bar_sync(NB_SKEW, 256);
#pragma unroll
        for (int kb = 0; kb < 9; kb++) {
          if (kb == 7 && c == 0) nst = 8;
          if (kb == 4 && c == 3) nst = 7;
          if (kb == 2 && c == 4) nst = 6;
          stage_begin();
#pragma unroll
          for (int kk = 0; kk < 4; kk++) { const int i = (kb * 4 + kk) * 4; wgmma_n128_rs_tb1(acc, xa[i], xa[i + 1], xa[i + 2], xa[i + 3], desc((dlo + kk * 128) | DLO_MN, DHI_SW128), (kb | kk) != 0); }
          if (kb == SKEW - 1 && wg == 0) bar_arrive(NB_SKEW, 256);
          if (kb == 8 && c >= 3 && c <= 5) mbar_wait(bars + 8 * (c == 5 ? B_SCAN : B_EMPTY + 10 - c), c == 3);
          stage_end(kb > 0);
        }
        wg_wait<0>();
        release(prev);
        keep(acc);
        if (c == 8) break;
        const uint32_t hc = ha + ((hblk >> (4 * c)) & 15) * 8192;
#pragma unroll
        for (int i = 0; i < 4; i++) sts128(hc + i * 2048, glu(4 * i), glu(4 * i + 1), glu(4 * i + 2), glu(4 * i + 3));
      }
#pragma unroll
      for (int i = 0; i < 32; i++) lds128(ha + ((hblk >> (4 * (i >> 2))) & 15) * 8192 + (i & 3) * 2048, xa[4 * i], xa[4 * i + 1], xa[4 * i + 2], xa[4 * i + 3]);
#pragma unroll
      for (int i = 0; i < 16; i++) xa[128 + i] = glu(i);
      asm volatile("fence.proxy.async.shared::cta;" ::: "memory");
      bar_arrive(NB_HFREE, 288);
    }

    const uint32_t dhs = (((sb + OFF_HS + wg * HS_BYTES) & 0x3FFFF) >> 4) | DLO_HS;
    const int rp = (g >> 2) + 2 * (g & 3);
    const uint32_t so = w4 * 2048 + rp * 128 + (q & 1) * 8, sx = ((q >> 1) ^ rp) << 4;
    const uint32_t rcv = sb + OFF_STG + wg * 32768 + 16384 + w4 * 2048 + lane * 16;
    auto staged = [&]() {
      asm volatile("fence.proxy.async.shared::cta;" ::: "memory");
      __syncwarp();
      if (elect()) mbar_arrive(bars + 8 * (B_SFULL + wg));
    };
    auto half_tile = [&](const bool first, const int kind) {
      float a2[32];
      if (wg == 1) bar_sync(NB_SKEW, 256);
      const uint32_t ph0 = ph;
      uint32_t d4;
#pragma unroll
      for (int kp = 0; kp < 5; kp++) {
        if (kp == 4) nst = NST + 1;
        stage_begin();
#pragma unroll
        for (int kk = 0; kk < (kp < 4 ? 8 : 4); kk++) { const int i = (kp * 8 + kk) * 4; wgmma_n64_rs_tb1(a2, xa[i], xa[i + 1], xa[i + 2], xa[i + 3], desc((dlo + kk * 128) | DLO_MN, DHI_SW128), (kp | kk) != 0); }
        if (kp == 1 && wg == 0) bar_arrive(NB_SKEW, 256);
        d4 = dlo;
        stage_end(kp > 0);
        if (kp == 0 && !first) staged();
      }
      if (first) mbar_wait(bars + 8 * B_HSFULL, 0);
      stage_begin();
#pragma unroll
      for (int kk = 0; kk < 8; kk++) wgmma_n64_ss_tb0(a2, desc(dhs + kk * (2 * HS_LBO >> 4), DHI_NONE), desc((dlo + (kk >> 2) * 512 + (kk & 3) * 2) | DLO_K, DHI_SW128), 1);
      wgmma_n64_ss_tb0(a2, desc(dhs + 8 * (2 * HS_LBO >> 4), DHI_NONE), desc((d4 + 512) | ((1024 >> 4) << 16), DHI_NONE), 1);
      wg_commit();
      if (!first) {
        if (kind == 1) mbar_wait(bars + 8 * (B_EMPTY + 2 + wg), ph0);
        if (kind == 2) { mbar_wait(bars + 8 * (B_SFREE + wg), 1); mbar_wait(bars + 8 * (B_RFULL + wg), 1); }
      }
      wg_wait<0>();
      release(prev); release(s); advance();
      keep(a2);
      if (!first && kind >= 2) {
#pragma unroll
        for (int i = 0; i < 4; i++) {
          uint32_t v[4];
          lds128(rcv + (kind & 1) * 8192 + i * 512, v[0], v[1], v[2], v[3]);
#pragma unroll
          for (int e = 0; e < 4; e++) { a2[8 * i + 2 * e] += bflo(v[e]); a2[8 * i + 2 * e + 1] += bfhi(v[e]); }
        }
        __syncwarp();
      }
      const uint32_t stg = (!first && kind == 1 ? sb + (2 + wg) * SLOT : sb + OFF_STG + wg * 32768 + (kind == 3 ? 16384 : 0)) + so;
#pragma unroll
      for (int i = 0; i < 8; i++) {
        const uint32_t a = stg + (i >> 2) * 8192 + (sx ^ ((i & 3) << 5));
        sts64f(a, a2[4 * i], a2[4 * i + 1]);
        sts64f(a + 1024, a2[4 * i + 2], a2[4 * i + 3]);
      }
    };
    if (rank) half_tile(true, 0);
    for (int t = 0; t < 4 - rank; t++) {
      if (wg == 1) bar_sync(NB_SKEW, 256);
#pragma unroll
      for (int kb = 0; kb < 9; kb++) {
        if (kb == 4) nst = NST + 1;
        stage_begin();
#pragma unroll
        for (int kk = 0; kk < 4; kk++) { const int i = (kb * 4 + kk) * 4; wgmma_n128_rs_tb1(acc, xa[i], xa[i + 1], xa[i + 2], xa[i + 3], desc((dlo + kk * 128) | DLO_MN, DHI_SW128), (kb | kk) != 0); }
        if (kb == SKEW - 1 && wg == 0) bar_arrive(NB_SKEW, 256);
        stage_end(kb > 0);
        if (kb == 0 && t + rank > 0) staged();
      }
      if (t == 0) mbar_wait(bars + 8 * B_HSFULL, 0);
      stage_begin();
#pragma unroll
      for (int kk = 0; kk < 4; kk++) wgmma_n128_ss_tb0(acc, desc(dhs + kk * (2 * HS_LBO >> 4), DHI_NONE), desc((dlo + kk * 2) | DLO_K, DHI_SW128), 1);
      stage_end(true);
      stage_begin();
#pragma unroll
      for (int kk = 0; kk < 4; kk++) wgmma_n128_ss_tb0(acc, desc(dhs + (4 + kk) * (2 * HS_LBO >> 4), DHI_NONE), desc((dlo + kk * 2) | DLO_K, DHI_SW128), 1);
      const int s_im = s;
      advance();
      stage_begin();
      wgmma_n128_ss_tb0(acc, desc(dhs + 8 * (2 * HS_LBO >> 4), DHI_NONE), desc(dlo | ((2048 >> 4) << 16), DHI_NONE), 1);
      stage_end(true);
      if (t + rank > 0) mbar_wait(bars + 8 * (B_SFREE + wg), (t + rank - 1) & 1);
      if (t & 1) mbar_wait(bars + 8 * (B_RFULL + wg), t >> 1);
      wg_wait<0>();
      release(s_im); release(prev);
      keep(acc);
      if (t & 1) {
        const uint32_t stg = sb + OFF_STG + wg * 32768 + so;
#pragma unroll
        for (int hh = 0; hh < 2; hh++) {
#pragma unroll
          for (int i = 4 * hh; i < 4 * hh + 4; i++) {
            uint32_t v[4];
            lds128(rcv + hh * 8192 + (i & 3) * 512, v[0], v[1], v[2], v[3]);
#pragma unroll
            for (int e = 0; e < 4; e++) { acc[8 * i + 2 * e] += bflo(v[e]); acc[8 * i + 2 * e + 1] += bfhi(v[e]); }
          }
          __syncwarp();
#pragma unroll
          for (int i = 8 * hh; i < 8 * hh + 8; i++) {
            const uint32_t a = stg + (i >> 2) * 8192 + (sx ^ ((i & 3) << 5));
            sts64f(a, acc[4 * i], acc[4 * i + 1]);
            sts64f(a + 1024, acc[4 * i + 2], acc[4 * i + 3]);
          }
        }
      } else {
#pragma unroll
        for (int i = 0; i < 8; i++)
          sts128(rcv - 16384 + (i >> 2) * 8192 + (i & 3) * 512, pack_bf16(acc[8 * i], acc[8 * i + 1]), pack_bf16(acc[8 * i + 2], acc[8 * i + 3]),
                 pack_bf16(acc[8 * i + 4], acc[8 * i + 5]), pack_bf16(acc[8 * i + 6], acc[8 * i + 7]));
      }
    }
#pragma unroll 1
    for (int kind = 1 + rank; kind < 2 + 2 * rank; kind++) half_tile(false, kind);
    staged();
  }
}

typedef CUresult (*EncodeFn)(CUtensorMap*, CUtensorMapDataType, cuuint32_t, void*, const cuuint64_t*, const cuuint64_t*, const cuuint32_t*,
                             const cuuint32_t*, CUtensorMapInterleave, CUtensorMapSwizzle, CUtensorMapL2promotion, CUtensorMapFloatOOBfill);

void map2d(EncodeFn enc, CUtensorMap* tm, const void* p, uint64_t cols, uint64_t rows, uint32_t bc, uint32_t br, CUtensorMapSwizzle sw) {
  cuuint64_t gd[2] = {cols, rows}, gs[1] = {cols * 2};
  cuuint32_t bd[2] = {bc, br}, es[2] = {1, 1};
  enc(tm, CU_TENSOR_MAP_DATA_TYPE_BFLOAT16, 2, (void*)p, gd, gs, bd, es, CU_TENSOR_MAP_INTERLEAVE_NONE, sw,
      sw == CU_TENSOR_MAP_SWIZZLE_128B ? CU_TENSOR_MAP_L2_PROMOTION_L2_128B : CU_TENSOR_MAP_L2_PROMOTION_NONE, CU_TENSOR_MAP_FLOAT_OOB_FILL_NONE);
}

}

extern "C" void kernel_launch(void* const* d_in, const int* in_sizes, int n_in, void* d_out, int out_size) {
  (void)in_sizes; (void)n_in; (void)out_size;
  static EncodeFn enc = nullptr;
  if (!enc) {
    cudaDriverEntryPointQueryResult qr;
    cudaGetDriverEntryPoint("cuTensorMapEncodeTiled", (void**)&enc, cudaEnableDefault, &qr);
    cudaFuncSetAttribute(fused_kernel, cudaFuncAttributeMaxDynamicSharedMemorySize, SMEM_BYTES);
  }
  Params prm;
  const CUtensorMapSwizzle S128 = CU_TENSOR_MAP_SWIZZLE_128B;
  map2d(enc, &prm.tx, d_in[0], kD, kS, 64, 64, S128);
  map2d(enc, &prm.tBre, d_in[3], kD, 576, 64, 72, S128);
  map2d(enc, &prm.tBim, d_in[4], kD, 576, 64, 72, S128);
  map2d(enc, &prm.tCre, d_in[5], 576, kD, 64, 64, S128);
  map2d(enc, &prm.tCim, d_in[6], 576, kD, 64, 64, S128);
  map2d(enc, &prm.tCre8, d_in[5], 576, kD, 8, 64, CU_TENSOR_MAP_SWIZZLE_NONE);
  map2d(enc, &prm.tCim8, d_in[6], 576, kD, 8, 64, CU_TENSOR_MAP_SWIZZLE_NONE);
  map2d(enc, &prm.tWg, d_in[10], kF, kD, 64, 64, S128);
  map2d(enc, &prm.tWu, d_in[11], kF, kD, 64, 64, S128);
  map2d(enc, &prm.tWd, d_in[12], kD, kF, 64, 64, S128);
  {
    cuuint64_t gd[4] = {kD, 2, 4, kS / 8}, gs[3] = {4 * kD * 4, kD * 4, 8 * kD * 4};
    cuuint32_t bd[4] = {32, 2, 4, 8}, es[4] = {1, 1, 1, 1};
    enc(&prm.tOut, CU_TENSOR_MAP_DATA_TYPE_FLOAT32, 4, d_out, gd, gs, bd, es, CU_TENSOR_MAP_INTERLEAVE_NONE, S128, CU_TENSOR_MAP_L2_PROMOTION_NONE,
        CU_TENSOR_MAP_FLOAT_OOB_FILL_NONE);
  }
  prm.x = (const __nv_bfloat16*)d_in[0];
  prm.lre = (const __nv_bfloat16*)d_in[1];
  prm.lim = (const __nv_bfloat16*)d_in[2];
  prm.bre = (const __nv_bfloat16*)d_in[3];
  prm.bim = (const __nv_bfloat16*)d_in[4];
  prm.cre = (const __nv_bfloat16*)d_in[5];
  prm.cim = (const __nv_bfloat16*)d_in[6];
  prm.wg = (const __nv_bfloat16*)d_in[10];
  prm.wu = (const __nv_bfloat16*)d_in[11];
  prm.wd = (const __nv_bfloat16*)d_in[12];
  prm.ldt = (const __nv_bfloat16*)d_in[7];
  prm.dskip = (const __nv_bfloat16*)d_in[8];
  prm.out = (float*)d_out;

  fused_kernel<<<128, 384, SMEM_BYTES, cudaStreamPerThread>>>(prm);
}
```

```cpp
#include <cuda_runtime.h>
#include <cuda.h>
#include <cuda_bf16.h>
#include <stdint.h>

namespace {

constexpr int kS = 2048, kD = 576, kF = 4608;
constexpr int SKEW = 4;
constexpr int PFD = 18;
constexpr int NST = 6;
constexpr uint32_t SLOT = 16384;
constexpr uint32_t OFF_H = NST * SLOT;
constexpr uint32_t HS_LBO = 1040;
constexpr uint32_t HS_BYTES = 18 * HS_LBO;
constexpr uint32_t OFF_DUMP = OFF_H + 65536 - HS_BYTES;
constexpr uint32_t OFF_STG = OFF_H + SLOT;
constexpr uint32_t OFF_HS = OFF_STG + 65536;
constexpr uint32_t OFF_BAR = OFF_H + 131072;
constexpr uint32_t OFF_CONST = OFF_BAR + 384;
constexpr uint32_t SMEM_BYTES = OFF_CONST + 4 * 576 + 384;
static_assert(SMEM_BYTES <= 232448 && OFF_HS + 2 * HS_BYTES <= OFF_BAR, "smem");

enum { B_FULL = 0, B_EMPTY = NST + 2, B_X = 2 * NST + 4, B_X8 = B_X + 8, B_BU  , B_RING = B_BU + 4, B_SCAN, B_HFREE, B_HSFULL, B_SFULL,
       B_SFREE = B_SFULL + 2, B_RFULL = B_SFREE + 2, B_RFREE = B_RFULL + 2, B_COUNT = B_RFREE + 2 };
static_assert(B_COUNT * 8 <= 384, "barriers");
enum { NB_SKEW = 1, NB_XDONE = 2  , NB_SCAN = 4, NB_DUMP = 5, NB_HFREE = 6, NB_STATS = 7 };
constexpr uint32_t HBLK0 = 0x76502CB4u, HBLK1 = 0x89A13DEFu;
constexpr uint32_t OFF_BU0 = SLOT, OFF_BU1 = OFF_H, OFF_BU2 = OFF_H + 65536 + 19456;
static_assert(OFF_BU1 + 5 * 9216 <= OFF_DUMP && OFF_BU2 >= OFF_DUMP + 2 * HS_BYTES && OFF_BU2 + 5 * 9216 <= OFF_BAR, "Bu tiles");

struct __align__(64) Params {
  CUtensorMap tx, tBre, tBim, tWg, tWu, tWd, tCre, tCim, tCre8, tCim8, tOut;
  const __nv_bfloat16 *lre, *lim, *bre, *bim, *cre, *cim, *ldt, *dskip, *wg, *wu, *wd;
  float* out;
};

__device__ unsigned g_epoch[128];
__device__ unsigned g_ready[16];
__device__ __align__(256) uint2 g_S[2][16][8][96];
__device__ __align__(128) uint8_t g_hs[128][2 * HS_BYTES];

__device__ __forceinline__ void wgmma_n72_rs_tb0(float (&d)[36], uint32_t a0, uint32_t a1, uint32_t a2, uint32_t a3, uint64_t db, int scale_d) {
  asm volatile("{\n.reg .pred p;\nsetp.ne.b32 p, %41, 0;\n"
    "wgmma.mma_async.sync.aligned.m64n72k16.f32.bf16.bf16 {"
    "%0, %1, %2, %3, %4, %5, %6, %7, %8, %9, %10, %11, %12, %13, %14, %15, "
    "%16, %17, %18, %19, %20, %21, %22, %23, %24, %25, %26, %27, %28, %29, %30, %31, "
    "%32, %33, %34, %35"
    "}, {%36, %37, %38, %39}, %40, p, 1, 1, 0;\n}\n"
    : "+f"(d[0]), "+f"(d[1]), "+f"(d[2]), "+f"(d[3]), "+f"(d[4]), "+f"(d[5]), "+f"(d[6]), "+f"(d[7]),
      "+f"(d[8]), "+f"(d[9]), "+f"(d[10]), "+f"(d[11]), "+f"(d[12]), "+f"(d[13]), "+f"(d[14]), "+f"(d[15]),
      "+f"(d[16]), "+f"(d[17]), "+f"(d[18]), "+f"(d[19]), "+f"(d[20]), "+f"(d[21]), "+f"(d[22]), "+f"(d[23]),
      "+f"(d[24]), "+f"(d[25]), "+f"(d[26]), "+f"(d[27]), "+f"(d[28]), "+f"(d[29]), "+f"(d[30]), "+f"(d[31]),
      "+f"(d[32]), "+f"(d[33]), "+f"(d[34]), "+f"(d[35])
    : "r"(a0), "r"(a1), "r"(a2), "r"(a3), "l"(db), "r"(scale_d));
}
__device__ __forceinline__ void wgmma_n128_rs_tb1(float (&d)[64], uint32_t a0, uint32_t a1, uint32_t a2, uint32_t a3, uint64_t db, int scale_d) {
  asm volatile("{\n.reg .pred p;\nsetp.ne.b32 p, %69, 0;\n"
    "wgmma.mma_async.sync.aligned.m64n128k16.f32.bf16.bf16 {"
    "%0, %1, %2, %3, %4, %5, %6, %7, %8, %9, %10, %11, %12, %13, %14, %15, "
    "%16, %17, %18, %19, %20, %21, %22, %23, %24, %25, %26, %27, %28, %29, %30, %31, "
    "%32, %33, %34, %35, %36, %37, %38, %39, %40, %41, %42, %43, %44, %45, %46, %47, "
    "%48, %49, %50, %51, %52, %53, %54, %55, %56, %57, %58, %59, %60, %61, %62, %63"
    "}, {%64, %65, %66, %67}, %68, p, 1, 1, 1;\n}\n"
    : "+f"(d[0]), "+f"(d[1]), "+f"(d[2]), "+f"(d[3]), "+f"(d[4]), "+f"(d[5]), "+f"(d[6]), "+f"(d[7]),
      "+f"(d[8]), "+f"(d[9]), "+f"(d[10]), "+f"(d[11]), "+f"(d[12]), "+f"(d[13]), "+f"(d[14]), "+f"(d[15]),
      "+f"(d[16]), "+f"(d[17]), "+f"(d[18]), "+f"(d[19]), "+f"(d[20]), "+f"(d[21]), "+f"(d[22]), "+f"(d[23]),
      "+f"(d[24]), "+f"(d[25]), "+f"(d[26]), "+f"(d[27]), "+f"(d[28]), "+f"(d[29]), "+f"(d[30]), "+f"(d[31]),
      "+f"(d[32]), "+f"(d[33]), "+f"(d[34]), "+f"(d[35]), "+f"(d[36]), "+f"(d[37]), "+f"(d[38]), "+f"(d[39]),
      "+f"(d[40]), "+f"(d[41]), "+f"(d[42]), "+f"(d[43]), "+f"(d[44]), "+f"(d[45]), "+f"(d[46]), "+f"(d[47]),
      "+f"(d[48]), "+f"(d[49]), "+f"(d[50]), "+f"(d[51]), "+f"(d[52]), "+f"(d[53]), "+f"(d[54]), "+f"(d[55]),
      "+f"(d[56]), "+f"(d[57]), "+f"(d[58]), "+f"(d[59]), "+f"(d[60]), "+f"(d[61]), "+f"(d[62]), "+f"(d[63])
    : "r"(a0), "r"(a1), "r"(a2), "r"(a3), "l"(db), "r"(scale_d));
}
__device__ __forceinline__ void wgmma_n128_ss_tb0(float (&d)[64], uint64_t da, uint64_t db, int scale_d) {
  asm volatile("{\n.reg .pred p;\nsetp.ne.b32 p, %66, 0;\n"
    "wgmma.mma_async.sync.aligned.m64n128k16.f32.bf16.bf16 {"
    "%0, %1, %2, %3, %4, %5, %6, %7, %8, %9, %10, %11, %12, %13, %14, %15, "
    "%16, %17, %18, %19, %20, %21, %22, %23, %24, %25, %26, %27, %28, %29, %30, %31, "
    "%32, %33, %34, %35, %36, %37, %38, %39, %40, %41, %42, %43, %44, %45, %46, %47, "
    "%48, %49, %50, %51, %52, %53, %54, %55, %56, %57, %58, %59, %60, %61, %62, %63"
    "}, %64, %65, p, 1, 1, 0, 0;\n}\n"
    : "+f"(d[0]), "+f"(d[1]), "+f"(d[2]), "+f"(d[3]), "+f"(d[4]), "+f"(d[5]), "+f"(d[6]), "+f"(d[7]),
      "+f"(d[8]), "+f"(d[9]), "+f"(d[10]), "+f"(d[11]), "+f"(d[12]), "+f"(d[13]), "+f"(d[14]), "+f"(d[15]),
      "+f"(d[16]), "+f"(d[17]), "+f"(d[18]), "+f"(d[19]), "+f"(d[20]), "+f"(d[21]), "+f"(d[22]), "+f"(d[23]),
      "+f"(d[24]), "+f"(d[25]), "+f"(d[26]), "+f"(d[27]), "+f"(d[28]), "+f"(d[29]), "+f"(d[30]), "+f"(d[31]),
      "+f"(d[32]), "+f"(d[33]), "+f"(d[34]), "+f"(d[35]), "+f"(d[36]), "+f"(d[37]), "+f"(d[38]), "+f"(d[39]),
      "+f"(d[40]), "+f"(d[41]), "+f"(d[42]), "+f"(d[43]), "+f"(d[44]), "+f"(d[45]), "+f"(d[46]), "+f"(d[47]),
      "+f"(d[48]), "+f"(d[49]), "+f"(d[50]), "+f"(d[51]), "+f"(d[52]), "+f"(d[53]), "+f"(d[54]), "+f"(d[55]),
      "+f"(d[56]), "+f"(d[57]), "+f"(d[58]), "+f"(d[59]), "+f"(d[60]), "+f"(d[61]), "+f"(d[62]), "+f"(d[63])
    : "l"(da), "l"(db), "r"(scale_d));
}
__device__ __forceinline__ void wgmma_n64_rs_tb1(float (&d)[32], uint32_t a0, uint32_t a1, uint32_t a2, uint32_t a3, uint64_t db, int scale_d) {
  asm volatile("{\n.reg .pred p;\nsetp.ne.b32 p, %37, 0;\n"
    "wgmma.mma_async.sync.aligned.m64n64k16.f32.bf16.bf16 {"
    "%0, %1, %2, %3, %4, %5, %6, %7, %8, %9, %10, %11, %12, %13, %14, %15, "
    "%16, %17, %18, %19, %20, %21, %22, %23, %24, %25, %26, %27, %28, %29, %30, %31"
    "}, {%32, %33, %34, %35}, %36, p, 1, 1, 1;\n}\n"
    : "+f"(d[0]), "+f"(d[1]), "+f"(d[2]), "+f"(d[3]), "+f"(d[4]), "+f"(d[5]), "+f"(d[6]), "+f"(d[7]),
      "+f"(d[8]), "+f"(d[9]), "+f"(d[10]), "+f"(d[11]), "+f"(d[12]), "+f"(d[13]), "+f"(d[14]), "+f"(d[15]),
      "+f"(d[16]), "+f"(d[17]), "+f"(d[18]), "+f"(d[19]), "+f"(d[20]), "+f"(d[21]), "+f"(d[22]), "+f"(d[23]),
      "+f"(d[24]), "+f"(d[25]), "+f"(d[26]), "+f"(d[27]), "+f"(d[28]), "+f"(d[29]), "+f"(d[30]), "+f"(d[31])
    : "r"(a0), "r"(a1), "r"(a2), "r"(a3), "l"(db), "r"(scale_d));
}
__device__ __forceinline__ void wgmma_n64_ss_tb0(float (&d)[32], uint64_t da, uint64_t db, int scale_d) {
  asm volatile("{\n.reg .pred p;\nsetp.ne.b32 p, %34, 0;\n"
    "wgmma.mma_async.sync.aligned.m64n64k16.f32.bf16.bf16 {"
    "%0, %1, %2, %3, %4, %5, %6, %7, %8, %9, %10, %11, %12, %13, %14, %15, "
    "%16, %17, %18, %19, %20, %21, %22, %23, %24, %25, %26, %27, %28, %29, %30, %31"
    "}, %32, %33, p, 1, 1, 0, 0;\n}\n"
    : "+f"(d[0]), "+f"(d[1]), "+f"(d[2]), "+f"(d[3]), "+f"(d[4]), "+f"(d[5]), "+f"(d[6]), "+f"(d[7]),
      "+f"(d[8]), "+f"(d[9]), "+f"(d[10]), "+f"(d[11]), "+f"(d[12]), "+f"(d[13]), "+f"(d[14]), "+f"(d[15]),
      "+f"(d[16]), "+f"(d[17]), "+f"(d[18]), "+f"(d[19]), "+f"(d[20]), "+f"(d[21]), "+f"(d[22]), "+f"(d[23]),
      "+f"(d[24]), "+f"(d[25]), "+f"(d[26]), "+f"(d[27]), "+f"(d[28]), "+f"(d[29]), "+f"(d[30]), "+f"(d[31])
    : "l"(da), "l"(db), "r"(scale_d));
}

__device__ __forceinline__ bool elect() {
  uint32_t p;
  asm volatile("{.reg .pred q; elect.sync _|q, 0xffffffff; selp.u32 %0,1,0,q;}" : "=r"(p));
  return p;
}
__device__ __forceinline__ void mbar_init(uint32_t bar, uint32_t cnt) { asm volatile("mbarrier.init.shared::cta.b64 [%0], %1;" ::"r"(bar), "r"(cnt) : "memory"); }
__device__ __forceinline__ void mbar_expect(uint32_t bar, uint32_t bytes) { asm volatile("mbarrier.arrive.expect_tx.shared::cta.b64 _, [%0], %1;" ::"r"(bar), "r"(bytes) : "memory"); }
__device__ __forceinline__ void mbar_arrive(uint32_t bar) { asm volatile("mbarrier.arrive.shared::cta.b64 _, [%0];" ::"r"(bar) : "memory"); }
__device__ __forceinline__ void mbar_arrive_cta(uint32_t bar, uint32_t cta) {
  asm volatile("{.reg .b32 ra; mapa.shared::cluster.u32 ra, %0, %1; mbarrier.arrive.shared::cluster.b64 _, [ra];}" ::"r"(bar), "r"(cta) : "memory");
}
__device__ __forceinline__ void mbar_wait(uint32_t bar, uint32_t parity) {
  asm volatile(
      "{\n.reg .pred p;\n.reg .u32 c, t;\n"
      "mbarrier.try_wait.parity.shared::cta.b64 p, [%0], %1;\n@p bra DONE;\n"
      "mov.u32 c, %%clock;\n"
      "LAB_WAIT:\nmbarrier.try_wait.parity.shared::cta.b64 p, [%0], %1;\n@p bra DONE;\n"
      "mov.u32 t, %%clock;\nsub.u32 t, t, c;\nsetp.lt.u32 p, t, 0x40000000;\n@p bra LAB_WAIT;\ntrap;\nDONE:\n}" ::"r"(bar), "r"(parity) : "memory");
}
__device__ __forceinline__ void bar_sync(int id, int n) { asm volatile("bar.sync %0, %1;" ::"r"(id), "r"(n) : "memory"); }
__device__ __forceinline__ void bar_arrive(int id, int n) { asm volatile("bar.arrive %0, %1;" ::"r"(id), "r"(n) : "memory"); }
__device__ __forceinline__ void wg_fence() { asm volatile("wgmma.fence.sync.aligned;" ::: "memory"); }
__device__ __forceinline__ void wg_commit() { asm volatile("wgmma.commit_group.sync.aligned;" ::: "memory"); }
template <int N> __device__ __forceinline__ void wg_wait() { asm volatile("wgmma.wait_group.sync.aligned %0;" ::"n"(N) : "memory"); }
__device__ __forceinline__ void tma2d(uint32_t dst, const CUtensorMap* tm, uint32_t bar, int c0, int c1) {
  asm volatile("cp.async.bulk.tensor.2d.shared::cluster.global.mbarrier::complete_tx::bytes [%0], [%1,{%3,%4}], [%2];" ::"r"(dst), "l"(tm), "r"(bar), "r"(c0), "r"(c1) : "memory");
}
__device__ __forceinline__ void tma2d_mc(uint32_t dst, const CUtensorMap* tm, uint32_t bar, int c0, int c1) {
  asm volatile("cp.async.bulk.tensor.2d.shared::cluster.global.mbarrier::complete_tx::bytes.multicast::cluster [%0], [%1,{%3,%4}], [%2], %5;" ::"r"(dst), "l"(tm), "r"(bar), "r"(c0), "r"(c1), "h"((uint16_t)3) : "memory");
}
__device__ __forceinline__ void l2_prefetch_line(const void* p) { asm volatile("prefetch.global.L2 [%0];" ::"l"(p)); }
__device__ __forceinline__ uint64_t desc(uint32_t lo, uint32_t hi) { return ((uint64_t)hi << 32) | lo; }
constexpr uint32_t DHI_SW128 = (1024 >> 4) | (1u << 30);
constexpr uint32_t DHI_NONE = (128 >> 4);
constexpr uint32_t DLO_HS = (HS_LBO >> 4) << 16;
constexpr uint32_t DLO_MN = (8192 >> 4) << 16;
constexpr uint32_t DLO_K = 1u << 16;
__device__ __forceinline__ float tanh_fast(float x) { float y; asm("tanh.approx.f32 %0, %1;" : "=f"(y) : "f"(x)); return y; }
__device__ __forceinline__ uint32_t pack_bf16(float lo, float hi) { uint32_t r; asm("cvt.rn.bf16x2.f32 %0, %1, %2;" : "=r"(r) : "f"(hi), "f"(lo)); return r; }
__device__ __forceinline__ float rbf(float x) { return __bfloat162float(__float2bfloat16_rn(x)); }
__device__ __forceinline__ void mma16816(float (&c)[4], uint32_t a0, uint32_t a1, uint32_t a2, uint32_t a3, uint32_t b0, uint32_t b1) {
  asm volatile("mma.sync.aligned.m16n8k16.row.col.f32.bf16.bf16.f32 {%0,%1,%2,%3}, {%4,%5,%6,%7}, {%8,%9}, {%0,%1,%2,%3};"
               : "+f"(c[0]), "+f"(c[1]), "+f"(c[2]), "+f"(c[3]) : "r"(a0), "r"(a1), "r"(a2), "r"(a3), "r"(b0), "r"(b1));
}
__device__ __forceinline__ void sts128(uint32_t a, uint32_t x, uint32_t y, uint32_t z, uint32_t w) {
  asm volatile("st.shared.v4.b32 [%0], {%1,%2,%3,%4};" ::"r"(a), "r"(x), "r"(y), "r"(z), "r"(w) : "memory");
}
__device__ __forceinline__ void sts64f(uint32_t a, float x, float y) { asm volatile("st.shared.v2.f32 [%0], {%1,%2};" ::"r"(a), "f"(x), "f"(y) : "memory"); }
__device__ __forceinline__ float2 lds64f(uint32_t a) { float2 v; asm volatile("ld.shared.v2.f32 {%0,%1}, [%2];" : "=f"(v.x), "=f"(v.y) : "r"(a) : "memory"); return v; }
__device__ __forceinline__ uint32_t lds32(uint32_t a) { uint32_t v; asm volatile("ld.shared.b32 %0, [%1];" : "=r"(v) : "r"(a) : "memory"); return v; }
__device__ __forceinline__ void lds128(uint32_t a, uint32_t& x, uint32_t& y, uint32_t& z, uint32_t& w) {
  asm volatile("ld.shared.v4.b32 {%0,%1,%2,%3}, [%4];" : "=r"(x), "=r"(y), "=r"(z), "=r"(w) : "r"(a) : "memory");
}
__device__ __forceinline__ float bflo(uint32_t v) { return __uint_as_float(v << 16); }
__device__ __forceinline__ float bfhi(uint32_t v) { return __uint_as_float(v & 0xffff0000u); }
template <int N> __device__ __forceinline__ void keep(float (&a)[N]) {
#pragma unroll
  for (int i = 0; i < N; i++) asm volatile("" : "+f"(a[i])::"memory");
}

__global__ void __cluster_dims__(2, 1, 1) __launch_bounds__(384, 1) fused_kernel(const __grid_constant__ Params prm) {
  extern __shared__ __align__(1024) uint8_t smem[];
  const int warp = __shfl_sync(0xffffffffu, threadIdx.x >> 5, 0);
  const uint32_t sb0 = (uint32_t)__cvta_generic_to_shared(smem);
  const int j = blockIdx.x & 7, m = blockIdx.x >> 3, rank = j & 1;
  auto smem_base = [&]() { return __shfl_sync(0xffffffffu, sb0 + (threadIdx.x & 31), 0); };

  if (threadIdx.x == 320) asm volatile("prefetch.tensormap [%0];" ::"l"(&prm.tx) : "memory");
  if (warp == 0) {
    if (elect()) {
#pragma unroll
      for (int i = B_X8; i >= B_X; i--) mbar_init(sb0 + OFF_BAR + 8 * i, 1);
      asm volatile("fence.mbarrier_init.release.cluster;" ::: "memory");
    }
    __syncwarp();
  }
  asm volatile("barrier.cluster.arrive.relaxed.aligned;" ::: "memory");
  if (warp == 0) {
    const uint32_t xb = sb0 + OFF_BAR;
    if (elect()) {
      mbar_expect(xb + 8 * B_X8, 16384);
      tma2d(sb0, &prm.tx, xb + 8 * B_X8, 512, m * 128);
      tma2d(sb0 + 8192, &prm.tx, xb + 8 * B_X8, 512, m * 128 + 64);
#pragma unroll
      for (int i = 0; i < 4; i++) {
        mbar_expect(xb + 8 * (B_X + i), 16384);
        tma2d(sb0 + OFF_H + i * 16384, &prm.tx, xb + 8 * (B_X + i), i * 128, m * 128);
        tma2d(sb0 + OFF_H + i * 16384 + 8192, &prm.tx, xb + 8 * (B_X + i), i * 128 + 64, m * 128);
      }
    }
    __syncwarp();
  }
  asm volatile("barrier.cluster.wait.aligned;" ::: "memory");
  if (warp == 8 || warp == 9) {
    if (elect()) {
      if (warp == 8) {
#pragma unroll
        for (int i = 0; i < B_X; i++) mbar_init(sb0 + OFF_BAR + 8 * i, i >= B_EMPTY ? 2 : 1);
#pragma unroll
        for (int i = NST; i < NST + 2; i++) { mbar_arrive(sb0 + OFF_BAR + 8 * (B_FULL + i)); mbar_arrive(sb0 + OFF_BAR + 8 * (B_EMPTY + i)); mbar_arrive(sb0 + OFF_BAR + 8 * (B_EMPTY + i)); }
        __threadfence_block();
      } else {
#pragma unroll
        for (int i = B_X8 + 1; i < B_COUNT; i++) mbar_init(sb0 + OFF_BAR + 8 * i, (i >= B_SFULL && i < B_SFULL + 2) ? 4 : i == B_RING ? 2 : 1);
        if (sb0 & 1023) __trap();
      }
      asm volatile("fence.mbarrier_init.release.cluster;" ::: "memory");
    }
    __syncwarp();
  }
  if (warp == 0) {
    const uint32_t xb = sb0 + OFF_BAR;
    const bool e = elect();
#pragma unroll
    for (int i = 0; i < 4; i++) {
      const int kb = i * 2 + rank;
      if (e) { mbar_expect(xb + 8 * (B_X + 4 + i), 16384); tma2d_mc(sb0 + OFF_H + 65536 + kb * 8192, &prm.tx, xb + 8 * (B_X + 4 + i), kb * 64, m * 128 + 64); }
    }
    __syncwarp();
  }
  asm volatile("barrier.cluster.arrive.relaxed.aligned;\nbarrier.cluster.wait.aligned;" ::: "memory");

  if (warp >= 8) {
    asm volatile("setmaxnreg.dec.sync.aligned.u32 24;");
    if (warp == 8) {
      const uint32_t sb = smem_base(), bars = sb + OFF_BAR;
      bool e;
      int s = 0, nst = NST; uint32_t ph = 1;
      uint32_t dst, fb;
      auto acquire = [&](uint32_t bytes) {
        mbar_wait(bars + 8 * (B_EMPTY + s), ph);
        fb = bars + 8 * (B_FULL + s); dst = sb + s * SLOT;
        e = elect();
        if (e) mbar_expect(fb, bytes);
        if (++s == nst) { s = 0; ph ^= 1; }
      };
      auto box = [&](const CUtensorMap* t, uint32_t o, int a, int b) { if (e) tma2d(dst + o, t, fb, a, b); };
      const int lane = threadIdx.x & 31;
      const char* pf = lane < 8 ? (const char*)(lane & 4 ? prm.wu : prm.wg) + ((size_t)(m * 4 + (lane & 3)) * kF + j * 576) * 2
                     : lane < 12 ? (const char*)prm.wd + (size_t)j * 576 * 1152 + (m * 324 + (lane & 3)) * 128
                                 : (const char*)(lane & 1 ? prm.cim : prm.cre) + (size_t)blockIdx.x * 5184;
      int pk = 0, pleft = 81;
      auto prefetch = [&]() {
        if (pleft > 0) {
          if (lane < 14) l2_prefetch_line(pf);
          pf += lane < 8 ? (pk == 8 ? 128 - 8 * 64 * kF * 2 : 64 * kF * 2) : lane < 12 ? 512 : 64;
          pk = pk == 8 ? 0 : pk + 1;
          pleft--;
        }
      };
      mbar_wait(bars + 8 * B_X8, 0);
      e = elect();
#pragma unroll 1
      for (int kb = 0; kb < 8; kb++) {
        fb = bars + 8 * (B_BU + (kb >> 2));
        if (e) { if ((kb & 3) == 0) mbar_expect(fb, 4 * 9216); tma2d(sb + OFF_BU0 + kb * 9216, &prm.tBre, fb, kb * 64, j * 72); }
      }
      bar_sync(NB_XDONE, 160);
      fb = bars + 8 * (B_BU + 2);
      if (e) { mbar_expect(fb, 5 * 9216); tma2d(sb + OFF_BU1, &prm.tBre, fb, 512, j * 72); }
#pragma unroll 1
      for (int kb = 0; kb < 4; kb++) if (e) tma2d(sb + OFF_BU1 + (kb + 1) * 9216, &prm.tBim, fb, kb * 64, j * 72);
      for (int i = 0; i < PFD / 2; i++) prefetch();
      bar_sync(NB_XDONE + 1, 160);
      fb = bars + 8 * (B_BU + 3);
      if (e) mbar_expect(fb, 5 * 9216);
#pragma unroll 1
      for (int kb = 4; kb < 9; kb++) if (e) tma2d(sb + OFF_BU2 + (kb - 4) * 9216, &prm.tBim, fb, kb * 64, j * 72);
      for (int i = PFD / 2; i < PFD; i++) prefetch();
      mbar_wait(bars + 8 * B_RING, 0);
      for (int c = 0; c < 9; c++) {
        const int col = j * 576 + c * 64;
#pragma unroll 1
        for (int kb = 0; kb < 9; kb++) {
          if (kb == 7 && c == 0) nst = 8;
          if (kb == 4 && c == 3) nst = 7;
          if (kb == 2 && c == 4) nst = 6;
          acquire(16384); box(&prm.tWg, 0, col, kb * 64); box(&prm.tWu, 8192, col, kb * 64); prefetch();
        }
      }
      auto half_tile = [&](int n0) {
#pragma unroll 1
        for (int kp = 0; kp < 4; kp++) { acquire(16384); box(&prm.tWd, 0, n0, j * 576 + kp * 128); box(&prm.tWd, 8192, n0, j * 576 + kp * 128 + 64); }
        nst = NST + 1;
        acquire(8192 + 2048); box(&prm.tWd, 0, n0, j * 576 + 512); box(&prm.tCre8, 8192, j * 72 + 64, n0); box(&prm.tCim8, 9216, j * 72 + 64, n0);
        acquire(16384); box(&prm.tCre, 0, j * 72, n0); box(&prm.tCim, 8192, j * 72, n0);
      };
      if (rank) half_tile(512);
#pragma unroll 1
      for (int t = 0; t < 4 - rank; t++) {
        const int n0 = ((rank ^ t ^ 1) & 1) * 256 + (((t >> 1) ^ (j >> 1)) & 1) * 128;
#pragma unroll 1
        for (int kb = 0; kb < 9; kb++) {
          if (kb == 4) nst = NST + 1;
          if (kb == 3 && t == 0 && rank) mbar_wait(bars + 8 * B_HFREE, 0);
          acquire(16384); box(&prm.tWd, 0, n0, j * 576 + kb * 64); box(&prm.tWd, 8192, n0 + 64, j * 576 + kb * 64);
        }
        if (t == 0) mbar_wait(bars + 8 * B_HFREE, 0);
        acquire(16384); box(&prm.tCre, 0, j * 72, n0); box(&prm.tCre, 8192, j * 72, n0 + 64);
        acquire(16384); box(&prm.tCim, 0, j * 72, n0); box(&prm.tCim, 8192, j * 72, n0 + 64);
        acquire(4096);
        box(&prm.tCre8, 0, j * 72 + 64, n0); box(&prm.tCre8, 1024, j * 72 + 64, n0 + 64);
        box(&prm.tCim8, 2048, j * 72 + 64, n0); box(&prm.tCim8, 3072, j * 72 + 64, n0 + 64);
      }
      if (!rank) half_tile(512);
      else {
#pragma unroll 1
        for (int hh = 0; hh < 2; hh++) half_tile(256 + (((j >> 1) ^ 1) & 1) * 128 + hh * 64);
      }
    } else {
      const uint32_t sb = smem_base(), bars = sb + OFF_BAR;
      const int p = min((int)threadIdx.x - 288, 71);
      if (threadIdx.x < 288 + 10) asm volatile("prefetch.tensormap [%0];" ::"l"(&prm.tBre + (threadIdx.x - 288)) : "memory");
      if (warp == 10) {
        const int l = threadIdx.x & 31;
        const char* q = (const char*)(l & 1 ? prm.bim : prm.bre) + (size_t)blockIdx.x * 5184;
        mbar_wait(bars + 8 * B_X8, 0);
#pragma unroll
        for (int i = 0; i < 3; i++) if (i * 16 + (l >> 1) < 42) l2_prefetch_line(q + min((i * 16 + (l >> 1)) * 128, 5183));
      }
      const unsigned epoch = *(volatile unsigned*)&g_epoch[blockIdx.x];
      {
        const int pg = j * 72 + p;
        const float lr = __bfloat162float(prm.lre[pg]), li = __bfloat162float(prm.lim[pg]);
        const float dt = rbf(expf(__bfloat162float(prm.ldt[pg])));
        const float ea = expf(dt * lr);
        float sn, cs;
        sincosf(dt * li, &sn, &cs);
        const float ar = ea * cs, ai = ea * sn;
        float br = ar, bi = ai;
#pragma unroll
        for (int k = 0; k < 6; k++) { const float t = br * br - bi * bi; bi = 2.f * br * bi; br = t; }
        const float nr = ar - 1.f, den = 4.f / (lr * lr + li * li);
        sts64f(sb + OFF_CONST + p * 8, ar, ai);
        sts64f(sb + OFF_CONST + 576 + p * 8, br, bi);
        sts64f(sb + OFF_CONST + 1152 + p * 8, (nr * lr + ai * li) * den, (ai * lr - nr * li) * den);
      }
      bar_sync(NB_DUMP, 352);
      {
        const int lane = threadIdx.x & 31;
        const int half = warp == 11 ? (lane >> 2) & 1 : warp - 9;
        const uint32_t cu = sb + OFF_CONST + (warp == 11 ? 32 + (lane & 3) : lane) * 16;
        uint32_t a0 = sb + OFF_DUMP + half * HS_BYTES + (warp == 11 ? 16 : lane >> 2) * HS_LBO + (lane & 3) * 4;
        asm volatile("" : "+r"(a0));
        const uint32_t di = warp == 11 ? HS_LBO : 8 * HS_LBO;
        float a[4], h[4] = {0.f, 0.f, 0.f, 0.f};
        auto ld4 = [&](uint32_t ad, float (&v)[4]) { asm volatile("ld.shared.v4.f32 {%0,%1,%2,%3}, [%4];" : "=f"(v[0]), "=f"(v[1]), "=f"(v[2]), "=f"(v[3]) : "r"(ad) : "memory"); };
        auto cfma = [&](const float (&c)[4], float r0, float i0, float r1, float i1) {
          const float n0 = fmaf(c[0], h[0], fmaf(-c[1], h[1], r0)), n1 = fmaf(c[2], h[2], fmaf(-c[3], h[3], r1));
          h[1] = fmaf(c[0], h[1], fmaf(c[1], h[0], i0)); h[3] = fmaf(c[2], h[3], fmaf(c[3], h[2], i1));
          h[0] = n0; h[2] = n1;
        };
        ld4(cu, a);
#pragma unroll 1
        for (uint32_t ad = a0; ad != a0 + 1024; ad += 64) {
          uint32_t wr[4], wi[4];
#pragma unroll
          for (int k = 0; k < 4; k++) { wr[k] = lds32(ad + k * 16); wi[k] = lds32(ad + di + k * 16); }
#pragma unroll
          for (int k = 0; k < 4; k++) cfma(a, bflo(wr[k]), bflo(wi[k]), bfhi(wr[k]), bfhi(wi[k]));
        }
        if (half == 0) sts128(cu + 1728, __float_as_uint(h[0]), __float_as_uint(h[1]), __float_as_uint(h[2]), __float_as_uint(h[3]));
        bar_sync(NB_SCAN, 96);
        if (half == 1 && m < 15) {
          float b[4], s1[4] = {h[0], h[1], h[2], h[3]};
          ld4(cu + 576, b); ld4(cu + 1728, h);
          cfma(b, s1[0], s1[1], s1[2], s1[3]);
          uint2* gp = &g_S[epoch & 1][m][j][(cu - sb - OFF_CONST) >> 3];
          asm volatile("st.relaxed.gpu.global.v2.b64 [%0], {%1,%2};" ::"l"(gp), "l"(~(((uint64_t)__float_as_uint(h[1]) << 32) | __float_as_uint(h[0]))),
                       "l"(~(((uint64_t)__float_as_uint(h[3]) << 32) | __float_as_uint(h[2]))) : "memory");
        }
        __syncwarp();
        g_S[(epoch & 1) ^ 1][m][j][p] = make_uint2(0u, 0u);
        {
          const float2 b = lds64f(sb + OFF_CONST + 576 + p * 8);
          const float br = b.x * b.x - b.y * b.y, bi = 2.f * b.x * b.y;
          float hr = 0.f, hi = 0.f;
          const uint2* sp = &g_S[epoch & 1][0][j][p];
#pragma unroll 1
          for (int left = m; left > 0; left -= 3, sp += 3 * 768) {
            uint32_t v[3][2];
            int spins = 0;
            uint32_t ok;
            do {
#pragma unroll
              for (int k = 0; k < 3; k++) {
                v[k][0] = v[k][1] = 0xffffffffu;
                if (k < left) asm volatile("ld.relaxed.gpu.global.v2.b32 {%0,%1}, [%2];" : "=r"(v[k][0]), "=r"(v[k][1]) : "l"(sp + k * 768) : "memory");
              }
              ok = min(min(min(v[0][0], v[0][1]), min(v[1][0], v[1][1])), min(v[2][0], v[2][1]));
              if (++spins > (1 << 22)) __trap();
            } while (ok == 0u);
#pragma unroll
            for (int k = 0; k < 3; k++)
              if (k < left) { const float nr = fmaf(br, hr, fmaf(-bi, hi, __uint_as_float(~v[k][0]))); hi = fmaf(br, hi, fmaf(bi, hr, __uint_as_float(~v[k][1]))); hr = nr; }
          }
          sts64f(sb + OFF_CONST + p * 8, hr, hi);
        }
        __syncwarp();
        bar_sync(NB_SCAN, 96);
        ld4(cu, h);
        uint32_t cr, ci, cn;
        {
          float b[4], s0[4];
          ld4(cu + 576, b); ld4(cu + 1728, s0);
          if (half == 1) cfma(b, s0[0], s0[1], s0[2], s0[3]);
          ld4(cu + 1152, b);
          cr = pack_bf16(b[0], b[2]); ci = pack_bf16(b[1], b[3]); cn = ci ^ 0x80008000u;
        }
        __syncwarp();
#pragma unroll 1
        for (uint32_t ad = a0; ad != a0 + 1024; ad += 32) {
          uint32_t wr[2], wi[2];
#pragma unroll
          for (int k = 0; k < 2; k++) { wr[k] = lds32(ad + k * 16); wi[k] = lds32(ad + di + k * 16); }
#pragma unroll
          for (int k = 0; k < 2; k++) {
            cfma(a, bflo(wr[k]), bflo(wi[k]), bfhi(wr[k]), bfhi(wi[k]));
            const uint32_t hr = pack_bf16(h[0], h[2]), hn = pack_bf16(-h[1], -h[3]);
            uint32_t o0, o1;
            asm("{.reg .b32 t; mul.rn.bf16x2 t, %2, %4; fma.rn.bf16x2 %0, %1, %3, t;}" : "=r"(o0) : "r"(hr), "r"(hn), "r"(cr), "r"(ci));
            asm("{.reg .b32 t; mul.rn.bf16x2 t, %1, %4; fma.rn.bf16x2 %0, %2, %3, t;}" : "=r"(o1) : "r"(hr), "r"(hn), "r"(cr), "r"(cn));
            asm volatile("st.shared.b32 [%0], %1;" ::"r"(ad + k * 16), "r"(o0) : "memory");
            asm volatile("st.shared.b32 [%0], %1;" ::"r"(ad + di + k * 16), "r"(o1) : "memory");
          }
        }
        asm volatile("fence.proxy.async.shared::cta;" ::: "memory");
      }
      bar_sync(NB_SCAN, 96);
      const bool lead = elect();
      if (warp == 9) {
        if (lead) {
#pragma unroll 1
          for (uint32_t o = 0; o < 2 * HS_BYTES; o += 4 * HS_LBO) {
            asm volatile("cp.async.bulk.global.shared::cta.bulk_group [%0], [%1], %2;" ::"l"(&g_hs[blockIdx.x][o]), "r"(sb + OFF_DUMP + o), "r"(4 * HS_LBO) : "memory");
            asm volatile("cp.async.bulk.commit_group;\ncp.async.bulk.wait_group.read 0;" ::: "memory");
          }
          mbar_arrive(bars + 8 * B_SCAN);
        }
        __syncwarp();
      }
      if (warp == 9) {
        if (lead) {
          __threadfence();
          asm volatile("red.release.gpu.global.add.u32 [%0], 1;" ::"l"(&g_ready[m]) : "memory");
          g_epoch[blockIdx.x] = epoch + 1u;
          asm volatile("cp.async.bulk.wait_group 0;" ::: "memory");
        }
        __syncwarp();
        bar_sync(NB_HFREE, 288);
        if (lead) {
          mbar_arrive(bars + 8 * B_HFREE);
          mbar_expect(bars + 8 * B_HSFULL, 2 * HS_BYTES);
          asm volatile("cp.async.bulk.shared::cluster.global.mbarrier::complete_tx::bytes [%0], [%1], %2, [%3];" ::"r"(sb + OFF_HS),
                       "l"(&g_hs[blockIdx.x][0]), "r"(2 * HS_BYTES), "r"(bars + 8 * B_HSFULL) : "memory");
          for (int w = 0; w < 2; w++) mbar_arrive_cta(bars + 8 * (B_RFREE + w), rank ^ 1);
        }
        __syncwarp();
      } else {
        const int w = warp - 10;
        {
          const unsigned target = 8u * (epoch + 1u);
          int spins = 0;
          unsigned v;
          do {
            if (spins) __nanosleep(500);
            asm volatile("ld.relaxed.gpu.global.u32 %0, [%1];" : "=r"(v) : "l"(&g_ready[m]) : "memory");
            if (++spins > (1 << 21)) __trap();
          } while ((int)(v - target) < 0);
          asm volatile("fence.acq_rel.gpu;" ::: "memory");
          asm volatile("fence.proxy.async.global;" ::: "memory");
        }
        const uint32_t stg = sb + OFF_STG + w * 32768;
        const int nu = 5 + rank;
#pragma unroll 1
        for (int u = 0; u < nu; u++) {
          const int t = u - rank;
          if (t == 0 || t == 2) {
            if (elect()) mbar_expect(bars + 8 * (B_RFULL + w), 16384);
            mbar_wait(bars + 8 * (B_SFULL + w), u & 1);
            mbar_wait(bars + 8 * (B_RFREE + w), t >> 1);
            if (elect())
              asm volatile("{.reg .b32 ra, rb; mapa.shared::cluster.u32 ra, %0, %3; mapa.shared::cluster.u32 rb, %2, %3;\n"
                           "cp.async.bulk.shared::cluster.shared::cta.mbarrier::complete_tx::bytes [ra], [%1], 16384, [rb];}" ::"r"(stg + 16384),
                           "r"(stg), "r"(bars + 8 * (B_RFULL + w)), "r"(rank ^ 1) : "memory");
            mbar_wait(bars + 8 * (B_RFULL + w), t >> 1);
            if (elect()) mbar_arrive_cta(bars + 8 * (B_SFREE + w), rank ^ 1);
          } else {
            mbar_wait(bars + 8 * (B_SFULL + w), u & 1);
            const bool d = u == (rank ? 0 : 4), hf = rank && u >= 4;
            const int n0 = d ? 512 : rank * 256 + (((min(t, 3) >> 1) ^ (j >> 1)) & 1) * 128 + (u == 5 ? 64 : 0);
            const uint32_t src = d && !rank ? sb + (2 + w) * SLOT : stg + (u == 5 ? 16384 : 0);
            if (elect()) {
#pragma unroll 1
              for (int b = 0; b < (d || hf ? 2 : 4); b++) {
                asm volatile("cp.reduce.async.bulk.tensor.4d.global.shared::cta.add.tile.bulk_group [%0, {%1,%2,%2,%3}], [%4];" ::"l"(&prm.tOut), "r"(n0 + b * 32), "r"(0),
                             "r"(m * 16 + w * 8), "r"(src + b * 8192) : "memory");
                asm volatile("cp.async.bulk.commit_group;" ::: "memory");
                if (u < nu - 1) asm volatile("cp.async.bulk.wait_group.read 0;" ::: "memory");
              }
              if (u < 3) {
                asm volatile("cp.async.bulk.wait_group.read 0;" ::: "memory");
                mbar_arrive(bars + 8 * (B_SFREE + w));
                if (t == 1) mbar_arrive_cta(bars + 8 * (B_RFREE + w), rank ^ 1);
              }
              if (u == nu - 1) asm volatile("cp.async.bulk.wait_group.read 0;" ::: "memory");
            }
          }
          __syncwarp();
        }
      }
    }
  } else {
    asm volatile("setmaxnreg.inc.sync.aligned.u32 240;");
    const uint32_t sb = smem_base(), bars = sb + OFF_BAR;
    const int wg = warp >> 2, w4 = warp & 3;
    const int lane = threadIdx.x & 31, g = lane >> 2, q = lane & 3;
    const uint32_t hw = sb + OFF_H + wg * 65536;

    int s = 0, nst = NST; uint32_t ph = 0;
    auto release = [&](int st) { if (w4 == 0) { if (elect()) mbar_arrive(bars + 8 * (B_EMPTY + st)); } };
    const uint32_t dring = (sb & 0x3FFFF) >> 4;
    uint32_t dlo; int prev = 0;
    auto stage_begin = [&]() { mbar_wait(bars + 8 * (B_FULL + s), ph); dlo = dring + s * (SLOT >> 4); wg_fence(); };
    auto advance = [&]() { if (++s == nst) { s = 0; ph ^= 1; } };
    auto stage_end = [&](bool rel) {
      wg_commit();
      if (rel) { wg_wait<1>(); release(prev); }
      prev = s;
      advance();
    };

    uint32_t xa[144];
    uint32_t xr[18], dk[9];
    uint32_t rh[2], cc[2];
#pragma unroll
    for (int i = 0; i < 9; i++) dk[i] = __ldg((const uint32_t*)(prm.dskip + j * 72 + i * 8 + q * 2));
    {
      const int r = w4 * 16 + (lane & 7) + ((lane >> 3) & 1) * 8;
      const uint32_t ro = r * 128, cx = ((lane >> 4) ^ (lane & 7)) << 4;
      float s1[2][4] = {};
      auto load = [&](int kb, uint32_t base) {
#pragma unroll
        for (int kk = 0; kk < 4; kk++) {
          const int i = (kb * 4 + kk) * 4;
          asm volatile("ldmatrix.sync.aligned.m8n8.x4.shared.b16 {%0,%1,%2,%3}, [%4];"
                       : "=r"(xa[i]), "=r"(xa[i + 1]), "=r"(xa[i + 2]), "=r"(xa[i + 3]) : "r"(base + ro + (cx ^ (kk << 5))) : "memory");
        }
      };
      const uint32_t b0 = (g & 1) ? 0u : 0x3f803f80u, b1 = b0 ^ 0x3f803f80u;
      auto sums = [&](int kb) {
#pragma unroll
        for (int kk = 0; kk < 4; kk++) {
          const int i = (kb * 4 + kk) * 4;
          uint32_t a[4];
#pragma unroll
          for (int e = 0; e < 2; e++) {
            asm("mul.rn.bf16x2 %0, %1, %1;" : "=r"(a[e]) : "r"(xa[i + e]));
            asm("add.rn.bf16x2 %0, %1, %2;" : "=r"(a[2 + e]) : "r"(xa[i + e]), "r"(xa[i + 2 + e]));
            asm("fma.rn.bf16x2 %0, %1, %1, %0;" : "+r"(a[e]) : "r"(xa[i + 2 + e]));
          }
          mma16816(s1[kk & 1], a[0], a[1], a[2], a[3], b0, b1);
        }
      };
#pragma unroll
      for (int i = 0; i < 9; i++) {
        const int c8 = j * 9 + i, kb = c8 >> 3;
        xr[2 * i] = (kb < 8 ? hw + kb * 8192 : sb + wg * 8192) + (w4 * 16 + g) * 128 + (((c8 & 7) ^ g) << 4) + q * 4;
        asm volatile("" : "+r"(xr[2 * i]));
      }
      mbar_wait(bars + 8 * B_X8, 0);
      load(8, sb + wg * 8192);
      auto pin = [&]() { asm volatile("{.reg .pred p; .reg .u32 c, z; mov.u32 c, %clock; mov.u32 z, %ntid.y; setp.eq.u32 p, z, 0; @p st.shared.u32 [c], c;}" ::: "memory"); };
#pragma unroll
      for (int kp = 0; kp < 4; kp++) {
        mbar_wait(bars + 8 * (B_X + wg * 4 + kp), 0);
        load(2 * kp, hw + 2 * kp * 8192);
        load(2 * kp + 1, hw + (2 * kp + 1) * 8192);
        if (kp == 3) {
#pragma unroll
          for (int i = 0; i < 9; i++) { xr[2 * i + 1] = lds32(xr[2 * i] + 1024); xr[2 * i] = lds32(xr[2 * i]); }
        }
        if (kp == 0) sums(8); else { sums(2 * kp - 2); sums(2 * kp - 1); }
      }
      asm volatile("fence.proxy.async.shared::cta;" ::: "memory");
      bar_arrive(NB_XDONE + wg, 160);
      if (wg == 1) bar_arrive(NB_STATS, 256);
      pin();
      sums(6);
      sums(7);
      pin();
#pragma unroll
      for (int e = 0; e < 2; e++) {
        const float mu = (s1[0][2 * e + 1] + s1[1][2 * e + 1]) * (1.f / kD);
        const float var = fmaxf(fmaf(-mu, mu, (s1[0][2 * e] + s1[1][2 * e]) * (1.f / kD)), 0.f);
        float sd, r;
        asm("sqrt.approx.f32 %0, %1;" : "=f"(sd) : "f"(rbf(rbf(var) + 1e-5f)));
        asm("rcp.approx.ftz.f32 %0, %1;" : "=f"(r) : "f"(rbf(sd)));
        r = rbf(0.5f * r);
        rh[e] = pack_bf16(r, r); cc[e] = pack_bf16(-mu * r, -mu * r);
      }
    }

    auto normalise = [&](int kb) {
#pragma unroll
      for (int i = 0; i < 16; i++) asm("fma.rn.bf16x2 %0, %0, %1, %2;" : "+r"(xa[16 * kb + (i >> 3) + 2 * (i & 7)]) : "r"(rh[i >> 3]), "r"(cc[i >> 3]));
    };
    {
      float ab[36];
      float* op = prm.out + (size_t)(m * 128 + wg * 64 + w4 * 16 + g) * kD + j * 72 + q * 2;
      auto residual = [&](int i) {
        asm volatile("add.rn.bf16x2 %0, %0, %0;" : "+r"(dk[i]));
#pragma unroll
        for (int e = 0; e < 2; e++) {
          uint32_t t;
          asm("fma.rn.bf16x2 %0, %1, %2, %3;" : "=r"(t) : "r"(xr[2 * i + e]), "r"(rh[e]), "r"(cc[e]));
          asm("fma.rn.bf16x2 %0, %0, %1, %2;" : "+r"(t) : "r"(dk[i]), "r"(xr[2 * i + e]));
          *(float2*)(op + e * 8 * kD + i * 8) = make_float2(bflo(t), bfhi(t));
        }
      };
      const uint32_t da = sb + OFF_DUMP + wg * HS_BYTES + (w4 * 16 + g) * 16 + q * 4;
      auto dump = [&](int im) {
#pragma unroll
        for (int i = 0; i < 18; i++)
          asm volatile("st.shared.b32 [%0], %1;" ::"r"(da + (i < 16 ? 8 * im + (i >> 1) : 16 + im) * HS_LBO + (i & 1) * 128), "r"(pack_bf16(ab[2 * i], ab[2 * i + 1])) : "memory");
      };
      auto bu = [&](int kb, uint32_t off) {
        wg_fence();
#pragma unroll
        for (int kk = 0; kk < 4; kk++) { const int i = (kb * 4 + kk) * 4; wgmma_n72_rs_tb0(ab, xa[i], xa[i + 1], xa[i + 2], xa[i + 3], desc((dring + (off >> 4) + kk * 2) + DLO_K, DHI_SW128), (kb | kk) != 0); }
        wg_commit();
      };
      normalise(0);
      if (wg == 0) {
#pragma unroll
        for (int kb = 1; kb < 9; kb++) normalise(kb);
        bar_sync(NB_STATS, 256);
      }
#pragma unroll
      for (int kb = 0; kb < 9; kb++) {
        if ((kb & 3) == 0) mbar_wait(bars + 8 * (B_BU + (kb >> 2)), 0);
        bu(kb, kb < 8 ? OFF_BU0 + kb * 9216 : OFF_BU1);
        if (kb < 8 && wg == 1) normalise(kb + 1);
      }
      wg_wait<0>();
      if (w4 == 0) { if (elect()) mbar_arrive(bars + 8 * B_RING); }
      keep(ab);
      dump(0);
#pragma unroll
      for (int kb = 0; kb < 9; kb++) {
        if (kb == 4) mbar_wait(bars + 8 * (B_BU + 3), 0);
        bu(kb, kb < 4 ? OFF_BU1 + (kb + 1) * 9216 : OFF_BU2 + (kb - 4) * 9216);
        residual(kb);
      }
      wg_wait<0>();
      keep(ab);
      dump(1);
      bar_arrive(NB_DUMP, 352);
    }

    float acc[64];
    {
      const uint32_t ha = sb + OFF_H + (threadIdx.x & 127) * 16, hblk = wg ? HBLK1 : HBLK0;
      auto glu = [&](int i) {
        return pack_bf16(fmaf(acc[32 + 2 * i], tanh_fast(acc[2 * i]), acc[32 + 2 * i]), fmaf(acc[33 + 2 * i], tanh_fast(acc[2 * i + 1]), acc[33 + 2 * i]));
      };
      for (int c = 0;; c++) {
        if (wg == 1) bar_sync(NB_SKEW, 256);
#pragma unroll
        for (int kb = 0; kb < 9; kb++) {
          if (kb == 7 && c == 0) nst = 8;
          if (kb == 4 && c == 3) nst = 7;
          if (kb == 2 && c == 4) nst = 6;
          stage_begin();
#pragma unroll
          for (int kk = 0; kk < 4; kk++) { const int i = (kb * 4 + kk) * 4; wgmma_n128_rs_tb1(acc, xa[i], xa[i + 1], xa[i + 2], xa[i + 3], desc((dlo + kk * 128) + DLO_MN, DHI_SW128), (kb | kk) != 0); }
          if (kb == SKEW - 1 && wg == 0) bar_arrive(NB_SKEW, 256);
          if (kb == 8 && c >= 3 && c <= 5) mbar_wait(bars + 8 * (c == 5 ? B_SCAN : B_EMPTY + 10 - c), c == 3);
          stage_end(kb > 0);
        }
        wg_wait<0>();
        release(prev);
        keep(acc);
        if (c == 8) break;
        const uint32_t hc = ha + ((hblk >> (4 * c)) & 15) * 8192;
#pragma unroll
        for (int i = 0; i < 4; i++) sts128(hc + i * 2048, glu(4 * i), glu(4 * i + 1), glu(4 * i + 2), glu(4 * i + 3));
      }
#pragma unroll
      for (int i = 0; i < 32; i++) lds128(ha + ((hblk >> (4 * (i >> 2))) & 15) * 8192 + (i & 3) * 2048, xa[4 * i], xa[4 * i + 1], xa[4 * i + 2], xa[4 * i + 3]);
#pragma unroll
      for (int i = 0; i < 16; i++) xa[128 + i] = glu(i);
      asm volatile("fence.proxy.async.shared::cta;" ::: "memory");
      bar_arrive(NB_HFREE, 288);
    }

    const uint32_t dhs = (((sb + OFF_HS + wg * HS_BYTES) & 0x3FFFF) >> 4) | DLO_HS;
    const int rp = (g >> 2) + 2 * (g & 3);
    const uint32_t so = w4 * 2048 + rp * 128 + (q & 1) * 8, sx = ((q >> 1) ^ rp) << 4;
    const uint32_t rcv = sb + OFF_STG + wg * 32768 + 16384 + w4 * 2048 + lane * 16;
    auto staged = [&]() {
      asm volatile("fence.proxy.async.shared::cta;" ::: "memory");
      __syncwarp();
      if (elect()) mbar_arrive(bars + 8 * (B_SFULL + wg));
    };
    auto half_tile = [&](const bool first, const int kind) {
      float a2[32];
      if (wg == 1) bar_sync(NB_SKEW, 256);
      const uint32_t ph0 = ph;
      uint32_t d4;
#pragma unroll
      for (int kp = 0; kp < 5; kp++) {
        if (kp == 4) nst = NST + 1;
        stage_begin();
#pragma unroll
        for (int kk = 0; kk < (kp < 4 ? 8 : 4); kk++) { const int i = (kp * 8 + kk) * 4; wgmma_n64_rs_tb1(a2, xa[i], xa[i + 1], xa[i + 2], xa[i + 3], desc((dlo + kk * 128) + DLO_MN, DHI_SW128), (kp | kk) != 0); }
        if (kp == 1 && wg == 0) bar_arrive(NB_SKEW, 256);
        d4 = dlo;
        stage_end(kp > 0);
        if (kp == 0 && !first) staged();
      }
      if (first) mbar_wait(bars + 8 * B_HSFULL, 0);
      stage_begin();
#pragma unroll
      for (int kk = 0; kk < 8; kk++) wgmma_n64_ss_tb0(a2, desc(dhs + kk * (2 * HS_LBO >> 4), DHI_NONE), desc((dlo + (kk >> 2) * 512 + (kk & 3) * 2) + DLO_K, DHI_SW128), 1);
      wgmma_n64_ss_tb0(a2, desc(dhs + 8 * (2 * HS_LBO >> 4), DHI_NONE), desc((d4 + 512) | ((1024 >> 4) << 16), DHI_NONE), 1);
      wg_commit();
      if (!first) {
        if (kind == 1) mbar_wait(bars + 8 * (B_EMPTY + 2 + wg), ph0);
        if (kind == 2) { mbar_wait(bars + 8 * (B_SFREE + wg), 1); mbar_wait(bars + 8 * (B_RFULL + wg), 1); }
      }
      wg_wait<0>();
      release(prev); release(s); advance();
      keep(a2);
      if (!first && kind >= 2) {
#pragma unroll
        for (int i = 0; i < 4; i++) {
          uint32_t v[4];
          lds128(rcv + (kind & 1) * 8192 + i * 512, v[0], v[1], v[2], v[3]);
#pragma unroll
          for (int e = 0; e < 4; e++) { a2[8 * i + 2 * e] += bflo(v[e]); a2[8 * i + 2 * e + 1] += bfhi(v[e]); }
        }
        __syncwarp();
      }
      const uint32_t stg = (!first && kind == 1 ? sb + (2 + wg) * SLOT : sb + OFF_STG + wg * 32768 + (kind == 3 ? 16384 : 0)) + so;
#pragma unroll
      for (int i = 0; i < 8; i++) {
        const uint32_t a = stg + (i >> 2) * 8192 + (sx ^ ((i & 3) << 5));
        sts64f(a, a2[4 * i], a2[4 * i + 1]);
        sts64f(a + 1024, a2[4 * i + 2], a2[4 * i + 3]);
      }
    };
    if (rank) half_tile(true, 0);
    for (int t = 0; t < 4 - rank; t++) {
      if (wg == 1) bar_sync(NB_SKEW, 256);
#pragma unroll
      for (int kb = 0; kb < 9; kb++) {
        if (kb == 4) nst = NST + 1;
        stage_begin();
#pragma unroll
        for (int kk = 0; kk < 4; kk++) { const int i = (kb * 4 + kk) * 4; wgmma_n128_rs_tb1(acc, xa[i], xa[i + 1], xa[i + 2], xa[i + 3], desc((dlo + kk * 128) + DLO_MN, DHI_SW128), (kb | kk) != 0); }
        if (kb == SKEW - 1 && wg == 0) bar_arrive(NB_SKEW, 256);
        stage_end(kb > 0);
        if (kb == 0 && t + rank > 0) staged();
      }
      if (t == 0) mbar_wait(bars + 8 * B_HSFULL, 0);
      stage_begin();
#pragma unroll
      for (int kk = 0; kk < 4; kk++) wgmma_n128_ss_tb0(acc, desc(dhs + kk * (2 * HS_LBO >> 4), DHI_NONE), desc((dlo + kk * 2) + DLO_K, DHI_SW128), 1);
      stage_end(true);
      stage_begin();
#pragma unroll
      for (int kk = 0; kk < 4; kk++) wgmma_n128_ss_tb0(acc, desc(dhs + (4 + kk) * (2 * HS_LBO >> 4), DHI_NONE), desc((dlo + kk * 2) + DLO_K, DHI_SW128), 1);
      const int s_im = s;
      advance();
      stage_begin();
      wgmma_n128_ss_tb0(acc, desc(dhs + 8 * (2 * HS_LBO >> 4), DHI_NONE), desc(dlo | ((2048 >> 4) << 16), DHI_NONE), 1);
      stage_end(true);
      if (t + rank > 0) mbar_wait(bars + 8 * (B_SFREE + wg), (t + rank - 1) & 1);
      if (t & 1) mbar_wait(bars + 8 * (B_RFULL + wg), t >> 1);
      wg_wait<0>();
      release(s_im); release(prev);
      keep(acc);
      if (t & 1) {
        const uint32_t stg = sb + OFF_STG + wg * 32768 + so;
#pragma unroll
        for (int hh = 0; hh < 2; hh++) {
#pragma unroll
          for (int i = 4 * hh; i < 4 * hh + 4; i++) {
            uint32_t v[4];
            lds128(rcv + hh * 8192 + (i & 3) * 512, v[0], v[1], v[2], v[3]);
#pragma unroll
            for (int e = 0; e < 4; e++) { acc[8 * i + 2 * e] += bflo(v[e]); acc[8 * i + 2 * e + 1] += bfhi(v[e]); }
          }
          __syncwarp();
#pragma unroll
          for (int i = 8 * hh; i < 8 * hh + 8; i++) {
            const uint32_t a = stg + (i >> 2) * 8192 + (sx ^ ((i & 3) << 5));
            sts64f(a, acc[4 * i], acc[4 * i + 1]);
            sts64f(a + 1024, acc[4 * i + 2], acc[4 * i + 3]);
          }
        }
      } else {
#pragma unroll
        for (int i = 0; i < 8; i++)
          sts128(rcv - 16384 + (i >> 2) * 8192 + (i & 3) * 512, pack_bf16(acc[8 * i], acc[8 * i + 1]), pack_bf16(acc[8 * i + 2], acc[8 * i + 3]),
                 pack_bf16(acc[8 * i + 4], acc[8 * i + 5]), pack_bf16(acc[8 * i + 6], acc[8 * i + 7]));
      }
    }
#pragma unroll 1
    for (int kind = 1 + rank; kind < 2 + 2 * rank; kind++) half_tile(false, kind);
    staged();
  }
}

typedef CUresult (*EncodeFn)(CUtensorMap*, CUtensorMapDataType, cuuint32_t, void*, const cuuint64_t*, const cuuint64_t*, const cuuint32_t*,
                             const cuuint32_t*, CUtensorMapInterleave, CUtensorMapSwizzle, CUtensorMapL2promotion, CUtensorMapFloatOOBfill);

void map2d(EncodeFn enc, CUtensorMap* tm, const void* p, uint64_t cols, uint64_t rows, uint32_t bc, uint32_t br, CUtensorMapSwizzle sw) {
  cuuint64_t gd[2] = {cols, rows}, gs[1] = {cols * 2};
  cuuint32_t bd[2] = {bc, br}, es[2] = {1, 1};
  enc(tm, CU_TENSOR_MAP_DATA_TYPE_BFLOAT16, 2, (void*)p, gd, gs, bd, es, CU_TENSOR_MAP_INTERLEAVE_NONE, sw,
      sw == CU_TENSOR_MAP_SWIZZLE_128B ? CU_TENSOR_MAP_L2_PROMOTION_L2_128B : CU_TENSOR_MAP_L2_PROMOTION_NONE, CU_TENSOR_MAP_FLOAT_OOB_FILL_NONE);
}

}

extern "C" void kernel_launch(void* const* d_in, const int* in_sizes, int n_in, void* d_out, int out_size) {
  (void)in_sizes; (void)n_in; (void)out_size;
  static EncodeFn enc = nullptr;
  if (!enc) {
    cudaDriverEntryPointQueryResult qr;
    cudaGetDriverEntryPoint("cuTensorMapEncodeTiled", (void**)&enc, cudaEnableDefault, &qr);
    cudaFuncSetAttribute(fused_kernel, cudaFuncAttributeMaxDynamicSharedMemorySize, SMEM_BYTES);
  }
  Params prm;
  const CUtensorMapSwizzle S128 = CU_TENSOR_MAP_SWIZZLE_128B;
  map2d(enc, &prm.tx, d_in[0], kD, kS, 64, 64, S128);
  map2d(enc, &prm.tBre, d_in[3], kD, 576, 64, 72, S128);
  map2d(enc, &prm.tBim, d_in[4], kD, 576, 64, 72, S128);
  map2d(enc, &prm.tCre, d_in[5], 576, kD, 64, 64, S128);
  map2d(enc, &prm.tCim, d_in[6], 576, kD, 64, 64, S128);
  map2d(enc, &prm.tCre8, d_in[5], 576, kD, 8, 64, CU_TENSOR_MAP_SWIZZLE_NONE);
  map2d(enc, &prm.tCim8, d_in[6], 576, kD, 8, 64, CU_TENSOR_MAP_SWIZZLE_NONE);
  map2d(enc, &prm.tWg, d_in[10], kF, kD, 64, 64, S128);
  map2d(enc, &prm.tWu, d_in[11], kF, kD, 64, 64, S128);
  map2d(enc, &prm.tWd, d_in[12], kD, kF, 64, 64, S128);
  {
    cuuint64_t gd[4] = {kD, 2, 4, kS / 8}, gs[3] = {4 * kD * 4, kD * 4, 8 * kD * 4};
    cuuint32_t bd[4] = {32, 2, 4, 8}, es[4] = {1, 1, 1, 1};
    enc(&prm.tOut, CU_TENSOR_MAP_DATA_TYPE_FLOAT32, 4, d_out, gd, gs, bd, es, CU_TENSOR_MAP_INTERLEAVE_NONE, S128, CU_TENSOR_MAP_L2_PROMOTION_NONE,
        CU_TENSOR_MAP_FLOAT_OOB_FILL_NONE);
  }
  prm.lre = (const __nv_bfloat16*)d_in[1];
  prm.lim = (const __nv_bfloat16*)d_in[2];
  prm.bre = (const __nv_bfloat16*)d_in[3];
  prm.bim = (const __nv_bfloat16*)d_in[4];
  prm.cre = (const __nv_bfloat16*)d_in[5];
  prm.cim = (const __nv_bfloat16*)d_in[6];
  prm.wg = (const __nv_bfloat16*)d_in[10];
  prm.wu = (const __nv_bfloat16*)d_in[11];
  prm.wd = (const __nv_bfloat16*)d_in[12];
  prm.ldt = (const __nv_bfloat16*)d_in[7];
  prm.dskip = (const __nv_bfloat16*)d_in[8];
  prm.out = (float*)d_out;

  fused_kernel<<<128, 384, SMEM_BYTES, cudaStreamPerThread>>>(prm);
}
```

```cpp
#include <cuda_runtime.h>
#include <cuda.h>
#include <cuda_bf16.h>
#include <stdint.h>

namespace {

constexpr int kS = 2048, kD = 576, kF = 4608;
constexpr int SKEW = 4;
constexpr int PFD = 18;
constexpr int NST = 6;
constexpr uint32_t SLOT = 16384;
constexpr uint32_t OFF_H = NST * SLOT;
constexpr uint32_t HS_LBO = 1040;
constexpr uint32_t HS_BYTES = 18 * HS_LBO;
constexpr uint32_t OFF_DUMP = OFF_H + 65536 - HS_BYTES;
constexpr uint32_t OFF_STG = OFF_H + SLOT;
constexpr uint32_t OFF_HS = OFF_STG + 65536;
constexpr uint32_t OFF_BAR = OFF_H + 131072;
constexpr uint32_t OFF_CONST = OFF_BAR + 384;
constexpr uint32_t SMEM_BYTES = OFF_CONST + 4 * 576 + 384;
static_assert(SMEM_BYTES <= 232448 && OFF_HS + 2 * HS_BYTES <= OFF_BAR, "smem");

enum { B_FULL = 0, B_EMPTY = NST + 2, B_X = 2 * NST + 4, B_X8 = B_X + 8, B_BU  , B_RING = B_BU + 4, B_SCAN, B_HFREE, B_HSFULL, B_SFULL,
       B_SFREE = B_SFULL + 2, B_RFULL = B_SFREE + 2, B_RFREE = B_RFULL + 2, B_COUNT = B_RFREE + 2 };
static_assert(B_COUNT * 8 <= 384, "barriers");
enum { NB_SKEW = 1, NB_XDONE = 2  , NB_SCAN = 4, NB_DUMP = 5, NB_HFREE = 6, NB_STATS = 7 };
constexpr uint32_t HBLK0 = 0x07652CB4u, HBLK1 = 0x189A3DEFu;
constexpr uint32_t OFF_BU0 = SLOT, OFF_BU1 = OFF_H, OFF_BU2 = OFF_H + 65536 + 19456;
static_assert(OFF_BU1 + 5 * 9216 <= OFF_DUMP && OFF_BU2 >= OFF_DUMP + 2 * HS_BYTES && OFF_BU2 + 5 * 9216 <= OFF_BAR, "Bu tiles");

struct __align__(64) Params {
  CUtensorMap tx, tBre, tBim, tWg, tWu, tWd, tCre, tCim, tCre8, tCim8, tOut;
  const __nv_bfloat16 *lre, *lim, *bre, *bim, *cre, *cim, *ldt, *dskip, *wg, *wu, *wd;
  float* out;
};

__device__ unsigned g_epoch[128];
__device__ unsigned g_ready[16];
__device__ __align__(256) uint2 g_S[2][16][8][96];
__device__ __align__(128) uint8_t g_hs[128][2 * HS_BYTES];

__device__ __forceinline__ void wgmma_n72_rs_tb0(float (&d)[36], uint32_t a0, uint32_t a1, uint32_t a2, uint32_t a3, uint64_t db, int scale_d) {
  asm volatile("{\n.reg .pred p;\nsetp.ne.b32 p, %41, 0;\n"
    "wgmma.mma_async.sync.aligned.m64n72k16.f32.bf16.bf16 {"
    "%0, %1, %2, %3, %4, %5, %6, %7, %8, %9, %10, %11, %12, %13, %14, %15, "
    "%16, %17, %18, %19, %20, %21, %22, %23, %24, %25, %26, %27, %28, %29, %30, %31, "
    "%32, %33, %34, %35"
    "}, {%36, %37, %38, %39}, %40, p, 1, 1, 0;\n}\n"
    : "+f"(d[0]), "+f"(d[1]), "+f"(d[2]), "+f"(d[3]), "+f"(d[4]), "+f"(d[5]), "+f"(d[6]), "+f"(d[7]),
      "+f"(d[8]), "+f"(d[9]), "+f"(d[10]), "+f"(d[11]), "+f"(d[12]), "+f"(d[13]), "+f"(d[14]), "+f"(d[15]),
      "+f"(d[16]), "+f"(d[17]), "+f"(d[18]), "+f"(d[19]), "+f"(d[20]), "+f"(d[21]), "+f"(d[22]), "+f"(d[23]),
      "+f"(d[24]), "+f"(d[25]), "+f"(d[26]), "+f"(d[27]), "+f"(d[28]), "+f"(d[29]), "+f"(d[30]), "+f"(d[31]),
      "+f"(d[32]), "+f"(d[33]), "+f"(d[34]), "+f"(d[35])
    : "r"(a0), "r"(a1), "r"(a2), "r"(a3), "l"(db), "r"(scale_d));
}
__device__ __forceinline__ void wgmma_n128_rs_tb1(float (&d)[64], uint32_t a0, uint32_t a1, uint32_t a2, uint32_t a3, uint64_t db, int scale_d) {
  asm volatile("{\n.reg .pred p;\nsetp.ne.b32 p, %69, 0;\n"
    "wgmma.mma_async.sync.aligned.m64n128k16.f32.bf16.bf16 {"
    "%0, %1, %2, %3, %4, %5, %6, %7, %8, %9, %10, %11, %12, %13, %14, %15, "
    "%16, %17, %18, %19, %20, %21, %22, %23, %24, %25, %26, %27, %28, %29, %30, %31, "
    "%32, %33, %34, %35, %36, %37, %38, %39, %40, %41, %42, %43, %44, %45, %46, %47, "
    "%48, %49, %50, %51, %52, %53, %54, %55, %56, %57, %58, %59, %60, %61, %62, %63"
    "}, {%64, %65, %66, %67}, %68, p, 1, 1, 1;\n}\n"
    : "+f"(d[0]), "+f"(d[1]), "+f"(d[2]), "+f"(d[3]), "+f"(d[4]), "+f"(d[5]), "+f"(d[6]), "+f"(d[7]),
      "+f"(d[8]), "+f"(d[9]), "+f"(d[10]), "+f"(d[11]), "+f"(d[12]), "+f"(d[13]), "+f"(d[14]), "+f"(d[15]),
      "+f"(d[16]), "+f"(d[17]), "+f"(d[18]), "+f"(d[19]), "+f"(d[20]), "+f"(d[21]), "+f"(d[22]), "+f"(d[23]),
      "+f"(d[24]), "+f"(d[25]), "+f"(d[26]), "+f"(d[27]), "+f"(d[28]), "+f"(d[29]), "+f"(d[30]), "+f"(d[31]),
      "+f"(d[32]), "+f"(d[33]), "+f"(d[34]), "+f"(d[35]), "+f"(d[36]), "+f"(d[37]), "+f"(d[38]), "+f"(d[39]),
      "+f"(d[40]), "+f"(d[41]), "+f"(d[42]), "+f"(d[43]), "+f"(d[44]), "+f"(d[45]), "+f"(d[46]), "+f"(d[47]),
      "+f"(d[48]), "+f"(d[49]), "+f"(d[50]), "+f"(d[51]), "+f"(d[52]), "+f"(d[53]), "+f"(d[54]), "+f"(d[55]),
      "+f"(d[56]), "+f"(d[57]), "+f"(d[58]), "+f"(d[59]), "+f"(d[60]), "+f"(d[61]), "+f"(d[62]), "+f"(d[63])
    : "r"(a0), "r"(a1), "r"(a2), "r"(a3), "l"(db), "r"(scale_d));
}
__device__ __forceinline__ void wgmma_n128_ss_tb0(float (&d)[64], uint64_t da, uint64_t db, int scale_d) {
  asm volatile("{\n.reg .pred p;\nsetp.ne.b32 p, %66, 0;\n"
    "wgmma.mma_async.sync.aligned.m64n128k16.f32.bf16.bf16 {"
    "%0, %1, %2, %3, %4, %5, %6, %7, %8, %9, %10, %11, %12, %13, %14, %15, "
    "%16, %17, %18, %19, %20, %21, %22, %23, %24, %25, %26, %27, %28, %29, %30, %31, "
    "%32, %33, %34, %35, %36, %37, %38, %39, %40, %41, %42, %43, %44, %45, %46, %47, "
    "%48, %49, %50, %51, %52, %53, %54, %55, %56, %57, %58, %59, %60, %61, %62, %63"
    "}, %64, %65, p, 1, 1, 0, 0;\n}\n"
    : "+f"(d[0]), "+f"(d[1]), "+f"(d[2]), "+f"(d[3]), "+f"(d[4]), "+f"(d[5]), "+f"(d[6]), "+f"(d[7]),
      "+f"(d[8]), "+f"(d[9]), "+f"(d[10]), "+f"(d[11]), "+f"(d[12]), "+f"(d[13]), "+f"(d[14]), "+f"(d[15]),
      "+f"(d[16]), "+f"(d[17]), "+f"(d[18]), "+f"(d[19]), "+f"(d[20]), "+f"(d[21]), "+f"(d[22]), "+f"(d[23]),
      "+f"(d[24]), "+f"(d[25]), "+f"(d[26]), "+f"(d[27]), "+f"(d[28]), "+f"(d[29]), "+f"(d[30]), "+f"(d[31]),
      "+f"(d[32]), "+f"(d[33]), "+f"(d[34]), "+f"(d[35]), "+f"(d[36]), "+f"(d[37]), "+f"(d[38]), "+f"(d[39]),
      "+f"(d[40]), "+f"(d[41]), "+f"(d[42]), "+f"(d[43]), "+f"(d[44]), "+f"(d[45]), "+f"(d[46]), "+f"(d[47]),
      "+f"(d[48]), "+f"(d[49]), "+f"(d[50]), "+f"(d[51]), "+f"(d[52]), "+f"(d[53]), "+f"(d[54]), "+f"(d[55]),
      "+f"(d[56]), "+f"(d[57]), "+f"(d[58]), "+f"(d[59]), "+f"(d[60]), "+f"(d[61]), "+f"(d[62]), "+f"(d[63])
    : "l"(da), "l"(db), "r"(scale_d));
}
__device__ __forceinline__ void wgmma_n64_rs_tb1(float (&d)[32], uint32_t a0, uint32_t a1, uint32_t a2, uint32_t a3, uint64_t db, int scale_d) {
  asm volatile("{\n.reg .pred p;\nsetp.ne.b32 p, %37, 0;\n"
    "wgmma.mma_async.sync.aligned.m64n64k16.f32.bf16.bf16 {"
    "%0, %1, %2, %3, %4, %5, %6, %7, %8, %9, %10, %11, %12, %13, %14, %15, "
    "%16, %17, %18, %19, %20, %21, %22, %23, %24, %25, %26, %27, %28, %29, %30, %31"
    "}, {%32, %33, %34, %35}, %36, p, 1, 1, 1;\n}\n"
    : "+f"(d[0]), "+f"(d[1]), "+f"(d[2]), "+f"(d[3]), "+f"(d[4]), "+f"(d[5]), "+f"(d[6]), "+f"(d[7]),
      "+f"(d[8]), "+f"(d[9]), "+f"(d[10]), "+f"(d[11]), "+f"(d[12]), "+f"(d[13]), "+f"(d[14]), "+f"(d[15]),
      "+f"(d[16]), "+f"(d[17]), "+f"(d[18]), "+f"(d[19]), "+f"(d[20]), "+f"(d[21]), "+f"(d[22]), "+f"(d[23]),
      "+f"(d[24]), "+f"(d[25]), "+f"(d[26]), "+f"(d[27]), "+f"(d[28]), "+f"(d[29]), "+f"(d[30]), "+f"(d[31])
    : "r"(a0), "r"(a1), "r"(a2), "r"(a3), "l"(db), "r"(scale_d));
}
__device__ __forceinline__ void wgmma_n64_ss_tb0(float (&d)[32], uint64_t da, uint64_t db, int scale_d) {
  asm volatile("{\n.reg .pred p;\nsetp.ne.b32 p, %34, 0;\n"
    "wgmma.mma_async.sync.aligned.m64n64k16.f32.bf16.bf16 {"
    "%0, %1, %2, %3, %4, %5, %6, %7, %8, %9, %10, %11, %12, %13, %14, %15, "
    "%16, %17, %18, %19, %20, %21, %22, %23, %24, %25, %26, %27, %28, %29, %30, %31"
    "}, %32, %33, p, 1, 1, 0, 0;\n}\n"
    : "+f"(d[0]), "+f"(d[1]), "+f"(d[2]), "+f"(d[3]), "+f"(d[4]), "+f"(d[5]), "+f"(d[6]), "+f"(d[7]),
      "+f"(d[8]), "+f"(d[9]), "+f"(d[10]), "+f"(d[11]), "+f"(d[12]), "+f"(d[13]), "+f"(d[14]), "+f"(d[15]),
      "+f"(d[16]), "+f"(d[17]), "+f"(d[18]), "+f"(d[19]), "+f"(d[20]), "+f"(d[21]), "+f"(d[22]), "+f"(d[23]),
      "+f"(d[24]), "+f"(d[25]), "+f"(d[26]), "+f"(d[27]), "+f"(d[28]), "+f"(d[29]), "+f"(d[30]), "+f"(d[31])
    : "l"(da), "l"(db), "r"(scale_d));
}

__device__ __forceinline__ bool elect() {
  uint32_t p;
  asm volatile("{.reg .pred q; elect.sync _|q, 0xffffffff; selp.u32 %0,1,0,q;}" : "=r"(p));
  return p;
}
__device__ __forceinline__ void mbar_init(uint32_t bar, uint32_t cnt) { asm volatile("mbarrier.init.shared::cta.b64 [%0], %1;" ::"r"(bar), "r"(cnt) : "memory"); }
__device__ __forceinline__ void mbar_expect(uint32_t bar, uint32_t bytes) { asm volatile("mbarrier.arrive.expect_tx.shared::cta.b64 _, [%0], %1;" ::"r"(bar), "r"(bytes) : "memory"); }
__device__ __forceinline__ void mbar_arrive(uint32_t bar) { asm volatile("mbarrier.arrive.shared::cta.b64 _, [%0];" ::"r"(bar) : "memory"); }
__device__ __forceinline__ void mbar_arrive_cta(uint32_t bar, uint32_t cta) {
  asm volatile("{.reg .b32 ra; mapa.shared::cluster.u32 ra, %0, %1; mbarrier.arrive.shared::cluster.b64 _, [ra];}" ::"r"(bar), "r"(cta) : "memory");
}
__device__ __forceinline__ void mbar_wait(uint32_t bar, uint32_t parity) {
  asm volatile(
      "{\n.reg .pred p;\n.reg .u32 c, t;\n"
      "mbarrier.try_wait.parity.shared::cta.b64 p, [%0], %1;\n@p bra DONE;\n"
      "mov.u32 c, %%clock;\n"
      "LAB_WAIT:\nmbarrier.try_wait.parity.shared::cta.b64 p, [%0], %1;\n@p bra DONE;\n"
      "mov.u32 t, %%clock;\nsub.u32 t, t, c;\nsetp.lt.u32 p, t, 0x40000000;\n@p bra LAB_WAIT;\ntrap;\nDONE:\n}" ::"r"(bar), "r"(parity) : "memory");
}
__device__ __forceinline__ void bar_sync(int id, int n) { asm volatile("bar.sync %0, %1;" ::"r"(id), "r"(n) : "memory"); }
__device__ __forceinline__ void bar_arrive(int id, int n) { asm volatile("bar.arrive %0, %1;" ::"r"(id), "r"(n) : "memory"); }
__device__ __forceinline__ void wg_fence() { asm volatile("wgmma.fence.sync.aligned;" ::: "memory"); }
__device__ __forceinline__ void wg_commit() { asm volatile("wgmma.commit_group.sync.aligned;" ::: "memory"); }
template <int N> __device__ __forceinline__ void wg_wait() { asm volatile("wgmma.wait_group.sync.aligned %0;" ::"n"(N) : "memory"); }
__device__ __forceinline__ void tma2d(uint32_t dst, const CUtensorMap* tm, uint32_t bar, int c0, int c1) {
  asm volatile("cp.async.bulk.tensor.2d.shared::cluster.global.mbarrier::complete_tx::bytes [%0], [%1,{%3,%4}], [%2];" ::"r"(dst), "l"(tm), "r"(bar), "r"(c0), "r"(c1) : "memory");
}
__device__ __forceinline__ void tma2d_mc(uint32_t dst, const CUtensorMap* tm, uint32_t bar, int c0, int c1) {
  asm volatile("cp.async.bulk.tensor.2d.shared::cluster.global.mbarrier::complete_tx::bytes.multicast::cluster [%0], [%1,{%3,%4}], [%2], %5;" ::"r"(dst), "l"(tm), "r"(bar), "r"(c0), "r"(c1), "h"((uint16_t)3) : "memory");
}
__device__ __forceinline__ void l2_prefetch_line(const void* p) { asm volatile("prefetch.global.L2 [%0];" ::"l"(p)); }
__device__ __forceinline__ uint64_t desc(uint32_t lo, uint32_t hi) { return ((uint64_t)hi << 32) | lo; }
constexpr uint32_t DHI_SW128 = (1024 >> 4) | (1u << 30);
constexpr uint32_t DHI_NONE = (128 >> 4);
constexpr uint32_t DLO_HS = (HS_LBO >> 4) << 16;
constexpr uint32_t DLO_MN = (8192 >> 4) << 16;
constexpr uint32_t DLO_K = 1u << 16;
__device__ __forceinline__ float tanh_fast(float x) { float y; asm("tanh.approx.f32 %0, %1;" : "=f"(y) : "f"(x)); return y; }
__device__ __forceinline__ uint32_t pack_bf16(float lo, float hi) { uint32_t r; asm("cvt.rn.bf16x2.f32 %0, %1, %2;" : "=r"(r) : "f"(hi), "f"(lo)); return r; }
__device__ __forceinline__ float rbf(float x) { return __uint_as_float(pack_bf16(0.f, x)); }
__device__ __forceinline__ void mma16816(float (&c)[4], uint32_t a0, uint32_t a1, uint32_t a2, uint32_t a3, uint32_t b0, uint32_t b1) {
  asm volatile("mma.sync.aligned.m16n8k16.row.col.f32.bf16.bf16.f32 {%0,%1,%2,%3}, {%4,%5,%6,%7}, {%8,%9}, {%0,%1,%2,%3};"
               : "+f"(c[0]), "+f"(c[1]), "+f"(c[2]), "+f"(c[3]) : "r"(a0), "r"(a1), "r"(a2), "r"(a3), "r"(b0), "r"(b1));
}
__device__ __forceinline__ void sts128(uint32_t a, uint32_t x, uint32_t y, uint32_t z, uint32_t w) {
  asm volatile("st.shared.v4.b32 [%0], {%1,%2,%3,%4};" ::"r"(a), "r"(x), "r"(y), "r"(z), "r"(w) : "memory");
}
__device__ __forceinline__ void sts64f(uint32_t a, float x, float y) { asm volatile("st.shared.v2.f32 [%0], {%1,%2};" ::"r"(a), "f"(x), "f"(y) : "memory"); }
__device__ __forceinline__ float2 lds64f(uint32_t a) { float2 v; asm volatile("ld.shared.v2.f32 {%0,%1}, [%2];" : "=f"(v.x), "=f"(v.y) : "r"(a) : "memory"); return v; }
__device__ __forceinline__ uint32_t lds32(uint32_t a) { uint32_t v; asm volatile("ld.shared.b32 %0, [%1];" : "=r"(v) : "r"(a) : "memory"); return v; }
__device__ __forceinline__ void lds128(uint32_t a, uint32_t& x, uint32_t& y, uint32_t& z, uint32_t& w) {
  asm volatile("ld.shared.v4.b32 {%0,%1,%2,%3}, [%4];" : "=r"(x), "=r"(y), "=r"(z), "=r"(w) : "r"(a) : "memory");
}
__device__ __forceinline__ float bflo(uint32_t v) { return __uint_as_float(v << 16); }
__device__ __forceinline__ float bfhi(uint32_t v) { return __uint_as_float(v & 0xffff0000u); }
template <int N> __device__ __forceinline__ void keep(float (&a)[N]) {
#pragma unroll
  for (int i = 0; i < N; i++) asm volatile("" : "+f"(a[i])::"memory");
}

__global__ void __cluster_dims__(2, 1, 1) __launch_bounds__(384, 1) fused_kernel(const __grid_constant__ Params prm) {
  extern __shared__ __align__(1024) uint8_t smem[];
  const int warp = __shfl_sync(0xffffffffu, threadIdx.x >> 5, 0);
  const uint32_t sb0 = (uint32_t)__cvta_generic_to_shared(smem);
  const int j = blockIdx.x & 7, m = blockIdx.x >> 3, rank = j & 1;
  auto smem_base = [&]() { return __shfl_sync(0xffffffffu, sb0 + (threadIdx.x & 31), 0); };

  if (threadIdx.x == 320) asm volatile("prefetch.tensormap [%0];" ::"l"(&prm.tx) : "memory");
  if (warp == 0) {
    if (elect()) {
#pragma unroll
      for (int i = B_X8; i >= B_X; i--) mbar_init(sb0 + OFF_BAR + 8 * i, 1);
      asm volatile("fence.mbarrier_init.release.cluster;" ::: "memory");
    }
    __syncwarp();
  }
  asm volatile("barrier.cluster.arrive.relaxed.aligned;" ::: "memory");
  if (warp == 0) {
    const uint32_t xb = sb0 + OFF_BAR;
    if (elect()) {
      mbar_expect(xb + 8 * B_X8, 16384);
      tma2d(sb0, &prm.tx, xb + 8 * B_X8, 512, m * 128);
      tma2d(sb0 + 8192, &prm.tx, xb + 8 * B_X8, 512, m * 128 + 64);
#pragma unroll
      for (int i = 0; i < 4; i++) {
        mbar_expect(xb + 8 * (B_X + i), 16384);
        tma2d(sb0 + OFF_H + i * 16384, &prm.tx, xb + 8 * (B_X + i), i * 128, m * 128);
        tma2d(sb0 + OFF_H + i * 16384 + 8192, &prm.tx, xb + 8 * (B_X + i), i * 128 + 64, m * 128);
      }
    }
    __syncwarp();
  }
  asm volatile("barrier.cluster.wait.aligned;" ::: "memory");
  if (warp == 8 || warp == 9) {
    if (elect()) {
      if (warp == 8) {
#pragma unroll
        for (int i = 0; i < B_X; i++) mbar_init(sb0 + OFF_BAR + 8 * i, i >= B_EMPTY ? 2 : 1);
#pragma unroll
        for (int i = NST; i < NST + 2; i++) { mbar_arrive(sb0 + OFF_BAR + 8 * (B_FULL + i)); mbar_arrive(sb0 + OFF_BAR + 8 * (B_EMPTY + i)); mbar_arrive(sb0 + OFF_BAR + 8 * (B_EMPTY + i)); }
        __threadfence_block();
      } else {
#pragma unroll
        for (int i = B_X8 + 1; i < B_COUNT; i++) mbar_init(sb0 + OFF_BAR + 8 * i, (i >= B_SFULL && i < B_SFULL + 2) ? 4 : i == B_RING ? 2 : 1);
        if (sb0 & 1023) __trap();
      }
      asm volatile("fence.mbarrier_init.release.cluster;" ::: "memory");
    }
    __syncwarp();
  }
  if (warp == 0) {
    const uint32_t xb = sb0 + OFF_BAR;
    const bool e = elect();
#pragma unroll
    for (int i = 0; i < 4; i++) {
      const int kb = i * 2 + rank;
      if (e) { mbar_expect(xb + 8 * (B_X + 4 + i), 16384); tma2d_mc(sb0 + OFF_H + 65536 + kb * 8192, &prm.tx, xb + 8 * (B_X + 4 + i), kb * 64, m * 128 + 64); }
    }
    __syncwarp();
  }
  asm volatile("barrier.cluster.arrive.relaxed.aligned;\nbarrier.cluster.wait.aligned;" ::: "memory");

  if (warp >= 8) {
    asm volatile("setmaxnreg.dec.sync.aligned.u32 24;");
    if (warp == 8) {
      const uint32_t sb = smem_base(), bars = sb + OFF_BAR;
      bool e;
      int s = 0, nst = NST; uint32_t ph = 1;
      uint32_t dst, fb;
      auto acquire = [&](uint32_t bytes) {
        mbar_wait(bars + 8 * (B_EMPTY + s), ph);
        fb = bars + 8 * (B_FULL + s); dst = sb + s * SLOT;
        e = elect();
        if (e) mbar_expect(fb, bytes);
        if (++s == nst) { s = 0; ph ^= 1; }
      };
      auto box = [&](const CUtensorMap* t, uint32_t o, int a, int b) { if (e) tma2d(dst + o, t, fb, a, b); };
      const int lane = threadIdx.x & 31;
      const char* pf = lane < 8 ? (const char*)(lane & 4 ? prm.wu : prm.wg) + ((size_t)(m * 4 + (lane & 3)) * kF + j * 576) * 2
                     : lane < 12 ? (const char*)prm.wd + (size_t)j * 576 * 1152 + (m * 324 + (lane & 3)) * 128
                                 : (const char*)(lane & 1 ? prm.cim : prm.cre) + (size_t)blockIdx.x * 5184;
      int pk = 0, pleft = 81;
      auto prefetch = [&]() {
        if (pleft > 0) {
          if (lane < 14) l2_prefetch_line(pf);
          pf += lane < 8 ? (pk == 8 ? 128 - 8 * 64 * kF * 2 : 64 * kF * 2) : lane < 12 ? 512 : 64;
          pk = pk == 8 ? 0 : pk + 1;
          pleft--;
        }
      };
      mbar_wait(bars + 8 * B_X8, 0);
      e = elect();
#pragma unroll 1
      for (int kb = 0; kb < 8; kb++) {
        fb = bars + 8 * (B_BU + (kb >> 2));
        if (e) { if ((kb & 3) == 0) mbar_expect(fb, 4 * 9216); tma2d(sb + OFF_BU0 + kb * 9216, &prm.tBre, fb, kb * 64, j * 72); }
      }
      bar_sync(NB_XDONE, 160);
      fb = bars + 8 * (B_BU + 2);
      if (e) { mbar_expect(fb, 5 * 9216); tma2d(sb + OFF_BU1, &prm.tBre, fb, 512, j * 72); }
#pragma unroll 1
      for (int kb = 0; kb < 4; kb++) if (e) tma2d(sb + OFF_BU1 + (kb + 1) * 9216, &prm.tBim, fb, kb * 64, j * 72);
      for (int i = 0; i < PFD / 2; i++) prefetch();
      bar_sync(NB_XDONE + 1, 160);
      fb = bars + 8 * (B_BU + 3);
      if (e) mbar_expect(fb, 5 * 9216);
#pragma unroll 1
      for (int kb = 4; kb < 9; kb++) if (e) tma2d(sb + OFF_BU2 + (kb - 4) * 9216, &prm.tBim, fb, kb * 64, j * 72);
      for (int i = PFD / 2; i < PFD; i++) prefetch();
      mbar_wait(bars + 8 * B_RING, 0);
      for (int c = 0; c < 9; c++) {
        const int col = j * 576 + c * 64;
#pragma unroll 1
        for (int kb = 0; kb < 9; kb++) {
          if (kb == 7 && c == 0) nst = 8;
          if (kb == 4 && c == 3) nst = 7;
          if (kb == 3 && c == 7) nst = 6;
          acquire(16384); box(&prm.tWg, 0, col, kb * 64); box(&prm.tWu, 8192, col, kb * 64); prefetch();
        }
      }
      auto half_tile = [&](int n0) {
#pragma unroll 1
        for (int kp = 0; kp < 4; kp++) { acquire(16384); box(&prm.tWd, 0, n0, j * 576 + kp * 128); box(&prm.tWd, 8192, n0, j * 576 + kp * 128 + 64); }
        acquire(8192 + 2048); box(&prm.tWd, 0, n0, j * 576 + 512); box(&prm.tCre8, 8192, j * 72 + 64, n0); box(&prm.tCim8, 9216, j * 72 + 64, n0);
        acquire(16384); box(&prm.tCre, 0, j * 72, n0); box(&prm.tCim, 8192, j * 72, n0);
      };
      if (rank) half_tile(512);
#pragma unroll 1
      for (int t = 0; t < 4 - rank; t++) {
        const int n0 = ((rank ^ t ^ 1) & 1) * 256 + (((t >> 1) ^ (j >> 1)) & 1) * 128;
#pragma unroll 1
        for (int kb = 0; kb < 9; kb++) {
          if (kb == (rank ? 4 : 8)) nst = NST + 1;
          if (kb == 3 && t == 0 && rank) mbar_wait(bars + 8 * B_HFREE, 0);
          acquire(16384); box(&prm.tWd, 0, n0, j * 576 + kb * 64); box(&prm.tWd, 8192, n0 + 64, j * 576 + kb * 64);
        }
        if (t == 0) mbar_wait(bars + 8 * B_HFREE, 0);
        acquire(16384); box(&prm.tCre, 0, j * 72, n0); box(&prm.tCre, 8192, j * 72, n0 + 64);
        acquire(16384); box(&prm.tCim, 0, j * 72, n0); box(&prm.tCim, 8192, j * 72, n0 + 64);
        acquire(4096);
        box(&prm.tCre8, 0, j * 72 + 64, n0); box(&prm.tCre8, 1024, j * 72 + 64, n0 + 64);
        box(&prm.tCim8, 2048, j * 72 + 64, n0); box(&prm.tCim8, 3072, j * 72 + 64, n0 + 64);
      }
      if (!rank) half_tile(512);
      else {
#pragma unroll 1
        for (int hh = 0; hh < 2; hh++) half_tile(256 + (((j >> 1) ^ 1) & 1) * 128 + hh * 64);
      }
    } else {
      const uint32_t sb = smem_base(), bars = sb + OFF_BAR;
      const int p = min((int)threadIdx.x - 288, 71);
      if (threadIdx.x < 288 + 10) asm volatile("prefetch.tensormap [%0];" ::"l"(&prm.tBre + (threadIdx.x - 288)) : "memory");
      if (warp == 10) {
        const int l = threadIdx.x & 31;
        const char* q = (const char*)(l & 1 ? prm.bim : prm.bre) + (size_t)blockIdx.x * 5184;
        mbar_wait(bars + 8 * B_X8, 0);
#pragma unroll
        for (int i = 0; i < 3; i++) if (i * 16 + (l >> 1) < 42) l2_prefetch_line(q + min((i * 16 + (l >> 1)) * 128, 5183));
      }
      const unsigned epoch = *(volatile unsigned*)&g_epoch[blockIdx.x];
      {
        const int pg = j * 72 + p;
        const float lr = __bfloat162float(prm.lre[pg]), li = __bfloat162float(prm.lim[pg]);
        const float dt = rbf(expf(__bfloat162float(prm.ldt[pg])));
        const float ea = expf(dt * lr);
        float sn, cs;
        sincosf(dt * li, &sn, &cs);
        const float ar = ea * cs, ai = ea * sn;
        float br = ar, bi = ai;
#pragma unroll
        for (int k = 0; k < 6; k++) { const float t = br * br - bi * bi; bi = 2.f * br * bi; br = t; }
        const float nr = ar - 1.f, den = 4.f / (lr * lr + li * li);
        sts64f(sb + OFF_CONST + p * 8, ar, ai);
        sts64f(sb + OFF_CONST + 576 + p * 8, br, bi);
        sts64f(sb + OFF_CONST + 1152 + p * 8, (nr * lr + ai * li) * den, (ai * lr - nr * li) * den);
      }
      bar_sync(NB_DUMP, 352);
      {
        const int lane = threadIdx.x & 31;
        const int half = warp == 11 ? (lane >> 2) & 1 : warp - 9;
        const uint32_t cu = sb + OFF_CONST + (warp == 11 ? 32 + (lane & 3) : lane) * 16;
        uint32_t a0 = sb + OFF_DUMP + half * HS_BYTES + (warp == 11 ? 16 : lane >> 2) * HS_LBO + (lane & 3) * 4;
        asm volatile("" : "+r"(a0));
        const uint32_t di = warp == 11 ? HS_LBO : 8 * HS_LBO;
        float a[4], h[4] = {0.f, 0.f, 0.f, 0.f};
        auto ld4 = [&](uint32_t ad, float (&v)[4]) { asm volatile("ld.shared.v4.f32 {%0,%1,%2,%3}, [%4];" : "=f"(v[0]), "=f"(v[1]), "=f"(v[2]), "=f"(v[3]) : "r"(ad) : "memory"); };
        auto cfma = [&](const float (&c)[4], float r0, float i0, float r1, float i1) {
          const float n0 = fmaf(c[0], h[0], fmaf(-c[1], h[1], r0)), n1 = fmaf(c[2], h[2], fmaf(-c[3], h[3], r1));
          h[1] = fmaf(c[0], h[1], fmaf(c[1], h[0], i0)); h[3] = fmaf(c[2], h[3], fmaf(c[3], h[2], i1));
          h[0] = n0; h[2] = n1;
        };
        ld4(cu, a);
#pragma unroll 1
        for (uint32_t ad = a0; ad != a0 + 1024; ad += 64) {
          uint32_t wr[4], wi[4];
#pragma unroll
          for (int k = 0; k < 4; k++) { wr[k] = lds32(ad + k * 16); wi[k] = lds32(ad + di + k * 16); }
#pragma unroll
          for (int k = 0; k < 4; k++) cfma(a, bflo(wr[k]), bflo(wi[k]), bfhi(wr[k]), bfhi(wi[k]));
        }
        if (half == 0) sts128(cu + 1728, __float_as_uint(h[0]), __float_as_uint(h[1]), __float_as_uint(h[2]), __float_as_uint(h[3]));
        bar_sync(NB_SCAN, 96);
        if (half == 1 && m < 15) {
          float b[4], s1[4] = {h[0], h[1], h[2], h[3]};
          ld4(cu + 576, b); ld4(cu + 1728, h);
          cfma(b, s1[0], s1[1], s1[2], s1[3]);
          uint2* gp = &g_S[epoch & 1][m][j][(cu - sb - OFF_CONST) >> 3];
          asm volatile("st.relaxed.gpu.global.v2.b64 [%0], {%1,%2};" ::"l"(gp), "l"(~(((uint64_t)__float_as_uint(h[1]) << 32) | __float_as_uint(h[0]))),
                       "l"(~(((uint64_t)__float_as_uint(h[3]) << 32) | __float_as_uint(h[2]))) : "memory");
        }
        __syncwarp();
        g_S[(epoch & 1) ^ 1][m][j][p] = make_uint2(0u, 0u);
        {
          const float2 b = lds64f(sb + OFF_CONST + 576 + p * 8);
          const float br = b.x * b.x - b.y * b.y, bi = 2.f * b.x * b.y;
          float hr = 0.f, hi = 0.f;
          const uint2* sp = &g_S[epoch & 1][0][j][p];
#pragma unroll 1
          for (int left = m; left > 0; left -= 3, sp += 3 * 768) {
            uint32_t v[3][2];
            int spins = 0;
            uint32_t ok;
            do {
#pragma unroll
              for (int k = 0; k < 3; k++) {
                v[k][0] = v[k][1] = 0xffffffffu;
                if (k < left) asm volatile("ld.relaxed.gpu.global.v2.b32 {%0,%1}, [%2];" : "=r"(v[k][0]), "=r"(v[k][1]) : "l"(sp + k * 768) : "memory");
              }
              ok = min(min(min(v[0][0], v[0][1]), min(v[1][0], v[1][1])), min(v[2][0], v[2][1]));
              if (++spins > (1 << 22)) __trap();
            } while (ok == 0u);
#pragma unroll
            for (int k = 0; k < 3; k++)
              if (k < left) { const float nr = fmaf(br, hr, fmaf(-bi, hi, __uint_as_float(~v[k][0]))); hi = fmaf(br, hi, fmaf(bi, hr, __uint_as_float(~v[k][1]))); hr = nr; }
          }
          sts64f(sb + OFF_CONST + p * 8, hr, hi);
        }
        __syncwarp();
        bar_sync(NB_SCAN, 96);
        ld4(cu, h);
        uint32_t cr, ci, cn;
        {
          float b[4], s0[4];
          ld4(cu + 576, b); ld4(cu + 1728, s0);
          if (half == 1) cfma(b, s0[0], s0[1], s0[2], s0[3]);
          ld4(cu + 1152, b);
          cr = pack_bf16(b[0], b[2]); ci = pack_bf16(b[1], b[3]); cn = ci ^ 0x80008000u;
        }
        h[1] = -h[1]; h[3] = -h[3];
        __syncwarp();
#pragma unroll 1
        for (uint32_t ad = a0; ad != a0 + 1024; ad += 32) {
          uint32_t wr[2], wi[2];
#pragma unroll
          for (int k = 0; k < 2; k++) { wr[k] = lds32(ad + k * 16); wi[k] = lds32(ad + di + k * 16); }
#pragma unroll
          for (int k = 0; k < 2; k++) {
            const float n0 = fmaf(a[0], h[0], fmaf(a[1], h[1], bflo(wr[k]))), n1 = fmaf(a[2], h[2], fmaf(a[3], h[3], bfhi(wr[k])));
            h[1] = fmaf(a[0], h[1], fmaf(-a[1], h[0], -bflo(wi[k]))); h[3] = fmaf(a[2], h[3], fmaf(-a[3], h[2], -bfhi(wi[k])));
            h[0] = n0; h[2] = n1;
            const uint32_t hr = pack_bf16(h[0], h[2]), hn = pack_bf16(h[1], h[3]);
            uint32_t o0, o1;
            asm("{.reg .b32 t; mul.rn.bf16x2 t, %2, %4; fma.rn.bf16x2 %0, %1, %3, t;}" : "=r"(o0) : "r"(hr), "r"(hn), "r"(cr), "r"(ci));
            asm("{.reg .b32 t; mul.rn.bf16x2 t, %1, %4; fma.rn.bf16x2 %0, %2, %3, t;}" : "=r"(o1) : "r"(hr), "r"(hn), "r"(cr), "r"(cn));
            asm volatile("st.shared.b32 [%0], %1;" ::"r"(ad + k * 16), "r"(o0) : "memory");
            asm volatile("st.shared.b32 [%0], %1;" ::"r"(ad + di + k * 16), "r"(o1) : "memory");
          }
        }
        asm volatile("fence.proxy.async.shared::cta;" ::: "memory");
      }
      bar_sync(NB_SCAN, 96);
      const bool lead = elect();
      if (warp == 9) {
        if (lead) {
#pragma unroll 1
          for (uint32_t o = 0; o < 2 * HS_BYTES; o += 4 * HS_LBO) {
            asm volatile("cp.async.bulk.global.shared::cta.bulk_group [%0], [%1], %2;" ::"l"(&g_hs[blockIdx.x][o]), "r"(sb + OFF_DUMP + o), "r"(4 * HS_LBO) : "memory");
            asm volatile("cp.async.bulk.commit_group;\ncp.async.bulk.wait_group.read 0;" ::: "memory");
          }
          mbar_arrive(bars + 8 * B_SCAN);
        }
        __syncwarp();
      }
      if (warp == 9) {
        if (lead) {
          __threadfence();
          asm volatile("red.release.gpu.global.add.u32 [%0], 1;" ::"l"(&g_ready[m]) : "memory");
          g_epoch[blockIdx.x] = epoch + 1u;
          asm volatile("cp.async.bulk.wait_group 0;" ::: "memory");
        }
        __syncwarp();
        bar_sync(NB_HFREE, 288);
        if (lead) {
          mbar_arrive(bars + 8 * B_HFREE);
          mbar_expect(bars + 8 * B_HSFULL, 2 * HS_BYTES);
          asm volatile("cp.async.bulk.shared::cluster.global.mbarrier::complete_tx::bytes [%0], [%1], %2, [%3];" ::"r"(sb + OFF_HS),
                       "l"(&g_hs[blockIdx.x][0]), "r"(2 * HS_BYTES), "r"(bars + 8 * B_HSFULL) : "memory");
          for (int w = 0; w < 2; w++) mbar_arrive_cta(bars + 8 * (B_RFREE + w), rank ^ 1);
        }
        __syncwarp();
      } else {
        const int w = warp - 10;
        {
          const unsigned target = 8u * (epoch + 1u);
          int spins = 0;
          unsigned v;
          do {
            if (spins) __nanosleep(500);
            asm volatile("ld.relaxed.gpu.global.u32 %0, [%1];" : "=r"(v) : "l"(&g_ready[m]) : "memory");
            if (++spins > (1 << 21)) __trap();
          } while ((int)(v - target) < 0);
          asm volatile("fence.acq_rel.gpu;" ::: "memory");
          asm volatile("fence.proxy.async.global;" ::: "memory");
        }
        const uint32_t stg = sb + OFF_STG + w * 32768;
        const int nu = 5 + rank;
#pragma unroll 1
        for (int u = 0; u < nu; u++) {
          const int t = u - rank;
          if (t == 0 || t == 2) {
            if (elect()) mbar_expect(bars + 8 * (B_RFULL + w), 16384);
            mbar_wait(bars + 8 * (B_SFULL + w), u & 1);
            mbar_wait(bars + 8 * (B_RFREE + w), t >> 1);
            if (elect())
              asm volatile("{.reg .b32 ra, rb; mapa.shared::cluster.u32 ra, %0, %3; mapa.shared::cluster.u32 rb, %2, %3;\n"
                           "cp.async.bulk.shared::cluster.shared::cta.mbarrier::complete_tx::bytes [ra], [%1], 16384, [rb];}" ::"r"(stg + 16384),
                           "r"(stg), "r"(bars + 8 * (B_RFULL + w)), "r"(rank ^ 1) : "memory");
            mbar_wait(bars + 8 * (B_RFULL + w), t >> 1);
            if (elect()) mbar_arrive_cta(bars + 8 * (B_SFREE + w), rank ^ 1);
          } else {
            mbar_wait(bars + 8 * (B_SFULL + w), u & 1);
            const bool d = u == (rank ? 0 : 4), hf = rank && u >= 4;
            const int n0 = d ? 512 : rank * 256 + (((min(t, 3) >> 1) ^ (j >> 1)) & 1) * 128 + (u == 5 ? 64 : 0);
            const uint32_t src = d && !rank ? sb + (5 + w) * SLOT : stg + (u == 5 ? 16384 : 0);
            if (elect()) {
#pragma unroll 1
              for (int b = 0; b < (d || hf ? 2 : 4); b++) {
                asm volatile("cp.reduce.async.bulk.tensor.4d.global.shared::cta.add.tile.bulk_group [%0, {%1,%2,%2,%3}], [%4];" ::"l"(&prm.tOut), "r"(n0 + b * 32), "r"(0),
                             "r"(m * 16 + w * 8), "r"(src + b * 8192) : "memory");
                asm volatile("cp.async.bulk.commit_group;" ::: "memory");
                if (u < nu - 1) asm volatile("cp.async.bulk.wait_group.read 0;" ::: "memory");
              }
              if (u < 3) {
                asm volatile("cp.async.bulk.wait_group.read 0;" ::: "memory");
                mbar_arrive(bars + 8 * (B_SFREE + w));
                if (t == 1) mbar_arrive_cta(bars + 8 * (B_RFREE + w), rank ^ 1);
              }
              if (u == nu - 1) asm volatile("cp.async.bulk.wait_group.read 0;" ::: "memory");
            }
          }
          __syncwarp();
        }
      }
    }
  } else {
    asm volatile("setmaxnreg.inc.sync.aligned.u32 240;");
    const uint32_t sb = smem_base(), bars = sb + OFF_BAR;
    const int wg = warp >> 2, w4 = warp & 3;
    const int lane = threadIdx.x & 31, g = lane >> 2, q = lane & 3;
    const uint32_t hw = sb + OFF_H + wg * 65536;

    int s = 0, nst = NST; uint32_t ph = 0;
    auto release = [&](int st) { if (w4 == 0) { if (elect()) mbar_arrive(bars + 8 * (B_EMPTY + st)); } };
    const uint32_t dring = (sb & 0x3FFFF) >> 4;
    uint32_t dlo; int prev = 0;
    auto stage_begin = [&]() { mbar_wait(bars + 8 * (B_FULL + s), ph); dlo = dring + s * (SLOT >> 4); wg_fence(); };
    auto advance = [&]() { if (++s == nst) { s = 0; ph ^= 1; } };
    auto stage_end = [&](bool rel) {
      wg_commit();
      if (rel) { wg_wait<1>(); release(prev); }
      prev = s;
      advance();
    };

    uint32_t xa[144];
    uint32_t xr[18], dk[9];
    uint32_t rh[2], cc[2];
#pragma unroll
    for (int i = 0; i < 9; i++) dk[i] = __ldg((const uint32_t*)(prm.dskip + j * 72 + i * 8 + q * 2));
    {
      const int r = w4 * 16 + (lane & 7) + ((lane >> 3) & 1) * 8;
      const uint32_t ro = r * 128, cx = ((lane >> 4) ^ (lane & 7)) << 4;
      float s1[2][4] = {};
      auto load = [&](int kb, uint32_t base) {
#pragma unroll
        for (int kk = 0; kk < 4; kk++) {
          const int i = (kb * 4 + kk) * 4;
          asm volatile("ldmatrix.sync.aligned.m8n8.x4.shared.b16 {%0,%1,%2,%3}, [%4];"
                       : "=r"(xa[i]), "=r"(xa[i + 1]), "=r"(xa[i + 2]), "=r"(xa[i + 3]) : "r"(base + ro + (cx ^ (kk << 5))) : "memory");
        }
      };
      const uint32_t b0 = (g & 1) ? 0u : 0x3f803f80u, b1 = b0 ^ 0x3f803f80u;
      auto sums = [&](int kb) {
#pragma unroll
        for (int kk = 0; kk < 4; kk++) {
          const int i = (kb * 4 + kk) * 4;
          uint32_t a[4];
#pragma unroll
          for (int e = 0; e < 2; e++) {
            asm("mul.rn.bf16x2 %0, %1, %1;" : "=r"(a[e]) : "r"(xa[i + e]));
            asm("add.rn.bf16x2 %0, %1, %2;" : "=r"(a[2 + e]) : "r"(xa[i + e]), "r"(xa[i + 2 + e]));
            asm("fma.rn.bf16x2 %0, %1, %1, %0;" : "+r"(a[e]) : "r"(xa[i + 2 + e]));
          }
          mma16816(s1[kk & 1], a[0], a[1], a[2], a[3], b0, b1);
        }
      };
#pragma unroll
      for (int i = 0; i < 9; i++) {
        const int c8 = j * 9 + i, kb = c8 >> 3;
        xr[2 * i] = (kb < 8 ? hw + kb * 8192 : sb + wg * 8192) + (w4 * 16 + g) * 128 + (((c8 & 7) ^ g) << 4) + q * 4;
        asm volatile("" : "+r"(xr[2 * i]));
      }
      mbar_wait(bars + 8 * B_X8, 0);
      load(8, sb + wg * 8192);
      auto pin = [&]() { asm volatile("{.reg .pred p; .reg .u32 c, z; mov.u32 c, %clock; mov.u32 z, %ntid.y; setp.eq.u32 p, z, 0; @p st.shared.u32 [c], c;}" ::: "memory"); };
#pragma unroll
      for (int kp = 0; kp < 4; kp++) {
        mbar_wait(bars + 8 * (B_X + wg * 4 + kp), 0);
        load(2 * kp, hw + 2 * kp * 8192);
        load(2 * kp + 1, hw + (2 * kp + 1) * 8192);
        if (kp == 3) {
#pragma unroll
          for (int i = 0; i < 9; i++) { xr[2 * i + 1] = lds32(xr[2 * i] + 1024); xr[2 * i] = lds32(xr[2 * i]); }
        }
        if (kp == 0) sums(8); else { sums(2 * kp - 2); sums(2 * kp - 1); }
      }
      asm volatile("fence.proxy.async.shared::cta;" ::: "memory");
      bar_arrive(NB_XDONE + wg, 160);
      if (wg == 1) bar_arrive(NB_STATS, 256);
      pin();
      sums(6);
      sums(7);
      pin();
#pragma unroll
      for (int e = 0; e < 2; e++) {
        const float mu = (s1[0][2 * e + 1] + s1[1][2 * e + 1]) * (1.f / kD);
        const float var = fmaxf(fmaf(-mu, mu, (s1[0][2 * e] + s1[1][2 * e]) * (1.f / kD)), 0.f);
        float sd, r;
        asm("sqrt.approx.ftz.f32 %0, %1;" : "=f"(sd) : "f"(rbf(rbf(var) + 1e-5f)));
        asm("rcp.approx.ftz.f32 %0, %1;" : "=f"(r) : "f"(rbf(sd)));
        rh[e] = pack_bf16(0.5f * r, 0.5f * r);
        r = -mu * bfhi(rh[e]);
        cc[e] = pack_bf16(r, r);
      }
    }

    auto normalise = [&](int kb) {
#pragma unroll
      for (int i = 0; i < 16; i++) asm("fma.rn.bf16x2 %0, %0, %1, %2;" : "+r"(xa[16 * kb + (i >> 3) + 2 * (i & 7)]) : "r"(rh[i >> 3]), "r"(cc[i >> 3]));
    };
    {
      float ab[36];
      float* op = prm.out + (size_t)(m * 128 + wg * 64 + w4 * 16 + g) * kD + j * 72 + q * 2;
      auto residual = [&](int i) {
        asm volatile("add.rn.bf16x2 %0, %0, %0;" : "+r"(dk[i]));
#pragma unroll
        for (int e = 0; e < 2; e++) {
          uint32_t t;
          asm("fma.rn.bf16x2 %0, %1, %2, %3;" : "=r"(t) : "r"(xr[2 * i + e]), "r"(rh[e]), "r"(cc[e]));
          asm("fma.rn.bf16x2 %0, %0, %1, %2;" : "+r"(t) : "r"(dk[i]), "r"(xr[2 * i + e]));
          *(float2*)(op + e * 8 * kD + i * 8) = make_float2(bflo(t), bfhi(t));
        }
      };
      const uint32_t da = sb + OFF_DUMP + wg * HS_BYTES + (w4 * 16 + g) * 16 + q * 4;
      auto dump = [&](int im) {
#pragma unroll
        for (int i = 0; i < 18; i++)
          asm volatile("st.shared.b32 [%0], %1;" ::"r"(da + (i < 16 ? 8 * im + (i >> 1) : 16 + im) * HS_LBO + (i & 1) * 128), "r"(pack_bf16(ab[2 * i], ab[2 * i + 1])) : "memory");
      };
      auto bu = [&](int kb, uint32_t off) {
        wg_fence();
#pragma unroll
        for (int kk = 0; kk < 4; kk++) { const int i = (kb * 4 + kk) * 4; wgmma_n72_rs_tb0(ab, xa[i], xa[i + 1], xa[i + 2], xa[i + 3], desc((dring + (off >> 4) + kk * 2) + DLO_K, DHI_SW128), (kb | kk) != 0); }
        wg_commit();
      };
      normalise(0);
      if (wg == 0) {
#pragma unroll
        for (int kb = 1; kb < 9; kb++) normalise(kb);
        bar_sync(NB_STATS, 256);
      }
#pragma unroll
      for (int kb = 0; kb < 9; kb++) {
        if ((kb & 3) == 0) mbar_wait(bars + 8 * (B_BU + (kb >> 2)), 0);
        bu(kb, kb < 8 ? OFF_BU0 + kb * 9216 : OFF_BU1);
        if (kb < 8 && wg == 1) normalise(kb + 1);
      }
      wg_wait<0>();
      if (w4 == 0) { if (elect()) mbar_arrive(bars + 8 * B_RING); }
      keep(ab);
      dump(0);
#pragma unroll
      for (int kb = 0; kb < 9; kb++) {
        if (kb == 4) mbar_wait(bars + 8 * (B_BU + 3), 0);
        bu(kb, kb < 4 ? OFF_BU1 + (kb + 1) * 9216 : OFF_BU2 + (kb - 4) * 9216);
        residual(kb);
      }
      wg_wait<0>();
      keep(ab);
      dump(1);
      bar_arrive(NB_DUMP, 352);
    }

    float acc[64];
    {
      const uint32_t ha = sb + OFF_H + (threadIdx.x & 127) * 16, hblk = wg ? HBLK1 : HBLK0;
      auto glu = [&](int i) {
        return pack_bf16(fmaf(acc[32 + 2 * i], tanh_fast(acc[2 * i]), acc[32 + 2 * i]), fmaf(acc[33 + 2 * i], tanh_fast(acc[2 * i + 1]), acc[33 + 2 * i]));
      };
      for (int c = 0;; c++) {
        if (wg == 1) bar_sync(NB_SKEW, 256);
#pragma unroll
        for (int kb = 0; kb < 9; kb++) {
          if (kb == 7 && c == 0) nst = 8;
          if (kb == 4 && c == 3) nst = 7;
          if (kb == 3 && c == 7) nst = 6;
          stage_begin();
#pragma unroll
          for (int kk = 0; kk < 4; kk++) { const int i = (kb * 4 + kk) * 4; wgmma_n128_rs_tb1(acc, xa[i], xa[i + 1], xa[i + 2], xa[i + 3], desc((dlo + kk * 128) + DLO_MN, DHI_SW128), (kb | kk) != 0); }
          if (kb == SKEW - 1 && wg == 0) bar_arrive(NB_SKEW, 256);
          if (kb == 8 && (c == 3 || c == 4 || c == 7)) mbar_wait(bars + 8 * (c == 4 ? B_SCAN : c == 3 ? B_EMPTY + 7 : B_EMPTY + 6), c == 3);
          stage_end(kb > 0);
        }
        wg_wait<0>();
        release(prev);
        keep(acc);
        if (c == 8) break;
        const uint32_t hc = ha + ((hblk >> (4 * c)) & 15) * 8192;
#pragma unroll
        for (int i = 0; i < 4; i++) sts128(hc + i * 2048, glu(4 * i), glu(4 * i + 1), glu(4 * i + 2), glu(4 * i + 3));
      }
#pragma unroll
      for (int i = 0; i < 32; i++) lds128(ha + ((hblk >> (4 * (i >> 2))) & 15) * 8192 + (i & 3) * 2048, xa[4 * i], xa[4 * i + 1], xa[4 * i + 2], xa[4 * i + 3]);
#pragma unroll
      for (int i = 0; i < 16; i++) xa[128 + i] = glu(i);
      asm volatile("fence.proxy.async.shared::cta;" ::: "memory");
      bar_arrive(NB_HFREE, 288);
    }

    const uint32_t dhs = (((sb + OFF_HS + wg * HS_BYTES) & 0x3FFFF) >> 4) | DLO_HS;
    const int rp = (g >> 2) + 2 * (g & 3);
    const uint32_t so = w4 * 2048 + rp * 128 + (q & 1) * 8, sx = ((q >> 1) ^ rp) << 4;
    const uint32_t rcv = sb + OFF_STG + wg * 32768 + 16384 + w4 * 2048 + lane * 16;
    auto staged = [&]() {
      asm volatile("fence.proxy.async.shared::cta;" ::: "memory");
      __syncwarp();
      if (elect()) mbar_arrive(bars + 8 * (B_SFULL + wg));
    };
    auto half_tile = [&](const bool first, const int kind) {
      float a2[32];
      if (wg == 1) bar_sync(NB_SKEW, 256);
      const uint32_t ph0 = ph;
      uint32_t d4;
#pragma unroll
      for (int kp = 0; kp < 5; kp++) {
        stage_begin();
#pragma unroll
        for (int kk = 0; kk < (kp < 4 ? 8 : 4); kk++) { const int i = (kp * 8 + kk) * 4; wgmma_n64_rs_tb1(a2, xa[i], xa[i + 1], xa[i + 2], xa[i + 3], desc((dlo + kk * 128) + DLO_MN, DHI_SW128), (kp | kk) != 0); }
        if (kp == 1 && wg == 0) bar_arrive(NB_SKEW, 256);
        d4 = dlo;
        stage_end(kp > 0);
        if (kp == 0 && !first) staged();
      }
      if (first) mbar_wait(bars + 8 * B_HSFULL, 0);
      stage_begin();
#pragma unroll
      for (int kk = 0; kk < 8; kk++) wgmma_n64_ss_tb0(a2, desc(dhs + kk * (2 * HS_LBO >> 4), DHI_NONE), desc((dlo + (kk >> 2) * 512 + (kk & 3) * 2) + DLO_K, DHI_SW128), 1);
      wgmma_n64_ss_tb0(a2, desc(dhs + 8 * (2 * HS_LBO >> 4), DHI_NONE), desc((d4 + 512) | ((1024 >> 4) << 16), DHI_NONE), 1);
      wg_commit();
      if (!first) {
        if (kind == 1) mbar_wait(bars + 8 * (B_EMPTY + 5 + wg), ph0);
        if (kind == 2) { mbar_wait(bars + 8 * (B_SFREE + wg), 1); mbar_wait(bars + 8 * (B_RFULL + wg), 1); }
      }
      wg_wait<0>();
      release(prev); release(s); advance();
      keep(a2);
      if (!first && kind >= 2) {
#pragma unroll
        for (int i = 0; i < 4; i++) {
          uint32_t v[4];
          lds128(rcv + (kind & 1) * 8192 + i * 512, v[0], v[1], v[2], v[3]);
#pragma unroll
          for (int e = 0; e < 4; e++) { a2[8 * i + 2 * e] += bflo(v[e]); a2[8 * i + 2 * e + 1] += bfhi(v[e]); }
        }
        __syncwarp();
      }
      const uint32_t stg = (!first && kind == 1 ? sb + (5 + wg) * SLOT : sb + OFF_STG + wg * 32768 + (kind == 3 ? 16384 : 0)) + so;
#pragma unroll
      for (int i = 0; i < 8; i++) {
        const uint32_t a = stg + (i >> 2) * 8192 + (sx ^ ((i & 3) << 5));
        sts64f(a, a2[4 * i], a2[4 * i + 1]);
        sts64f(a + 1024, a2[4 * i + 2], a2[4 * i + 3]);
      }
    };
    if (rank) half_tile(true, 0);
    for (int t = 0; t < 4 - rank; t++) {
      if (wg == 1) bar_sync(NB_SKEW, 256);
#pragma unroll
      for (int kb = 0; kb < 9; kb++) {
        if ((kb == 4 && rank) || kb == 8) nst = NST + 1;
        stage_begin();
#pragma unroll
        for (int kk = 0; kk < 4; kk++) { const int i = (kb * 4 + kk) * 4; wgmma_n128_rs_tb1(acc, xa[i], xa[i + 1], xa[i + 2], xa[i + 3], desc((dlo + kk * 128) + DLO_MN, DHI_SW128), (kb | kk) != 0); }
        if (kb == SKEW - 1 && wg == 0) bar_arrive(NB_SKEW, 256);
        stage_end(kb > 0);
        if (kb == 0 && t + rank > 0) staged();
      }
      if (t == 0) mbar_wait(bars + 8 * B_HSFULL, 0);
      stage_begin();
#pragma unroll
      for (int kk = 0; kk < 4; kk++) wgmma_n128_ss_tb0(acc, desc(dhs + kk * (2 * HS_LBO >> 4), DHI_NONE), desc((dlo + kk * 2) + DLO_K, DHI_SW128), 1);
      stage_end(true);
      stage_begin();
#pragma unroll
      for (int kk = 0; kk < 4; kk++) wgmma_n128_ss_tb0(acc, desc(dhs + (4 + kk) * (2 * HS_LBO >> 4), DHI_NONE), desc((dlo + kk * 2) + DLO_K, DHI_SW128), 1);
      const int s_im = s;
      advance();
      stage_begin();
      wgmma_n128_ss_tb0(acc, desc(dhs + 8 * (2 * HS_LBO >> 4), DHI_NONE), desc(dlo | ((2048 >> 4) << 16), DHI_NONE), 1);
      stage_end(true);
      if (t + rank > 0) mbar_wait(bars + 8 * (B_SFREE + wg), (t + rank - 1) & 1);
      if (t & 1) mbar_wait(bars + 8 * (B_RFULL + wg), t >> 1);
      wg_wait<0>();
      release(s_im); release(prev);
      keep(acc);
      if (t & 1) {
        const uint32_t stg = sb + OFF_STG + wg * 32768 + so;
#pragma unroll
        for (int hh = 0; hh < 2; hh++) {
#pragma unroll
          for (int i = 4 * hh; i < 4 * hh + 4; i++) {
            uint32_t v[4];
            lds128(rcv + hh * 8192 + (i & 3) * 512, v[0], v[1], v[2], v[3]);
#pragma unroll
            for (int e = 0; e < 4; e++) { acc[8 * i + 2 * e] += bflo(v[e]); acc[8 * i + 2 * e + 1] += bfhi(v[e]); }
          }
          __syncwarp();
#pragma unroll
          for (int i = 8 * hh; i < 8 * hh + 8; i++) {
            const uint32_t a = stg + (i >> 2) * 8192 + (sx ^ ((i & 3) << 5));
            sts64f(a, acc[4 * i], acc[4 * i + 1]);
            sts64f(a + 1024, acc[4 * i + 2], acc[4 * i + 3]);
          }
        }
      } else {
#pragma unroll
        for (int i = 0; i < 8; i++)
          sts128(rcv - 16384 + (i >> 2) * 8192 + (i & 3) * 512, pack_bf16(acc[8 * i], acc[8 * i + 1]), pack_bf16(acc[8 * i + 2], acc[8 * i + 3]),
                 pack_bf16(acc[8 * i + 4], acc[8 * i + 5]), pack_bf16(acc[8 * i + 6], acc[8 * i + 7]));
      }
    }
#pragma unroll 1
    for (int kind = 1 + rank; kind < 2 + 2 * rank; kind++) half_tile(false, kind);
    staged();
  }
}

typedef CUresult (*EncodeFn)(CUtensorMap*, CUtensorMapDataType, cuuint32_t, void*, const cuuint64_t*, const cuuint64_t*, const cuuint32_t*,
                             const cuuint32_t*, CUtensorMapInterleave, CUtensorMapSwizzle, CUtensorMapL2promotion, CUtensorMapFloatOOBfill);

void map2d(EncodeFn enc, CUtensorMap* tm, const void* p, uint64_t cols, uint64_t rows, uint32_t bc, uint32_t br, CUtensorMapSwizzle sw) {
  cuuint64_t gd[2] = {cols, rows}, gs[1] = {cols * 2};
  cuuint32_t bd[2] = {bc, br}, es[2] = {1, 1};
  enc(tm, CU_TENSOR_MAP_DATA_TYPE_BFLOAT16, 2, (void*)p, gd, gs, bd, es, CU_TENSOR_MAP_INTERLEAVE_NONE, sw,
      sw == CU_TENSOR_MAP_SWIZZLE_128B ? CU_TENSOR_MAP_L2_PROMOTION_L2_128B : CU_TENSOR_MAP_L2_PROMOTION_NONE, CU_TENSOR_MAP_FLOAT_OOB_FILL_NONE);
}

}

extern "C" void kernel_launch(void* const* d_in, const int* in_sizes, int n_in, void* d_out, int out_size) {
  (void)in_sizes; (void)n_in; (void)out_size;
  static EncodeFn enc = nullptr;
  if (!enc) {
    cudaDriverEntryPointQueryResult qr;
    cudaGetDriverEntryPoint("cuTensorMapEncodeTiled", (void**)&enc, cudaEnableDefault, &qr);
    cudaFuncSetAttribute(fused_kernel, cudaFuncAttributeMaxDynamicSharedMemorySize, SMEM_BYTES);
  }
  Params prm;
  const CUtensorMapSwizzle S128 = CU_TENSOR_MAP_SWIZZLE_128B;
  map2d(enc, &prm.tx, d_in[0], kD, kS, 64, 64, S128);
  map2d(enc, &prm.tBre, d_in[3], kD, 576, 64, 72, S128);
  map2d(enc, &prm.tBim, d_in[4], kD, 576, 64, 72, S128);
  map2d(enc, &prm.tCre, d_in[5], 576, kD, 64, 64, S128);
  map2d(enc, &prm.tCim, d_in[6], 576, kD, 64, 64, S128);
  map2d(enc, &prm.tCre8, d_in[5], 576, kD, 8, 64, CU_TENSOR_MAP_SWIZZLE_NONE);
  map2d(enc, &prm.tCim8, d_in[6], 576, kD, 8, 64, CU_TENSOR_MAP_SWIZZLE_NONE);
  map2d(enc, &prm.tWg, d_in[10], kF, kD, 64, 64, S128);
  map2d(enc, &prm.tWu, d_in[11], kF, kD, 64, 64, S128);
  map2d(enc, &prm.tWd, d_in[12], kD, kF, 64, 64, S128);
  {
    cuuint64_t gd[4] = {kD, 2, 4, kS / 8}, gs[3] = {4 * kD * 4, kD * 4, 8 * kD * 4};
    cuuint32_t bd[4] = {32, 2, 4, 8}, es[4] = {1, 1, 1, 1};
    enc(&prm.tOut, CU_TENSOR_MAP_DATA_TYPE_FLOAT32, 4, d_out, gd, gs, bd, es, CU_TENSOR_MAP_INTERLEAVE_NONE, S128, CU_TENSOR_MAP_L2_PROMOTION_NONE,
        CU_TENSOR_MAP_FLOAT_OOB_FILL_NONE);
  }
  prm.lre = (const __nv_bfloat16*)d_in[1];
  prm.lim = (const __nv_bfloat16*)d_in[2];
  prm.bre = (const __nv_bfloat16*)d_in[3];
  prm.bim = (const __nv_bfloat16*)d_in[4];
  prm.cre = (const __nv_bfloat16*)d_in[5];
  prm.cim = (const __nv_bfloat16*)d_in[6];
  prm.wg = (const __nv_bfloat16*)d_in[10];
  prm.wu = (const __nv_bfloat16*)d_in[11];
  prm.wd = (const __nv_bfloat16*)d_in[12];
  prm.ldt = (const __nv_bfloat16*)d_in[7];
  prm.dskip = (const __nv_bfloat16*)d_in[8];
  prm.out = (float*)d_out;

  fused_kernel<<<128, 384, SMEM_BYTES, cudaStreamPerThread>>>(prm);
}
```

```cpp
#include <cuda_runtime.h>
#include <cuda.h>
#include <cuda_bf16.h>
#include <stdint.h>

namespace {

constexpr int kS = 2048, kD = 576, kF = 4608;
constexpr int SKEW = 4, SKEWB = 5;
constexpr int PFD = 18;
constexpr int NST = 6;
constexpr uint32_t SLOT = 16384;
constexpr uint32_t OFF_H = NST * SLOT;
constexpr uint32_t HS_LBO = 1040;
constexpr uint32_t HS_BYTES = 18 * HS_LBO;
constexpr uint32_t OFF_DUMP = OFF_H + 65536 - HS_BYTES;
constexpr uint32_t OFF_STG = OFF_H + 2 * SLOT;
constexpr uint32_t OFF_HS = OFF_STG + 65536;
constexpr uint32_t HS_MAIN = 16 * HS_LBO, HS_REM = 2 * HS_LBO;
constexpr uint32_t OFF_CONST = OFF_H + 131072;
constexpr uint32_t OFF_BAR = OFF_CONST + 4 * 576;
constexpr uint32_t SMEM_BYTES = OFF_BAR + 384 + 384;
static_assert(SMEM_BYTES <= 232448 && OFF_HS + 2 * HS_MAIN <= OFF_BAR, "smem");

enum { B_FULL = 0, B_EMPTY = NST + 2, B_X = 2 * NST + 4, B_X8 = B_X + 8, B_BU  , B_RING = B_BU + 4, B_SCAN, B_PARK, B_HFREE, B_HSFULL, B_SFULL,
       B_SFREE = B_SFULL + 2, B_RFULL = B_SFREE + 2, B_RFREE = B_RFULL + 2, B_COUNT = B_RFREE + 2 };
static_assert(B_COUNT * 8 <= 384, "barriers");
enum { NB_SKEW = 1, NB_XDONE = 2  , NB_SCAN = 4, NB_DUMP = 5, NB_HFREE = 6, NB_STATS = 7 };
constexpr uint32_t HBLK0 = 0x07652CB4u, HBLK1 = 0x189A3DEFu;
constexpr uint32_t OFF_BU0 = SLOT, OFF_BU1 = OFF_H, OFF_BU2 = OFF_H + 65536 + 19456;
static_assert(OFF_BU1 + 5 * 9216 <= OFF_DUMP && OFF_BU2 >= OFF_DUMP + 2 * HS_BYTES && OFF_BU2 + 5 * 9216 <= OFF_CONST, "Bu tiles");

struct __align__(64) Params {
  CUtensorMap tx, tBre, tBim, tWg, tWu, tWd, tCre, tCim, tCre8, tCim8, tOut;
  const __nv_bfloat16 *lre, *lim, *bre, *bim, *cre, *cim, *ldt, *dskip, *wg, *wu, *wd;
  float* out;
};

__device__ unsigned g_epoch[128];
__device__ unsigned g_ready[16];
__device__ __align__(256) uint2 g_S[2][16][8][96];
__device__ __align__(128) uint8_t g_hs[128][2 * HS_BYTES];

__device__ __forceinline__ void wgmma_n72_rs_tb0(float (&d)[36], uint32_t a0, uint32_t a1, uint32_t a2, uint32_t a3, uint64_t db, int scale_d) {
  asm volatile("{\n.reg .pred p;\nsetp.ne.b32 p, %41, 0;\n"
    "wgmma.mma_async.sync.aligned.m64n72k16.f32.bf16.bf16 {"
    "%0, %1, %2, %3, %4, %5, %6, %7, %8, %9, %10, %11, %12, %13, %14, %15, "
    "%16, %17, %18, %19, %20, %21, %22, %23, %24, %25, %26, %27, %28, %29, %30, %31, "
    "%32, %33, %34, %35"
    "}, {%36, %37, %38, %39}, %40, p, 1, 1, 0;\n}\n"
    : "+f"(d[0]), "+f"(d[1]), "+f"(d[2]), "+f"(d[3]), "+f"(d[4]), "+f"(d[5]), "+f"(d[6]), "+f"(d[7]),
      "+f"(d[8]), "+f"(d[9]), "+f"(d[10]), "+f"(d[11]), "+f"(d[12]), "+f"(d[13]), "+f"(d[14]), "+f"(d[15]),
      "+f"(d[16]), "+f"(d[17]), "+f"(d[18]), "+f"(d[19]), "+f"(d[20]), "+f"(d[21]), "+f"(d[22]), "+f"(d[23]),
      "+f"(d[24]), "+f"(d[25]), "+f"(d[26]), "+f"(d[27]), "+f"(d[28]), "+f"(d[29]), "+f"(d[30]), "+f"(d[31]),
      "+f"(d[32]), "+f"(d[33]), "+f"(d[34]), "+f"(d[35])
    : "r"(a0), "r"(a1), "r"(a2), "r"(a3), "l"(db), "r"(scale_d));
}
__device__ __forceinline__ void wgmma_n128_rs_tb1(float (&d)[64], uint32_t a0, uint32_t a1, uint32_t a2, uint32_t a3, uint64_t db, int scale_d) {
  asm volatile("{\n.reg .pred p;\nsetp.ne.b32 p, %69, 0;\n"
    "wgmma.mma_async.sync.aligned.m64n128k16.f32.bf16.bf16 {"
    "%0, %1, %2, %3, %4, %5, %6, %7, %8, %9, %10, %11, %12, %13, %14, %15, "
    "%16, %17, %18, %19, %20, %21, %22, %23, %24, %25, %26, %27, %28, %29, %30, %31, "
    "%32, %33, %34, %35, %36, %37, %38, %39, %40, %41, %42, %43, %44, %45, %46, %47, "
    "%48, %49, %50, %51, %52, %53, %54, %55, %56, %57, %58, %59, %60, %61, %62, %63"
    "}, {%64, %65, %66, %67}, %68, p, 1, 1, 1;\n}\n"
    : "+f"(d[0]), "+f"(d[1]), "+f"(d[2]), "+f"(d[3]), "+f"(d[4]), "+f"(d[5]), "+f"(d[6]), "+f"(d[7]),
      "+f"(d[8]), "+f"(d[9]), "+f"(d[10]), "+f"(d[11]), "+f"(d[12]), "+f"(d[13]), "+f"(d[14]), "+f"(d[15]),
      "+f"(d[16]), "+f"(d[17]), "+f"(d[18]), "+f"(d[19]), "+f"(d[20]), "+f"(d[21]), "+f"(d[22]), "+f"(d[23]),
      "+f"(d[24]), "+f"(d[25]), "+f"(d[26]), "+f"(d[27]), "+f"(d[28]), "+f"(d[29]), "+f"(d[30]), "+f"(d[31]),
      "+f"(d[32]), "+f"(d[33]), "+f"(d[34]), "+f"(d[35]), "+f"(d[36]), "+f"(d[37]), "+f"(d[38]), "+f"(d[39]),
      "+f"(d[40]), "+f"(d[41]), "+f"(d[42]), "+f"(d[43]), "+f"(d[44]), "+f"(d[45]), "+f"(d[46]), "+f"(d[47]),
      "+f"(d[48]), "+f"(d[49]), "+f"(d[50]), "+f"(d[51]), "+f"(d[52]), "+f"(d[53]), "+f"(d[54]), "+f"(d[55]),
      "+f"(d[56]), "+f"(d[57]), "+f"(d[58]), "+f"(d[59]), "+f"(d[60]), "+f"(d[61]), "+f"(d[62]), "+f"(d[63])
    : "r"(a0), "r"(a1), "r"(a2), "r"(a3), "l"(db), "r"(scale_d));
}
__device__ __forceinline__ void wgmma_n128_ss_tb0(float (&d)[64], uint64_t da, uint64_t db, int scale_d) {
  asm volatile("{\n.reg .pred p;\nsetp.ne.b32 p, %66, 0;\n"
    "wgmma.mma_async.sync.aligned.m64n128k16.f32.bf16.bf16 {"
    "%0, %1, %2, %3, %4, %5, %6, %7, %8, %9, %10, %11, %12, %13, %14, %15, "
    "%16, %17, %18, %19, %20, %21, %22, %23, %24, %25, %26, %27, %28, %29, %30, %31, "
    "%32, %33, %34, %35, %36, %37, %38, %39, %40, %41, %42, %43, %44, %45, %46, %47, "
    "%48, %49, %50, %51, %52, %53, %54, %55, %56, %57, %58, %59, %60, %61, %62, %63"
    "}, %64, %65, p, 1, 1, 0, 0;\n}\n"
    : "+f"(d[0]), "+f"(d[1]), "+f"(d[2]), "+f"(d[3]), "+f"(d[4]), "+f"(d[5]), "+f"(d[6]), "+f"(d[7]),
      "+f"(d[8]), "+f"(d[9]), "+f"(d[10]), "+f"(d[11]), "+f"(d[12]), "+f"(d[13]), "+f"(d[14]), "+f"(d[15]),
      "+f"(d[16]), "+f"(d[17]), "+f"(d[18]), "+f"(d[19]), "+f"(d[20]), "+f"(d[21]), "+f"(d[22]), "+f"(d[23]),
      "+f"(d[24]), "+f"(d[25]), "+f"(d[26]), "+f"(d[27]), "+f"(d[28]), "+f"(d[29]), "+f"(d[30]), "+f"(d[31]),
      "+f"(d[32]), "+f"(d[33]), "+f"(d[34]), "+f"(d[35]), "+f"(d[36]), "+f"(d[37]), "+f"(d[38]), "+f"(d[39]),
      "+f"(d[40]), "+f"(d[41]), "+f"(d[42]), "+f"(d[43]), "+f"(d[44]), "+f"(d[45]), "+f"(d[46]), "+f"(d[47]),
      "+f"(d[48]), "+f"(d[49]), "+f"(d[50]), "+f"(d[51]), "+f"(d[52]), "+f"(d[53]), "+f"(d[54]), "+f"(d[55]),
      "+f"(d[56]), "+f"(d[57]), "+f"(d[58]), "+f"(d[59]), "+f"(d[60]), "+f"(d[61]), "+f"(d[62]), "+f"(d[63])
    : "l"(da), "l"(db), "r"(scale_d));
}
__device__ __forceinline__ void wgmma_n64_rs_tb1(float (&d)[32], uint32_t a0, uint32_t a1, uint32_t a2, uint32_t a3, uint64_t db, int scale_d) {
  asm volatile("{\n.reg .pred p;\nsetp.ne.b32 p, %37, 0;\n"
    "wgmma.mma_async.sync.aligned.m64n64k16.f32.bf16.bf16 {"
    "%0, %1, %2, %3, %4, %5, %6, %7, %8, %9, %10, %11, %12, %13, %14, %15, "
    "%16, %17, %18, %19, %20, %21, %22, %23, %24, %25, %26, %27, %28, %29, %30, %31"
    "}, {%32, %33, %34, %35}, %36, p, 1, 1, 1;\n}\n"
    : "+f"(d[0]), "+f"(d[1]), "+f"(d[2]), "+f"(d[3]), "+f"(d[4]), "+f"(d[5]), "+f"(d[6]), "+f"(d[7]),
      "+f"(d[8]), "+f"(d[9]), "+f"(d[10]), "+f"(d[11]), "+f"(d[12]), "+f"(d[13]), "+f"(d[14]), "+f"(d[15]),
      "+f"(d[16]), "+f"(d[17]), "+f"(d[18]), "+f"(d[19]), "+f"(d[20]), "+f"(d[21]), "+f"(d[22]), "+f"(d[23]),
      "+f"(d[24]), "+f"(d[25]), "+f"(d[26]), "+f"(d[27]), "+f"(d[28]), "+f"(d[29]), "+f"(d[30]), "+f"(d[31])
    : "r"(a0), "r"(a1), "r"(a2), "r"(a3), "l"(db), "r"(scale_d));
}
__device__ __forceinline__ void wgmma_n64_ss_tb0(float (&d)[32], uint64_t da, uint64_t db, int scale_d) {
  asm volatile("{\n.reg .pred p;\nsetp.ne.b32 p, %34, 0;\n"
    "wgmma.mma_async.sync.aligned.m64n64k16.f32.bf16.bf16 {"
    "%0, %1, %2, %3, %4, %5, %6, %7, %8, %9, %10, %11, %12, %13, %14, %15, "
    "%16, %17, %18, %19, %20, %21, %22, %23, %24, %25, %26, %27, %28, %29, %30, %31"
    "}, %32, %33, p, 1, 1, 0, 0;\n}\n"
    : "+f"(d[0]), "+f"(d[1]), "+f"(d[2]), "+f"(d[3]), "+f"(d[4]), "+f"(d[5]), "+f"(d[6]), "+f"(d[7]),
      "+f"(d[8]), "+f"(d[9]), "+f"(d[10]), "+f"(d[11]), "+f"(d[12]), "+f"(d[13]), "+f"(d[14]), "+f"(d[15]),
      "+f"(d[16]), "+f"(d[17]), "+f"(d[18]), "+f"(d[19]), "+f"(d[20]), "+f"(d[21]), "+f"(d[22]), "+f"(d[23]),
      "+f"(d[24]), "+f"(d[25]), "+f"(d[26]), "+f"(d[27]), "+f"(d[28]), "+f"(d[29]), "+f"(d[30]), "+f"(d[31])
    : "l"(da), "l"(db), "r"(scale_d));
}

__device__ __forceinline__ bool elect() {
  uint32_t p;
  asm volatile("{.reg .pred q; elect.sync _|q, 0xffffffff; selp.u32 %0,1,0,q;}" : "=r"(p));
  return p;
}
__device__ __forceinline__ void mbar_init(uint32_t bar, uint32_t cnt) { asm volatile("mbarrier.init.shared::cta.b64 [%0], %1;" ::"r"(bar), "r"(cnt) : "memory"); }
__device__ __forceinline__ void mbar_expect(uint32_t bar, uint32_t bytes) { asm volatile("mbarrier.arrive.expect_tx.shared::cta.b64 _, [%0], %1;" ::"r"(bar), "r"(bytes) : "memory"); }
__device__ __forceinline__ void mbar_arrive(uint32_t bar) { asm volatile("mbarrier.arrive.shared::cta.b64 _, [%0];" ::"r"(bar) : "memory"); }
__device__ __forceinline__ void mbar_arrive_cta(uint32_t bar, uint32_t cta) {
  asm volatile("{.reg .b32 ra; mapa.shared::cluster.u32 ra, %0, %1; mbarrier.arrive.shared::cluster.b64 _, [ra];}" ::"r"(bar), "r"(cta) : "memory");
}
__device__ __forceinline__ void mbar_wait(uint32_t bar, uint32_t parity) {
  asm volatile(
      "{\n.reg .pred p;\n.reg .u32 c, t;\n"
      "mbarrier.try_wait.parity.shared::cta.b64 p, [%0], %1;\n@p bra DONE;\n"
      "mov.u32 c, %%clock;\n"
      "LAB_WAIT:\nmbarrier.try_wait.parity.shared::cta.b64 p, [%0], %1;\n@p bra DONE;\n"
      "mov.u32 t, %%clock;\nsub.u32 t, t, c;\nsetp.lt.u32 p, t, 0x40000000;\n@p bra LAB_WAIT;\ntrap;\nDONE:\n}" ::"r"(bar), "r"(parity) : "memory");
}
__device__ __forceinline__ void bar_sync(int id, int n) { asm volatile("bar.sync %0, %1;" ::"r"(id), "r"(n) : "memory"); }
__device__ __forceinline__ void bar_arrive(int id, int n) { asm volatile("bar.arrive %0, %1;" ::"r"(id), "r"(n) : "memory"); }
__device__ __forceinline__ void wg_fence() { asm volatile("wgmma.fence.sync.aligned;" ::: "memory"); }
__device__ __forceinline__ void wg_commit() { asm volatile("wgmma.commit_group.sync.aligned;" ::: "memory"); }
template <int N> __device__ __forceinline__ void wg_wait() { asm volatile("wgmma.wait_group.sync.aligned %0;" ::"n"(N) : "memory"); }
__device__ __forceinline__ void tma2d(uint32_t dst, const CUtensorMap* tm, uint32_t bar, int c0, int c1) {
  asm volatile("cp.async.bulk.tensor.2d.shared::cluster.global.mbarrier::complete_tx::bytes [%0], [%1,{%3,%4}], [%2];" ::"r"(dst), "l"(tm), "r"(bar), "r"(c0), "r"(c1) : "memory");
}
__device__ __forceinline__ void tma2d_mc(uint32_t dst, const CUtensorMap* tm, uint32_t bar, int c0, int c1) {
  asm volatile("cp.async.bulk.tensor.2d.shared::cluster.global.mbarrier::complete_tx::bytes.multicast::cluster [%0], [%1,{%3,%4}], [%2], %5;" ::"r"(dst), "l"(tm), "r"(bar), "r"(c0), "r"(c1), "h"((uint16_t)3) : "memory");
}
__device__ __forceinline__ void l2_prefetch_line(const void* p) { asm volatile("prefetch.global.L2 [%0];" ::"l"(p)); }
__device__ __forceinline__ uint64_t desc(uint32_t lo, uint32_t hi) { return ((uint64_t)hi << 32) | lo; }
constexpr uint32_t DHI_SW128 = (1024 >> 4) | (1u << 30);
constexpr uint32_t DHI_NONE = (128 >> 4);
constexpr uint32_t DLO_HS = (HS_LBO >> 4) << 16;
constexpr uint32_t DLO_MN = (8192 >> 4) << 16;
constexpr uint32_t DLO_K = 1u << 16;
__device__ __forceinline__ float tanh_fast(float x) { float y; asm("tanh.approx.f32 %0, %1;" : "=f"(y) : "f"(x)); return y; }
__device__ __forceinline__ uint32_t pack_bf16(float lo, float hi) { uint32_t r; asm("cvt.rn.bf16x2.f32 %0, %1, %2;" : "=r"(r) : "f"(hi), "f"(lo)); return r; }
__device__ __forceinline__ float rbf(float x) { return __uint_as_float(pack_bf16(0.f, x)); }
__device__ __forceinline__ void mma16816(float (&c)[4], uint32_t a0, uint32_t a1, uint32_t a2, uint32_t a3, uint32_t b0, uint32_t b1) {
  asm volatile("mma.sync.aligned.m16n8k16.row.col.f32.bf16.bf16.f32 {%0,%1,%2,%3}, {%4,%5,%6,%7}, {%8,%9}, {%0,%1,%2,%3};"
               : "+f"(c[0]), "+f"(c[1]), "+f"(c[2]), "+f"(c[3]) : "r"(a0), "r"(a1), "r"(a2), "r"(a3), "r"(b0), "r"(b1));
}
__device__ __forceinline__ void sts128(uint32_t a, uint32_t x, uint32_t y, uint32_t z, uint32_t w) {
  asm volatile("st.shared.v4.b32 [%0], {%1,%2,%3,%4};" ::"r"(a), "r"(x), "r"(y), "r"(z), "r"(w) : "memory");
}
__device__ __forceinline__ void sts64f(uint32_t a, float x, float y) { asm volatile("st.shared.v2.f32 [%0], {%1,%2};" ::"r"(a), "f"(x), "f"(y) : "memory"); }
__device__ __forceinline__ float2 lds64f(uint32_t a) { float2 v; asm volatile("ld.shared.v2.f32 {%0,%1}, [%2];" : "=f"(v.x), "=f"(v.y) : "r"(a) : "memory"); return v; }
__device__ __forceinline__ uint32_t lds32(uint32_t a) { uint32_t v; asm volatile("ld.shared.b32 %0, [%1];" : "=r"(v) : "r"(a) : "memory"); return v; }
__device__ __forceinline__ void lds128(uint32_t a, uint32_t& x, uint32_t& y, uint32_t& z, uint32_t& w) {
  asm volatile("ld.shared.v4.b32 {%0,%1,%2,%3}, [%4];" : "=r"(x), "=r"(y), "=r"(z), "=r"(w) : "r"(a) : "memory");
}
__device__ __forceinline__ float bflo(uint32_t v) { return __uint_as_float(v << 16); }
__device__ __forceinline__ float bfhi(uint32_t v) { return __uint_as_float(v & 0xffff0000u); }
template <int N> __device__ __forceinline__ void keep(float (&a)[N]) {
#pragma unroll
  for (int i = 0; i < N; i++) asm volatile("" : "+f"(a[i])::"memory");
}

__global__ void __cluster_dims__(2, 1, 1) __launch_bounds__(384, 1) fused_kernel(const __grid_constant__ Params prm) {
  extern __shared__ __align__(1024) uint8_t smem[];
  const int warp = __shfl_sync(0xffffffffu, threadIdx.x >> 5, 0);
  const uint32_t sb0 = (uint32_t)__cvta_generic_to_shared(smem);
  const int j = blockIdx.x & 7, m = blockIdx.x >> 3, rank = j & 1;
  auto smem_base = [&]() { return __shfl_sync(0xffffffffu, sb0 + (threadIdx.x & 31), 0); };

  if (threadIdx.x == 320) asm volatile("prefetch.tensormap [%0];" ::"l"(&prm.tx) : "memory");
  if (warp == 0) {
    if (elect()) {
#pragma unroll
      for (int i = B_X8; i >= B_X; i--) mbar_init(sb0 + OFF_BAR + 8 * i, 1);
      asm volatile("fence.mbarrier_init.release.cluster;" ::: "memory");
    }
    __syncwarp();
  }
  asm volatile("barrier.cluster.arrive.relaxed.aligned;" ::: "memory");
  if (warp == 0) {
    const uint32_t xb = sb0 + OFF_BAR;
    if (elect()) {
      mbar_expect(xb + 8 * B_X8, 16384);
      tma2d(sb0, &prm.tx, xb + 8 * B_X8, 512, m * 128);
      tma2d(sb0 + 8192, &prm.tx, xb + 8 * B_X8, 512, m * 128 + 64);
#pragma unroll
      for (int i = 0; i < 4; i++) {
        mbar_expect(xb + 8 * (B_X + i), 16384);
        tma2d(sb0 + OFF_H + i * 16384, &prm.tx, xb + 8 * (B_X + i), i * 128, m * 128);
        tma2d(sb0 + OFF_H + i * 16384 + 8192, &prm.tx, xb + 8 * (B_X + i), i * 128 + 64, m * 128);
      }
    }
    __syncwarp();
  }
  asm volatile("barrier.cluster.wait.aligned;" ::: "memory");
  if (warp == 8 || warp == 9) {
    if (elect()) {
      if (warp == 8) {
#pragma unroll
        for (int i = 0; i < B_X; i++) mbar_init(sb0 + OFF_BAR + 8 * i, i >= B_EMPTY ? 2 : 1);
#pragma unroll
        for (int i = NST; i < NST + 2; i++) { mbar_arrive(sb0 + OFF_BAR + 8 * (B_FULL + i)); mbar_arrive(sb0 + OFF_BAR + 8 * (B_EMPTY + i)); mbar_arrive(sb0 + OFF_BAR + 8 * (B_EMPTY + i)); }
        __threadfence_block();
      } else {
#pragma unroll
        for (int i = B_X8 + 1; i < B_COUNT; i++) mbar_init(sb0 + OFF_BAR + 8 * i, (i >= B_SFULL && i < B_SFULL + 2) ? 4 : i == B_RING ? 2 : 1);
        if (sb0 & 1023) __trap();
      }
      asm volatile("fence.mbarrier_init.release.cluster;" ::: "memory");
    }
    __syncwarp();
  }
  if (warp == 0) {
    const uint32_t xb = sb0 + OFF_BAR;
    const bool e = elect();
#pragma unroll
    for (int i = 0; i < 4; i++) {
      const int kb = i * 2 + rank;
      if (e) { mbar_expect(xb + 8 * (B_X + 4 + i), 16384); tma2d_mc(sb0 + OFF_H + 65536 + kb * 8192, &prm.tx, xb + 8 * (B_X + 4 + i), kb * 64, m * 128 + 64); }
    }
    __syncwarp();
  }
  asm volatile("barrier.cluster.arrive.relaxed.aligned;\nbarrier.cluster.wait.aligned;" ::: "memory");

  if (warp >= 8) {
    asm volatile("setmaxnreg.dec.sync.aligned.u32 24;");
    if (warp == 8) {
      const uint32_t sb = smem_base(), bars = sb + OFF_BAR;
      bool e;
      int s = 0, nst = NST; uint32_t ph = 1;
      uint32_t dst, fb;
      auto acquire = [&](uint32_t bytes) {
        mbar_wait(bars + 8 * (B_EMPTY + s), ph);
        fb = bars + 8 * (B_FULL + s); dst = sb + s * SLOT;
        e = elect();
        if (e) mbar_expect(fb, bytes);
        if (++s == nst) { s = 0; ph ^= 1; }
      };
      auto box = [&](const CUtensorMap* t, uint32_t o, int a, int b) { if (e) tma2d(dst + o, t, fb, a, b); };
      auto hs_rem = [&](uint32_t o) {
        if (e) asm volatile("cp.async.bulk.shared::cluster.global.mbarrier::complete_tx::bytes [%0], [%1], %2, [%3];" ::"r"(dst + o),
                            "l"(&g_hs[blockIdx.x][2 * HS_MAIN]), "r"(2 * HS_REM), "r"(fb) : "memory");
      };
      const int lane = threadIdx.x & 31;
      const char* pf = lane < 8 ? (const char*)(lane & 4 ? prm.wu : prm.wg) + ((size_t)(m * 4 + (lane & 3)) * kF + j * 576) * 2
                     : lane < 12 ? (const char*)prm.wd + (size_t)j * 576 * 1152 + (m * 324 + (lane & 3)) * 128
                                 : (const char*)(lane & 1 ? prm.cim : prm.cre) + (size_t)blockIdx.x * 5184;
      int pk = 0, pleft = 81;
      auto prefetch = [&]() {
        if (pleft > 0) {
          if (lane < 14) l2_prefetch_line(pf);
          pf += lane < 8 ? (pk == 8 ? 128 - 8 * 64 * kF * 2 : 64 * kF * 2) : lane < 12 ? 512 : 64;
          pk = pk == 8 ? 0 : pk + 1;
          pleft--;
        }
      };
      mbar_wait(bars + 8 * B_X8, 0);
      e = elect();
#pragma unroll 1
      for (int kb = 0; kb < 8; kb++) {
        fb = bars + 8 * (B_BU + (kb >> 2));
        if (e) { if ((kb & 3) == 0) mbar_expect(fb, 4 * 9216); tma2d(sb + OFF_BU0 + kb * 9216, &prm.tBre, fb, kb * 64, j * 72); }
      }
      bar_sync(NB_XDONE, 160);
      fb = bars + 8 * (B_BU + 2);
      if (e) { mbar_expect(fb, 5 * 9216); tma2d(sb + OFF_BU1, &prm.tBre, fb, 512, j * 72); }
#pragma unroll 1
      for (int kb = 0; kb < 4; kb++) if (e) tma2d(sb + OFF_BU1 + (kb + 1) * 9216, &prm.tBim, fb, kb * 64, j * 72);
      for (int i = 0; i < PFD / 2; i++) prefetch();
      bar_sync(NB_XDONE + 1, 160);
      fb = bars + 8 * (B_BU + 3);
      if (e) mbar_expect(fb, 5 * 9216);
#pragma unroll 1
      for (int kb = 4; kb < 9; kb++) if (e) tma2d(sb + OFF_BU2 + (kb - 4) * 9216, &prm.tBim, fb, kb * 64, j * 72);
      for (int i = PFD / 2; i < PFD; i++) prefetch();
      mbar_wait(bars + 8 * B_RING, 0);
      for (int c = 0; c < 9; c++) {
        const int col = j * 576 + c * 64;
#pragma unroll 1
        for (int kb = 0; kb < 9; kb++) {
          if (kb == 7 && c == 0) nst = 8;
          if (kb == 4 && c == 3) nst = 7;
          if (kb == 3 && c == 7) nst = 6;
          acquire(16384); box(&prm.tWg, 0, col, kb * 64); box(&prm.tWu, 8192, col, kb * 64); prefetch();
        }
      }
      auto half_tile = [&](int n0) {
#pragma unroll 1
        for (int kp = 0; kp < 4; kp++) { acquire(16384); box(&prm.tWd, 0, n0, j * 576 + kp * 128); box(&prm.tWd, 8192, n0, j * 576 + kp * 128 + 64); }
        acquire(8192 + 2048 + 2 * HS_REM); box(&prm.tWd, 0, n0, j * 576 + 512); box(&prm.tCre8, 8192, j * 72 + 64, n0); box(&prm.tCim8, 9216, j * 72 + 64, n0); hs_rem(10240);
        acquire(16384); box(&prm.tCre, 0, j * 72, n0); box(&prm.tCim, 8192, j * 72, n0);
      };
      mbar_wait(bars + 8 * B_PARK, 0);
      asm volatile("fence.proxy.async.global;" ::: "memory");
      if (rank) half_tile(512);
#pragma unroll 1
      for (int t = 0; t < 4 - rank; t++) {
        const int n0 = ((rank ^ t ^ 1) & 1) * 256 + (((t >> 1) ^ (j >> 1)) & 1) * 128;
#pragma unroll 1
        for (int kb = 0; kb < 9; kb++) {
          if (t == 0 && kb == (rank ? 4 : 8)) nst = NST + 1;
          if (t == 1 && kb == (rank ? 1 : 5)) nst = NST + 2;
          if (kb == 3 && t == 0 && rank) mbar_wait(bars + 8 * B_HFREE, 0);
          acquire(16384); box(&prm.tWd, 0, n0, j * 576 + kb * 64); box(&prm.tWd, 8192, n0 + 64, j * 576 + kb * 64);
        }
        if (t == 0) mbar_wait(bars + 8 * B_HFREE, 0);
        acquire(16384); box(&prm.tCre, 0, j * 72, n0); box(&prm.tCre, 8192, j * 72, n0 + 64);
        acquire(16384); box(&prm.tCim, 0, j * 72, n0); box(&prm.tCim, 8192, j * 72, n0 + 64);
        acquire(4096 + 2 * HS_REM); hs_rem(4096);
        box(&prm.tCre8, 0, j * 72 + 64, n0); box(&prm.tCre8, 1024, j * 72 + 64, n0 + 64);
        box(&prm.tCim8, 2048, j * 72 + 64, n0); box(&prm.tCim8, 3072, j * 72 + 64, n0 + 64);
      }
      if (!rank) half_tile(512);
      else {
#pragma unroll 1
        for (int hh = 0; hh < 2; hh++) half_tile(256 + (((j >> 1) ^ 1) & 1) * 128 + hh * 64);
      }
    } else {
      const uint32_t sb = smem_base(), bars = sb + OFF_BAR;
      const int p = min((int)threadIdx.x - 288, 71);
      if (threadIdx.x < 288 + 10) asm volatile("prefetch.tensormap [%0];" ::"l"(&prm.tBre + (threadIdx.x - 288)) : "memory");
      if (warp == 10) {
        const int l = threadIdx.x & 31;
        const char* q = (const char*)(l & 1 ? prm.bim : prm.bre) + (size_t)blockIdx.x * 5184;
        mbar_wait(bars + 8 * B_X8, 0);
#pragma unroll
        for (int i = 0; i < 3; i++) if (i * 16 + (l >> 1) < 42) l2_prefetch_line(q + min((i * 16 + (l >> 1)) * 128, 5183));
      }
      const unsigned epoch = *(volatile unsigned*)&g_epoch[blockIdx.x];
      {
        const int pg = j * 72 + p;
        const float lr = __bfloat162float(prm.lre[pg]), li = __bfloat162float(prm.lim[pg]);
        const float dt = rbf(expf(__bfloat162float(prm.ldt[pg])));
        const float ea = expf(dt * lr);
        float sn, cs;
        sincosf(dt * li, &sn, &cs);
        const float ar = ea * cs, ai = ea * sn;
        float br = ar, bi = ai;
#pragma unroll
        for (int k = 0; k < 6; k++) { const float t = br * br - bi * bi; bi = 2.f * br * bi; br = t; }
        const float nr = ar - 1.f, den = 4.f / (lr * lr + li * li);
        sts64f(sb + OFF_CONST + p * 8, ar, ai);
        sts64f(sb + OFF_CONST + 576 + p * 8, br, bi);
        sts64f(sb + OFF_CONST + 1152 + p * 8, (nr * lr + ai * li) * den, (ai * lr - nr * li) * den);
      }
      bar_sync(NB_DUMP, 352);
      {
        const int lane = threadIdx.x & 31;
        const int half = warp == 11 ? (lane >> 2) & 1 : warp - 9;
        const uint32_t cu = sb + OFF_CONST + (warp == 11 ? 32 + (lane & 3) : lane) * 16;
        uint32_t a0 = sb + OFF_DUMP + half * HS_BYTES + (warp == 11 ? 16 : lane >> 2) * HS_LBO + (lane & 3) * 4;
        asm volatile("" : "+r"(a0));
        const uint32_t di = warp == 11 ? HS_LBO : 8 * HS_LBO;
        float a[4], h[4] = {0.f, 0.f, 0.f, 0.f};
        auto ld4 = [&](uint32_t ad, float (&v)[4]) { asm volatile("ld.shared.v4.f32 {%0,%1,%2,%3}, [%4];" : "=f"(v[0]), "=f"(v[1]), "=f"(v[2]), "=f"(v[3]) : "r"(ad) : "memory"); };
        auto cfma = [&](const float (&c)[4], float r0, float i0, float r1, float i1) {
          const float n0 = fmaf(c[0], h[0], fmaf(-c[1], h[1], r0)), n1 = fmaf(c[2], h[2], fmaf(-c[3], h[3], r1));
          h[1] = fmaf(c[0], h[1], fmaf(c[1], h[0], i0)); h[3] = fmaf(c[2], h[3], fmaf(c[3], h[2], i1));
          h[0] = n0; h[2] = n1;
        };
        ld4(cu, a);
#pragma unroll 1
        for (uint32_t ad = a0; ad != a0 + 1024; ad += 64) {
          uint32_t wr[4], wi[4];
#pragma unroll
          for (int k = 0; k < 4; k++) { wr[k] = lds32(ad + k * 16); wi[k] = lds32(ad + di + k * 16); }
#pragma unroll
          for (int k = 0; k < 4; k++) cfma(a, bflo(wr[k]), bflo(wi[k]), bfhi(wr[k]), bfhi(wi[k]));
        }
        if (half == 0) sts128(cu + 1728, __float_as_uint(h[0]), __float_as_uint(h[1]), __float_as_uint(h[2]), __float_as_uint(h[3]));
        bar_sync(NB_SCAN, 96);
        if (half == 1 && m < 15) {
          float b[4], s1[4] = {h[0], h[1], h[2], h[3]};
          ld4(cu + 576, b); ld4(cu + 1728, h);
          cfma(b, s1[0], s1[1], s1[2], s1[3]);
          uint2* gp = &g_S[epoch & 1][m][j][(cu - sb - OFF_CONST) >> 3];
          asm volatile("st.relaxed.gpu.global.v2.b64 [%0], {%1,%2};" ::"l"(gp), "l"(~(((uint64_t)__float_as_uint(h[1]) << 32) | __float_as_uint(h[0]))),
                       "l"(~(((uint64_t)__float_as_uint(h[3]) << 32) | __float_as_uint(h[2]))) : "memory");
        }
        __syncwarp();
        g_S[(epoch & 1) ^ 1][m][j][p] = make_uint2(0u, 0u);
        {
          const float2 b = lds64f(sb + OFF_CONST + 576 + p * 8);
          const float br = b.x * b.x - b.y * b.y, bi = 2.f * b.x * b.y;
          float hr = 0.f, hi = 0.f;
          const uint2* sp = &g_S[epoch & 1][0][j][p];
#pragma unroll 1
          for (int left = m; left > 0; left -= 3, sp += 3 * 768) {
            uint32_t v[3][2];
            int spins = 0;
            uint32_t ok;
            do {
#pragma unroll
              for (int k = 0; k < 3; k++) {
                v[k][0] = v[k][1] = 0xffffffffu;
                if (k < left) asm volatile("ld.relaxed.gpu.global.v2.b32 {%0,%1}, [%2];" : "=r"(v[k][0]), "=r"(v[k][1]) : "l"(sp + k * 768) : "memory");
              }
              ok = min(min(min(v[0][0], v[0][1]), min(v[1][0], v[1][1])), min(v[2][0], v[2][1]));
              if (++spins > (1 << 22)) __trap();
            } while (ok == 0u);
#pragma unroll
            for (int k = 0; k < 3; k++)
              if (k < left) { const float nr = fmaf(br, hr, fmaf(-bi, hi, __uint_as_float(~v[k][0]))); hi = fmaf(br, hi, fmaf(bi, hr, __uint_as_float(~v[k][1]))); hr = nr; }
          }
          sts64f(sb + OFF_CONST + p * 8, hr, hi);
        }
        __syncwarp();
        bar_sync(NB_SCAN, 96);
        ld4(cu, h);
        uint32_t cr, ci, cn;
        {
          float b[4], s0[4];
          ld4(cu + 576, b); ld4(cu + 1728, s0);
          if (half == 1) cfma(b, s0[0], s0[1], s0[2], s0[3]);
          ld4(cu + 1152, b);
          cr = pack_bf16(b[0], b[2]); ci = pack_bf16(b[1], b[3]); cn = ci ^ 0x80008000u;
        }
        h[1] = -h[1]; h[3] = -h[3];
        __syncwarp();
#pragma unroll 1
        for (uint32_t ad = a0; ad != a0 + 1024; ad += 32) {
          uint32_t wr[2], wi[2];
#pragma unroll
          for (int k = 0; k < 2; k++) { wr[k] = lds32(ad + k * 16); wi[k] = lds32(ad + di + k * 16); }
#pragma unroll
          for (int k = 0; k < 2; k++) {
            const float n0 = fmaf(a[0], h[0], fmaf(a[1], h[1], bflo(wr[k]))), n1 = fmaf(a[2], h[2], fmaf(a[3], h[3], bfhi(wr[k])));
            h[1] = fmaf(a[0], h[1], fmaf(-a[1], h[0], -bflo(wi[k]))); h[3] = fmaf(a[2], h[3], fmaf(-a[3], h[2], -bfhi(wi[k])));
            h[0] = n0; h[2] = n1;
            const uint32_t hr = pack_bf16(h[0], h[2]), hn = pack_bf16(h[1], h[3]);
            uint32_t o0, o1;
            asm("{.reg .b32 t; mul.rn.bf16x2 t, %2, %4; fma.rn.bf16x2 %0, %1, %3, t;}" : "=r"(o0) : "r"(hr), "r"(hn), "r"(cr), "r"(ci));
            asm("{.reg .b32 t; mul.rn.bf16x2 t, %1, %4; fma.rn.bf16x2 %0, %2, %3, t;}" : "=r"(o1) : "r"(hr), "r"(hn), "r"(cr), "r"(cn));
            asm volatile("st.shared.b32 [%0], %1;" ::"r"(ad + k * 16), "r"(o0) : "memory");
            asm volatile("st.shared.b32 [%0], %1;" ::"r"(ad + di + k * 16), "r"(o1) : "memory");
          }
        }
        asm volatile("fence.proxy.async.shared::cta;" ::: "memory");
      }
      bar_sync(NB_SCAN, 96);
      const bool lead = elect();
      if (warp == 9) {
        if (lead) {
#pragma unroll 1
          for (int i = 0; i < 10; i++) {
            const int w = i & 1, c4 = i >> 1;
            asm volatile("cp.async.bulk.global.shared::cta.bulk_group [%0], [%1], %2;" ::"l"(&g_hs[blockIdx.x][c4 < 4 ? w * HS_MAIN + c4 * 4 * HS_LBO : 2 * HS_MAIN + w * HS_REM]),
                         "r"(sb + OFF_DUMP + w * HS_BYTES + c4 * 4 * HS_LBO), "r"(c4 < 4 ? 4 * HS_LBO : HS_REM) : "memory");
            asm volatile("cp.async.bulk.commit_group;\ncp.async.bulk.wait_group.read 0;" ::: "memory");
          }
          mbar_arrive(bars + 8 * B_SCAN);
        }
        __syncwarp();
      }
      if (warp == 9) {
        if (lead) {
          __threadfence();
          asm volatile("red.release.gpu.global.add.u32 [%0], 1;" ::"l"(&g_ready[m]) : "memory");
          g_epoch[blockIdx.x] = epoch + 1u;
          asm volatile("cp.async.bulk.wait_group 0;" ::: "memory");
          mbar_arrive(bars + 8 * B_PARK);
        }
        __syncwarp();
        bar_sync(NB_HFREE, 288);
        if (lead) {
          mbar_arrive(bars + 8 * B_HFREE);
          mbar_expect(bars + 8 * B_HSFULL, 2 * HS_MAIN);
          asm volatile("cp.async.bulk.shared::cluster.global.mbarrier::complete_tx::bytes [%0], [%1], %2, [%3];" ::"r"(sb + OFF_HS),
                       "l"(&g_hs[blockIdx.x][0]), "r"(2 * HS_MAIN), "r"(bars + 8 * B_HSFULL) : "memory");
          for (int w = 0; w < 2; w++) mbar_arrive_cta(bars + 8 * (B_RFREE + w), rank ^ 1);
        }
        __syncwarp();
      } else {
        const int w = warp - 10;
        {
          const unsigned target = 8u * (epoch + 1u);
          int spins = 0;
          unsigned v;
          do {
            if (spins) __nanosleep(500);
            asm volatile("ld.relaxed.gpu.global.u32 %0, [%1];" : "=r"(v) : "l"(&g_ready[m]) : "memory");
            if (++spins > (1 << 21)) __trap();
          } while ((int)(v - target) < 0);
          asm volatile("fence.acq_rel.gpu;" ::: "memory");
          asm volatile("fence.proxy.async.global;" ::: "memory");
        }
        const uint32_t stg = sb + OFF_STG + w * 32768;
        const int nu = 5 + rank;
#pragma unroll 1
        for (int u = 0; u < nu; u++) {
          const int t = u - rank;
          if (t == 0 || t == 2) {
            if (elect()) mbar_expect(bars + 8 * (B_RFULL + w), 16384);
            mbar_wait(bars + 8 * (B_SFULL + w), u & 1);
            mbar_wait(bars + 8 * (B_RFREE + w), t >> 1);
            if (elect())
              asm volatile("{.reg .b32 ra, rb; mapa.shared::cluster.u32 ra, %0, %3; mapa.shared::cluster.u32 rb, %2, %3;\n"
                           "cp.async.bulk.shared::cluster.shared::cta.mbarrier::complete_tx::bytes [ra], [%1], 16384, [rb];}" ::"r"(stg + 16384),
                           "r"(stg), "r"(bars + 8 * (B_RFULL + w)), "r"(rank ^ 1) : "memory");
            mbar_wait(bars + 8 * (B_RFULL + w), t >> 1);
            if (elect()) mbar_arrive_cta(bars + 8 * (B_SFREE + w), rank ^ 1);
          } else {
            mbar_wait(bars + 8 * (B_SFULL + w), u & 1);
            const bool d = u == (rank ? 0 : 4), hf = rank && u >= 4;
            const int n0 = d ? 512 : rank * 256 + (((min(t, 3) >> 1) ^ (j >> 1)) & 1) * 128 + (u == 5 ? 64 : 0);
            const uint32_t src = d && !rank ? sb + (1 + w) * SLOT : stg + (u == 5 ? 16384 : 0);
            if (elect()) {
#pragma unroll 1
              for (int b = 0; b < (d || hf ? 2 : 4); b++) {
                asm volatile("cp.reduce.async.bulk.tensor.4d.global.shared::cta.add.tile.bulk_group [%0, {%1,%2,%2,%3}], [%4];" ::"l"(&prm.tOut), "r"(n0 + b * 32), "r"(0),
                             "r"(m * 16 + w * 8), "r"(src + b * 8192) : "memory");
                asm volatile("cp.async.bulk.commit_group;" ::: "memory");
                if (u < nu - 1) asm volatile("cp.async.bulk.wait_group.read 0;" ::: "memory");
              }
              if (u < 3) {
                asm volatile("cp.async.bulk.wait_group.read 0;" ::: "memory");
                mbar_arrive(bars + 8 * (B_SFREE + w));
                if (t == 1) mbar_arrive_cta(bars + 8 * (B_RFREE + w), rank ^ 1);
              }
              if (u == nu - 1) asm volatile("cp.async.bulk.wait_group.read 0;" ::: "memory");
            }
          }
          __syncwarp();
        }
      }
    }
  } else {
    asm volatile("setmaxnreg.inc.sync.aligned.u32 240;");
    const uint32_t sb = smem_base(), bars = sb + OFF_BAR;
    const int wg = warp >> 2, w4 = warp & 3;
    const int lane = threadIdx.x & 31, g = lane >> 2, q = lane & 3;
    const uint32_t hw = sb + OFF_H + wg * 65536;

    int s = 0, nst = NST; uint32_t ph = 0;
    auto release = [&](int st) { if (w4 == 0) { if (elect()) mbar_arrive(bars + 8 * (B_EMPTY + st)); } };
    const uint32_t dring = (sb & 0x3FFFF) >> 4;
    uint32_t dlo; int prev = 0;
    auto stage_begin = [&]() { mbar_wait(bars + 8 * (B_FULL + s), ph); dlo = dring + s * (SLOT >> 4); wg_fence(); };
    auto advance = [&]() { if (++s == nst) { s = 0; ph ^= 1; } };
    auto stage_end = [&](bool rel) {
      wg_commit();
      if (rel) { wg_wait<1>(); release(prev); }
      prev = s;
      advance();
    };

    uint32_t xa[144];
    uint32_t xr[18], dk[9];
    uint32_t rh[2], cc[2];
#pragma unroll
    for (int i = 0; i < 9; i++) dk[i] = __ldg((const uint32_t*)(prm.dskip + j * 72 + i * 8 + q * 2));
    {
      const int r = w4 * 16 + (lane & 7) + ((lane >> 3) & 1) * 8;
      const uint32_t ro = r * 128, cx = ((lane >> 4) ^ (lane & 7)) << 4;
      float s1[2][4] = {};
      auto load = [&](int kb, uint32_t base) {
#pragma unroll
        for (int kk = 0; kk < 4; kk++) {
          const int i = (kb * 4 + kk) * 4;
          asm volatile("ldmatrix.sync.aligned.m8n8.x4.shared.b16 {%0,%1,%2,%3}, [%4];"
                       : "=r"(xa[i]), "=r"(xa[i + 1]), "=r"(xa[i + 2]), "=r"(xa[i + 3]) : "r"(base + ro + (cx ^ (kk << 5))) : "memory");
        }
      };
      const uint32_t b0 = (g & 1) ? 0u : 0x3f803f80u, b1 = b0 ^ 0x3f803f80u;
      auto sums = [&](int kb) {
#pragma unroll
        for (int kk = 0; kk < 4; kk++) {
          const int i = (kb * 4 + kk) * 4;
          uint32_t a[4];
#pragma unroll
          for (int e = 0; e < 2; e++) {
            asm("mul.rn.bf16x2 %0, %1, %1;" : "=r"(a[e]) : "r"(xa[i + e]));
            asm("add.rn.bf16x2 %0, %1, %2;" : "=r"(a[2 + e]) : "r"(xa[i + e]), "r"(xa[i + 2 + e]));
            asm("fma.rn.bf16x2 %0, %1, %1, %0;" : "+r"(a[e]) : "r"(xa[i + 2 + e]));
          }
          mma16816(s1[kk & 1], a[0], a[1], a[2], a[3], b0, b1);
        }
      };
#pragma unroll
      for (int i = 0; i < 9; i++) {
        const int c8 = j * 9 + i, kb = c8 >> 3;
        xr[2 * i] = (kb < 8 ? hw + kb * 8192 : sb + wg * 8192) + (w4 * 16 + g) * 128 + (((c8 & 7) ^ g) << 4) + q * 4;
        asm volatile("" : "+r"(xr[2 * i]));
      }
      mbar_wait(bars + 8 * B_X8, 0);
      load(8, sb + wg * 8192);
      auto pin = [&]() { asm volatile("{.reg .pred p; .reg .u32 c, z; mov.u32 c, %clock; mov.u32 z, %ntid.y; setp.eq.u32 p, z, 0; @p st.shared.u32 [c], c;}" ::: "memory"); };
#pragma unroll
      for (int kp = 0; kp < 4; kp++) {
        mbar_wait(bars + 8 * (B_X + wg * 4 + kp), 0);
        load(2 * kp, hw + 2 * kp * 8192);
        load(2 * kp + 1, hw + (2 * kp + 1) * 8192);
        if (kp == 3) {
#pragma unroll
          for (int i = 0; i < 9; i++) { xr[2 * i + 1] = lds32(xr[2 * i] + 1024); xr[2 * i] = lds32(xr[2 * i]); }
        }
        if (kp == 0) sums(8); else { sums(2 * kp - 2); sums(2 * kp - 1); }
      }
      asm volatile("fence.proxy.async.shared::cta;" ::: "memory");
      bar_arrive(NB_XDONE + wg, 160);
      if (wg == 1) bar_arrive(NB_STATS, 256);
      pin();
      sums(6);
      sums(7);
      pin();
#pragma unroll
      for (int e = 0; e < 2; e++) {
        const float mu = (s1[0][2 * e + 1] + s1[1][2 * e + 1]) * (1.f / kD);
        const float var = fmaxf(fmaf(-mu, mu, (s1[0][2 * e] + s1[1][2 * e]) * (1.f / kD)), 0.f);
        float sd, r;
        asm("sqrt.approx.ftz.f32 %0, %1;" : "=f"(sd) : "f"(rbf(rbf(var) + 1e-5f)));
        asm("rcp.approx.ftz.f32 %0, %1;" : "=f"(r) : "f"(rbf(sd)));
        rh[e] = pack_bf16(0.5f * r, 0.5f * r);
        r = -mu * bfhi(rh[e]);
        cc[e] = pack_bf16(r, r);
      }
    }

    auto normalise = [&](int kb) {
#pragma unroll
      for (int i = 0; i < 16; i++) asm("fma.rn.bf16x2 %0, %0, %1, %2;" : "+r"(xa[16 * kb + (i >> 3) + 2 * (i & 7)]) : "r"(rh[i >> 3]), "r"(cc[i >> 3]));
    };
    {
      float ab[36];
      float* op = prm.out + (size_t)(m * 128 + wg * 64 + w4 * 16 + g) * kD + j * 72 + q * 2;
      auto residual = [&](int i) {
        asm volatile("add.rn.bf16x2 %0, %0, %0;" : "+r"(dk[i]));
#pragma unroll
        for (int e = 0; e < 2; e++) {
          uint32_t t;
          asm("fma.rn.bf16x2 %0, %1, %2, %3;" : "=r"(t) : "r"(xr[2 * i + e]), "r"(rh[e]), "r"(cc[e]));
          asm("fma.rn.bf16x2 %0, %0, %1, %2;" : "+r"(t) : "r"(dk[i]), "r"(xr[2 * i + e]));
          *(float2*)(op + e * 8 * kD + i * 8) = make_float2(bflo(t), bfhi(t));
        }
      };
      const uint32_t da = sb + OFF_DUMP + wg * HS_BYTES + (w4 * 16 + g) * 16 + q * 4;
      auto dump = [&](int im) {
#pragma unroll
        for (int i = 0; i < 18; i++)
          asm volatile("st.shared.b32 [%0], %1;" ::"r"(da + (i < 16 ? 8 * im + (i >> 1) : 16 + im) * HS_LBO + (i & 1) * 128), "r"(pack_bf16(ab[2 * i], ab[2 * i + 1])) : "memory");
      };
      auto bu = [&](int kb, uint32_t off) {
        wg_fence();
#pragma unroll
        for (int kk = 0; kk < 4; kk++) { const int i = (kb * 4 + kk) * 4; wgmma_n72_rs_tb0(ab, xa[i], xa[i + 1], xa[i + 2], xa[i + 3], desc((dring + (off >> 4) + kk * 2) + DLO_K, DHI_SW128), (kb | kk) != 0); }
        wg_commit();
      };
      normalise(0);
      if (wg == 0) {
#pragma unroll
        for (int kb = 1; kb < 9; kb++) normalise(kb);
        bar_sync(NB_STATS, 256);
      }
#pragma unroll
      for (int kb = 0; kb < 9; kb++) {
        if ((kb & 3) == 0) mbar_wait(bars + 8 * (B_BU + (kb >> 2)), 0);
        bu(kb, kb < 8 ? OFF_BU0 + kb * 9216 : OFF_BU1);
        if (wg == 0) residual(kb);
        else if (kb < 8) normalise(kb + 1);
      }
      wg_wait<0>();
      if (w4 == 0) { if (elect()) mbar_arrive(bars + 8 * B_RING); }
      keep(ab);
      dump(0);
#pragma unroll
      for (int kb = 0; kb < 9; kb++) {
        if (kb == 4) mbar_wait(bars + 8 * (B_BU + 3), 0);
        bu(kb, kb < 4 ? OFF_BU1 + (kb + 1) * 9216 : OFF_BU2 + (kb - 4) * 9216);
        if (wg == 1) residual(kb);
      }
      wg_wait<0>();
      keep(ab);
      dump(1);
      bar_arrive(NB_DUMP, 352);
    }

    float acc[64];
    {
      const uint32_t ha = sb + OFF_H + (threadIdx.x & 127) * 16, hblk = wg ? HBLK1 : HBLK0;
      auto glu = [&](int i) {
        return pack_bf16(fmaf(acc[32 + 2 * i], tanh_fast(acc[2 * i]), acc[32 + 2 * i]), fmaf(acc[33 + 2 * i], tanh_fast(acc[2 * i + 1]), acc[33 + 2 * i]));
      };
      for (int c = 0;; c++) {
        if (wg == 1) bar_sync(NB_SKEW, 256);
#pragma unroll
        for (int kb = 0; kb < 9; kb++) {
          if (kb == 7 && c == 0) nst = 8;
          if (kb == 4 && c == 3) nst = 7;
          if (kb == 3 && c == 7) nst = 6;
          stage_begin();
#pragma unroll
          for (int kk = 0; kk < 4; kk++) { const int i = (kb * 4 + kk) * 4; wgmma_n128_rs_tb1(acc, xa[i], xa[i + 1], xa[i + 2], xa[i + 3], desc((dlo + kk * 128) + DLO_MN, DHI_SW128), (kb | kk) != 0); }
          if (kb == SKEW - 1 && wg == 0) bar_arrive(NB_SKEW, 256);
          if (kb == 8 && (c == 3 || c == 4 || c == 7)) mbar_wait(bars + 8 * (c == 4 ? B_SCAN : c == 3 ? B_EMPTY + 7 : B_EMPTY + 6), c == 3);
          stage_end(kb > 0);
        }
        wg_wait<0>();
        release(prev);
        keep(acc);
        if (c == 8) break;
        const uint32_t hc = ha + ((hblk >> (4 * c)) & 15) * 8192;
#pragma unroll
        for (int i = 0; i < 4; i++) sts128(hc + i * 2048, glu(4 * i), glu(4 * i + 1), glu(4 * i + 2), glu(4 * i + 3));
      }
#pragma unroll
      for (int i = 0; i < 32; i++) lds128(ha + ((hblk >> (4 * (i >> 2))) & 15) * 8192 + (i & 3) * 2048, xa[4 * i], xa[4 * i + 1], xa[4 * i + 2], xa[4 * i + 3]);
#pragma unroll
      for (int i = 0; i < 16; i++) xa[128 + i] = glu(i);
      asm volatile("fence.proxy.async.shared::cta;" ::: "memory");
      bar_arrive(NB_HFREE, 288);
    }

    const uint32_t dhs = (((sb + OFF_HS + wg * HS_MAIN) & 0x3FFFF) >> 4) | DLO_HS, drem = DLO_HS + wg * (HS_REM >> 4);
    const int rp = (g >> 2) + 2 * (g & 3);
    const uint32_t so = w4 * 2048 + rp * 128 + (q & 1) * 8, sx = ((q >> 1) ^ rp) << 4;
    const uint32_t rcv = sb + OFF_STG + wg * 32768 + 16384 + w4 * 2048 + lane * 16;
    auto staged = [&]() {
      asm volatile("fence.proxy.async.shared::cta;" ::: "memory");
      __syncwarp();
      if (elect()) mbar_arrive(bars + 8 * (B_SFULL + wg));
    };
    auto half_tile = [&](const bool first, const int kind) {
      float a2[32];
      if (wg == 1) bar_sync(NB_SKEW, 256);
      const uint32_t ph0 = ph;
      uint32_t d4;
#pragma unroll
      for (int kp = 0; kp < 5; kp++) {
        stage_begin();
#pragma unroll
        for (int kk = 0; kk < (kp < 4 ? 8 : 4); kk++) { const int i = (kp * 8 + kk) * 4; wgmma_n64_rs_tb1(a2, xa[i], xa[i + 1], xa[i + 2], xa[i + 3], desc((dlo + kk * 128) + DLO_MN, DHI_SW128), (kp | kk) != 0); }
        if (kp == 2 && wg == 0) bar_arrive(NB_SKEW, 256);
        d4 = dlo;
        stage_end(kp > 0);
        if (kp == 0 && !first) staged();
      }
      if (first) mbar_wait(bars + 8 * B_HSFULL, 0);
      stage_begin();
#pragma unroll
      for (int kk = 0; kk < 8; kk++) wgmma_n64_ss_tb0(a2, desc(dhs + kk * (2 * HS_LBO >> 4), DHI_NONE), desc((dlo + (kk >> 2) * 512 + (kk & 3) * 2) + DLO_K, DHI_SW128), 1);
      wgmma_n64_ss_tb0(a2, desc(d4 + 640 + drem, DHI_NONE), desc((d4 + 512) | ((1024 >> 4) << 16), DHI_NONE), 1);
      wg_commit();
      if (!first) {
        if (kind == 1) mbar_wait(bars + 8 * (B_EMPTY + 1 + wg), ph0);
        if (kind == 2) { mbar_wait(bars + 8 * (B_SFREE + wg), 1); mbar_wait(bars + 8 * (B_RFULL + wg), 1); }
      }
      wg_wait<0>();
      release(prev); release(s); advance();
      keep(a2);
      if (!first && kind >= 2) {
#pragma unroll
        for (int i = 0; i < 4; i++) {
          uint32_t v[4];
          lds128(rcv + (kind & 1) * 8192 + i * 512, v[0], v[1], v[2], v[3]);
#pragma unroll
          for (int e = 0; e < 4; e++) { a2[8 * i + 2 * e] += bflo(v[e]); a2[8 * i + 2 * e + 1] += bfhi(v[e]); }
        }
        __syncwarp();
      }
      const uint32_t stg = (!first && kind == 1 ? sb + (1 + wg) * SLOT : sb + OFF_STG + wg * 32768 + (kind == 3 ? 16384 : 0)) + so;
#pragma unroll
      for (int i = 0; i < 8; i++) {
        const uint32_t a = stg + (i >> 2) * 8192 + (sx ^ ((i & 3) << 5));
        sts64f(a, a2[4 * i], a2[4 * i + 1]);
        sts64f(a + 1024, a2[4 * i + 2], a2[4 * i + 3]);
      }
    };
    if (rank) half_tile(true, 0);
    for (int t = 0; t < 4 - rank; t++) {
      if (wg == 1) bar_sync(NB_SKEW, 256);
#pragma unroll
      for (int kb = 0; kb < 9; kb++) {
        if (t == 0 && ((kb == 4 && rank) || kb == 8)) nst = NST + 1;
        if (t == 1 && ((kb == 1 && rank) || kb == 5)) nst = NST + 2;
        stage_begin();
#pragma unroll
        for (int kk = 0; kk < 4; kk++) { const int i = (kb * 4 + kk) * 4; wgmma_n128_rs_tb1(acc, xa[i], xa[i + 1], xa[i + 2], xa[i + 3], desc((dlo + kk * 128) + DLO_MN, DHI_SW128), (kb | kk) != 0); }
        if (kb == SKEWB - 1 && wg == 0) bar_arrive(NB_SKEW, 256);
        stage_end(kb > 0);
        if (kb == 2 && t + rank > 0) staged();
      }
      if (t == 0) mbar_wait(bars + 8 * B_HSFULL, 0);
      stage_begin();
#pragma unroll
      for (int kk = 0; kk < 4; kk++) wgmma_n128_ss_tb0(acc, desc(dhs + kk * (2 * HS_LBO >> 4), DHI_NONE), desc((dlo + kk * 2) + DLO_K, DHI_SW128), 1);
      stage_end(true);
      stage_begin();
#pragma unroll
      for (int kk = 0; kk < 4; kk++) wgmma_n128_ss_tb0(acc, desc(dhs + (4 + kk) * (2 * HS_LBO >> 4), DHI_NONE), desc((dlo + kk * 2) + DLO_K, DHI_SW128), 1);
      const int s_im = s;
      advance();
      stage_begin();
      wgmma_n128_ss_tb0(acc, desc(dlo + 256 + drem, DHI_NONE), desc(dlo | ((2048 >> 4) << 16), DHI_NONE), 1);
      stage_end(true);
      if (t + rank > 0) mbar_wait(bars + 8 * (B_SFREE + wg), (t + rank - 1) & 1);
      if (t & 1) mbar_wait(bars + 8 * (B_RFULL + wg), t >> 1);
      wg_wait<0>();
      release(s_im); release(prev);
      keep(acc);
      if (t & 1) {
        const uint32_t stg = sb + OFF_STG + wg * 32768 + so;
#pragma unroll
        for (int hh = 0; hh < 2; hh++) {
#pragma unroll
          for (int i = 4 * hh; i < 4 * hh + 4; i++) {
            uint32_t v[4];
            lds128(rcv + hh * 8192 + (i & 3) * 512, v[0], v[1], v[2], v[3]);
#pragma unroll
            for (int e = 0; e < 4; e++) { acc[8 * i + 2 * e] += bflo(v[e]); acc[8 * i + 2 * e + 1] += bfhi(v[e]); }
          }
          __syncwarp();
#pragma unroll
          for (int i = 8 * hh; i < 8 * hh + 8; i++) {
            const uint32_t a = stg + (i >> 2) * 8192 + (sx ^ ((i & 3) << 5));
            sts64f(a, acc[4 * i], acc[4 * i + 1]);
            sts64f(a + 1024, acc[4 * i + 2], acc[4 * i + 3]);
          }
        }
      } else {
#pragma unroll
        for (int i = 0; i < 8; i++)
          sts128(rcv - 16384 + (i >> 2) * 8192 + (i & 3) * 512, pack_bf16(acc[8 * i], acc[8 * i + 1]), pack_bf16(acc[8 * i + 2], acc[8 * i + 3]),
                 pack_bf16(acc[8 * i + 4], acc[8 * i + 5]), pack_bf16(acc[8 * i + 6], acc[8 * i + 7]));
      }
    }
#pragma unroll 1
    for (int kind = 1 + rank; kind < 2 + 2 * rank; kind++) half_tile(false, kind);
    staged();
  }
}

typedef CUresult (*EncodeFn)(CUtensorMap*, CUtensorMapDataType, cuuint32_t, void*, const cuuint64_t*, const cuuint64_t*, const cuuint32_t*,
                             const cuuint32_t*, CUtensorMapInterleave, CUtensorMapSwizzle, CUtensorMapL2promotion, CUtensorMapFloatOOBfill);

void map2d(EncodeFn enc, CUtensorMap* tm, const void* p, uint64_t cols, uint64_t rows, uint32_t bc, uint32_t br, CUtensorMapSwizzle sw) {
  cuuint64_t gd[2] = {cols, rows}, gs[1] = {cols * 2};
  cuuint32_t bd[2] = {bc, br}, es[2] = {1, 1};
  enc(tm, CU_TENSOR_MAP_DATA_TYPE_BFLOAT16, 2, (void*)p, gd, gs, bd, es, CU_TENSOR_MAP_INTERLEAVE_NONE, sw,
      sw == CU_TENSOR_MAP_SWIZZLE_128B ? CU_TENSOR_MAP_L2_PROMOTION_L2_128B : CU_TENSOR_MAP_L2_PROMOTION_NONE, CU_TENSOR_MAP_FLOAT_OOB_FILL_NONE);
}

}

extern "C" void kernel_launch(void* const* d_in, const int* in_sizes, int n_in, void* d_out, int out_size) {
  (void)in_sizes; (void)n_in; (void)out_size;
  static EncodeFn enc = nullptr;
  if (!enc) {
    cudaDriverEntryPointQueryResult qr;
    cudaGetDriverEntryPoint("cuTensorMapEncodeTiled", (void**)&enc, cudaEnableDefault, &qr);
    cudaFuncSetAttribute(fused_kernel, cudaFuncAttributeMaxDynamicSharedMemorySize, SMEM_BYTES);
  }
  Params prm;
  const CUtensorMapSwizzle S128 = CU_TENSOR_MAP_SWIZZLE_128B;
  map2d(enc, &prm.tx, d_in[0], kD, kS, 64, 64, S128);
  map2d(enc, &prm.tBre, d_in[3], kD, 576, 64, 72, S128);
  map2d(enc, &prm.tBim, d_in[4], kD, 576, 64, 72, S128);
  map2d(enc, &prm.tCre, d_in[5], 576, kD, 64, 64, S128);
  map2d(enc, &prm.tCim, d_in[6], 576, kD, 64, 64, S128);
  map2d(enc, &prm.tCre8, d_in[5], 576, kD, 8, 64, CU_TENSOR_MAP_SWIZZLE_NONE);
  map2d(enc, &prm.tCim8, d_in[6], 576, kD, 8, 64, CU_TENSOR_MAP_SWIZZLE_NONE);
  map2d(enc, &prm.tWg, d_in[10], kF, kD, 64, 64, S128);
  map2d(enc, &prm.tWu, d_in[11], kF, kD, 64, 64, S128);
  map2d(enc, &prm.tWd, d_in[12], kD, kF, 64, 64, S128);
  {
    cuuint64_t gd[4] = {kD, 2, 4, kS / 8}, gs[3] = {4 * kD * 4, kD * 4, 8 * kD * 4};
    cuuint32_t bd[4] = {32, 2, 4, 8}, es[4] = {1, 1, 1, 1};
    enc(&prm.tOut, CU_TENSOR_MAP_DATA_TYPE_FLOAT32, 4, d_out, gd, gs, bd, es, CU_TENSOR_MAP_INTERLEAVE_NONE, S128, CU_TENSOR_MAP_L2_PROMOTION_NONE,
        CU_TENSOR_MAP_FLOAT_OOB_FILL_NONE);
  }
  prm.lre = (const __nv_bfloat16*)d_in[1];
  prm.lim = (const __nv_bfloat16*)d_in[2];
  prm.bre = (const __nv_bfloat16*)d_in[3];
  prm.bim = (const __nv_bfloat16*)d_in[4];
  prm.cre = (const __nv_bfloat16*)d_in[5];
  prm.cim = (const __nv_bfloat16*)d_in[6];
  prm.wg = (const __nv_bfloat16*)d_in[10];
  prm.wu = (const __nv_bfloat16*)d_in[11];
  prm.wd = (const __nv_bfloat16*)d_in[12];
  prm.ldt = (const __nv_bfloat16*)d_in[7];
  prm.dskip = (const __nv_bfloat16*)d_in[8];
  prm.out = (float*)d_out;

  fused_kernel<<<128, 384, SMEM_BYTES, cudaStreamPerThread>>>(prm);
}
```

```cpp
#include <cuda_runtime.h>
#include <cuda.h>
#include <cuda_bf16.h>
#include <stdint.h>

namespace {

constexpr int kS = 2048, kD = 576, kF = 4608;
constexpr int SKEW = 4;
constexpr int PFD = 18;
constexpr int NST = 6;
constexpr uint32_t SLOT = 16384;
constexpr uint32_t OFF_H = NST * SLOT;
constexpr uint32_t HS_LBO = 1040;
constexpr uint32_t HS_BYTES = 18 * HS_LBO;
constexpr uint32_t OFF_DUMP = OFF_H + 65536 - HS_BYTES;
constexpr uint32_t OFF_STG = OFF_H + 2 * SLOT;
constexpr uint32_t OFF_HS = OFF_STG + 65536;
constexpr uint32_t HS_MAIN = 16 * HS_LBO, HS_REM = 2 * HS_LBO;
constexpr uint32_t OFF_CONST = OFF_H + 131072;
constexpr uint32_t OFF_BAR = OFF_CONST + 4 * 576;
constexpr uint32_t SMEM_BYTES = OFF_BAR + 384 + 384;
static_assert(SMEM_BYTES <= 232448 && OFF_HS + 2 * HS_MAIN <= OFF_BAR, "smem");

enum { B_FULL = 0, B_EMPTY = NST + 2, B_X = 2 * NST + 4, B_X8 = B_X + 8, B_BU  , B_RING = B_BU + 4  , B_SCAN = B_RING + 2, B_PARK, B_HFREE, B_HSFULL, B_SFULL,
       B_SFREE = B_SFULL + 2, B_RFULL = B_SFREE + 2, B_RFREE = B_RFULL + 2, B_COUNT = B_RFREE + 2 };
static_assert(B_COUNT * 8 <= 384, "barriers");
enum { NB_SKEW = 1, NB_XDONE = 2  , NB_SCAN = 4, NB_DUMP = 5, NB_HFREE = 6, NB_STATS = 7 };
constexpr uint32_t HBLK0 = 0x07652CB4u, HBLK1 = 0x189A3DEFu;
constexpr uint32_t OFF_BU0 = SLOT, OFF_BU1 = OFF_H, OFF_BU2 = OFF_H + 65536 + 19456;
static_assert(OFF_BU1 + 5 * 9216 <= OFF_DUMP && OFF_BU2 >= OFF_DUMP + 2 * HS_BYTES && OFF_BU2 + 5 * 9216 <= OFF_CONST, "Bu tiles");

struct __align__(64) Params {
  CUtensorMap tx, tBre, tBim, tWg, tWu, tWd, tCre, tCim, tCre8, tCim8, tOut;
  const __nv_bfloat16 *lre, *lim, *bre, *bim, *cre, *cim, *ldt, *dskip, *wg, *wu, *wd;
  float* out;
};

__device__ unsigned g_epoch[128];
__device__ unsigned g_ready[16];
__device__ __align__(256) uint2 g_S[2][16][8][96];
__device__ __align__(128) uint8_t g_hs[128][2 * HS_BYTES];

__device__ __forceinline__ void wgmma_n72_rs_tb0(float (&d)[36], uint32_t a0, uint32_t a1, uint32_t a2, uint32_t a3, uint64_t db, int scale_d) {
  asm volatile("{\n.reg .pred p;\nsetp.ne.b32 p, %41, 0;\n"
    "wgmma.mma_async.sync.aligned.m64n72k16.f32.bf16.bf16 {"
    "%0, %1, %2, %3, %4, %5, %6, %7, %8, %9, %10, %11, %12, %13, %14, %15, "
    "%16, %17, %18, %19, %20, %21, %22, %23, %24, %25, %26, %27, %28, %29, %30, %31, "
    "%32, %33, %34, %35"
    "}, {%36, %37, %38, %39}, %40, p, 1, 1, 0;\n}\n"
    : "+f"(d[0]), "+f"(d[1]), "+f"(d[2]), "+f"(d[3]), "+f"(d[4]), "+f"(d[5]), "+f"(d[6]), "+f"(d[7]),
      "+f"(d[8]), "+f"(d[9]), "+f"(d[10]), "+f"(d[11]), "+f"(d[12]), "+f"(d[13]), "+f"(d[14]), "+f"(d[15]),
      "+f"(d[16]), "+f"(d[17]), "+f"(d[18]), "+f"(d[19]), "+f"(d[20]), "+f"(d[21]), "+f"(d[22]), "+f"(d[23]),
      "+f"(d[24]), "+f"(d[25]), "+f"(d[26]), "+f"(d[27]), "+f"(d[28]), "+f"(d[29]), "+f"(d[30]), "+f"(d[31]),
      "+f"(d[32]), "+f"(d[33]), "+f"(d[34]), "+f"(d[35])
    : "r"(a0), "r"(a1), "r"(a2), "r"(a3), "l"(db), "r"(scale_d));
}
__device__ __forceinline__ void wgmma_n128_rs_tb1(float (&d)[64], uint32_t a0, uint32_t a1, uint32_t a2, uint32_t a3, uint64_t db, int scale_d) {
  asm volatile("{\n.reg .pred p;\nsetp.ne.b32 p, %69, 0;\n"
    "wgmma.mma_async.sync.aligned.m64n128k16.f32.bf16.bf16 {"
    "%0, %1, %2, %3, %4, %5, %6, %7, %8, %9, %10, %11, %12, %13, %14, %15, "
    "%16, %17, %18, %19, %20, %21, %22, %23, %24, %25, %26, %27, %28, %29, %30, %31, "
    "%32, %33, %34, %35, %36, %37, %38, %39, %40, %41, %42, %43, %44, %45, %46, %47, "
    "%48, %49, %50, %51, %52, %53, %54, %55, %56, %57, %58, %59, %60, %61, %62, %63"
    "}, {%64, %65, %66, %67}, %68, p, 1, 1, 1;\n}\n"
    : "+f"(d[0]), "+f"(d[1]), "+f"(d[2]), "+f"(d[3]), "+f"(d[4]), "+f"(d[5]), "+f"(d[6]), "+f"(d[7]),
      "+f"(d[8]), "+f"(d[9]), "+f"(d[10]), "+f"(d[11]), "+f"(d[12]), "+f"(d[13]), "+f"(d[14]), "+f"(d[15]),
      "+f"(d[16]), "+f"(d[17]), "+f"(d[18]), "+f"(d[19]), "+f"(d[20]), "+f"(d[21]), "+f"(d[22]), "+f"(d[23]),
      "+f"(d[24]), "+f"(d[25]), "+f"(d[26]), "+f"(d[27]), "+f"(d[28]), "+f"(d[29]), "+f"(d[30]), "+f"(d[31]),
      "+f"(d[32]), "+f"(d[33]), "+f"(d[34]), "+f"(d[35]), "+f"(d[36]), "+f"(d[37]), "+f"(d[38]), "+f"(d[39]),
      "+f"(d[40]), "+f"(d[41]), "+f"(d[42]), "+f"(d[43]), "+f"(d[44]), "+f"(d[45]), "+f"(d[46]), "+f"(d[47]),
      "+f"(d[48]), "+f"(d[49]), "+f"(d[50]), "+f"(d[51]), "+f"(d[52]), "+f"(d[53]), "+f"(d[54]), "+f"(d[55]),
      "+f"(d[56]), "+f"(d[57]), "+f"(d[58]), "+f"(d[59]), "+f"(d[60]), "+f"(d[61]), "+f"(d[62]), "+f"(d[63])
    : "r"(a0), "r"(a1), "r"(a2), "r"(a3), "l"(db), "r"(scale_d));
}
__device__ __forceinline__ void wgmma_n128_ss_tb0(float (&d)[64], uint64_t da, uint64_t db, int scale_d) {
  asm volatile("{\n.reg .pred p;\nsetp.ne.b32 p, %66, 0;\n"
    "wgmma.mma_async.sync.aligned.m64n128k16.f32.bf16.bf16 {"
    "%0, %1, %2, %3, %4, %5, %6, %7, %8, %9, %10, %11, %12, %13, %14, %15, "
    "%16, %17, %18, %19, %20, %21, %22, %23, %24, %25, %26, %27, %28, %29, %30, %31, "
    "%32, %33, %34, %35, %36, %37, %38, %39, %40, %41, %42, %43, %44, %45, %46, %47, "
    "%48, %49, %50, %51, %52, %53, %54, %55, %56, %57, %58, %59, %60, %61, %62, %63"
    "}, %64, %65, p, 1, 1, 0, 0;\n}\n"
    : "+f"(d[0]), "+f"(d[1]), "+f"(d[2]), "+f"(d[3]), "+f"(d[4]), "+f"(d[5]), "+f"(d[6]), "+f"(d[7]),
      "+f"(d[8]), "+f"(d[9]), "+f"(d[10]), "+f"(d[11]), "+f"(d[12]), "+f"(d[13]), "+f"(d[14]), "+f"(d[15]),
      "+f"(d[16]), "+f"(d[17]), "+f"(d[18]), "+f"(d[19]), "+f"(d[20]), "+f"(d[21]), "+f"(d[22]), "+f"(d[23]),
      "+f"(d[24]), "+f"(d[25]), "+f"(d[26]), "+f"(d[27]), "+f"(d[28]), "+f"(d[29]), "+f"(d[30]), "+f"(d[31]),
      "+f"(d[32]), "+f"(d[33]), "+f"(d[34]), "+f"(d[35]), "+f"(d[36]), "+f"(d[37]), "+f"(d[38]), "+f"(d[39]),
      "+f"(d[40]), "+f"(d[41]), "+f"(d[42]), "+f"(d[43]), "+f"(d[44]), "+f"(d[45]), "+f"(d[46]), "+f"(d[47]),
      "+f"(d[48]), "+f"(d[49]), "+f"(d[50]), "+f"(d[51]), "+f"(d[52]), "+f"(d[53]), "+f"(d[54]), "+f"(d[55]),
      "+f"(d[56]), "+f"(d[57]), "+f"(d[58]), "+f"(d[59]), "+f"(d[60]), "+f"(d[61]), "+f"(d[62]), "+f"(d[63])
    : "l"(da), "l"(db), "r"(scale_d));
}
__device__ __forceinline__ void wgmma_n64_rs_tb1(float (&d)[32], uint32_t a0, uint32_t a1, uint32_t a2, uint32_t a3, uint64_t db, int scale_d) {
  asm volatile("{\n.reg .pred p;\nsetp.ne.b32 p, %37, 0;\n"
    "wgmma.mma_async.sync.aligned.m64n64k16.f32.bf16.bf16 {"
    "%0, %1, %2, %3, %4, %5, %6, %7, %8, %9, %10, %11, %12, %13, %14, %15, "
    "%16, %17, %18, %19, %20, %21, %22, %23, %24, %25, %26, %27, %28, %29, %30, %31"
    "}, {%32, %33, %34, %35}, %36, p, 1, 1, 1;\n}\n"
    : "+f"(d[0]), "+f"(d[1]), "+f"(d[2]), "+f"(d[3]), "+f"(d[4]), "+f"(d[5]), "+f"(d[6]), "+f"(d[7]),
      "+f"(d[8]), "+f"(d[9]), "+f"(d[10]), "+f"(d[11]), "+f"(d[12]), "+f"(d[13]), "+f"(d[14]), "+f"(d[15]),
      "+f"(d[16]), "+f"(d[17]), "+f"(d[18]), "+f"(d[19]), "+f"(d[20]), "+f"(d[21]), "+f"(d[22]), "+f"(d[23]),
      "+f"(d[24]), "+f"(d[25]), "+f"(d[26]), "+f"(d[27]), "+f"(d[28]), "+f"(d[29]), "+f"(d[30]), "+f"(d[31])
    : "r"(a0), "r"(a1), "r"(a2), "r"(a3), "l"(db), "r"(scale_d));
}
__device__ __forceinline__ void wgmma_n64_ss_tb0(float (&d)[32], uint64_t da, uint64_t db, int scale_d) {
  asm volatile("{\n.reg .pred p;\nsetp.ne.b32 p, %34, 0;\n"
    "wgmma.mma_async.sync.aligned.m64n64k16.f32.bf16.bf16 {"
    "%0, %1, %2, %3, %4, %5, %6, %7, %8, %9, %10, %11, %12, %13, %14, %15, "
    "%16, %17, %18, %19, %20, %21, %22, %23, %24, %25, %26, %27, %28, %29, %30, %31"
    "}, %32, %33, p, 1, 1, 0, 0;\n}\n"
    : "+f"(d[0]), "+f"(d[1]), "+f"(d[2]), "+f"(d[3]), "+f"(d[4]), "+f"(d[5]), "+f"(d[6]), "+f"(d[7]),
      "+f"(d[8]), "+f"(d[9]), "+f"(d[10]), "+f"(d[11]), "+f"(d[12]), "+f"(d[13]), "+f"(d[14]), "+f"(d[15]),
      "+f"(d[16]), "+f"(d[17]), "+f"(d[18]), "+f"(d[19]), "+f"(d[20]), "+f"(d[21]), "+f"(d[22]), "+f"(d[23]),
      "+f"(d[24]), "+f"(d[25]), "+f"(d[26]), "+f"(d[27]), "+f"(d[28]), "+f"(d[29]), "+f"(d[30]), "+f"(d[31])
    : "l"(da), "l"(db), "r"(scale_d));
}

__device__ __forceinline__ bool elect() {
  uint32_t p;
  asm volatile("{.reg .pred q; elect.sync _|q, 0xffffffff; selp.u32 %0,1,0,q;}" : "=r"(p));
  return p;
}
__device__ __forceinline__ void mbar_init(uint32_t bar, uint32_t cnt) { asm volatile("mbarrier.init.shared::cta.b64 [%0], %1;" ::"r"(bar), "r"(cnt) : "memory"); }
__device__ __forceinline__ void mbar_expect(uint32_t bar, uint32_t bytes) { asm volatile("mbarrier.arrive.expect_tx.shared::cta.b64 _, [%0], %1;" ::"r"(bar), "r"(bytes) : "memory"); }
__device__ __forceinline__ void mbar_arrive(uint32_t bar) { asm volatile("mbarrier.arrive.shared::cta.b64 _, [%0];" ::"r"(bar) : "memory"); }
__device__ __forceinline__ void mbar_arrive_cta(uint32_t bar, uint32_t cta) {
  asm volatile("{.reg .b32 ra; mapa.shared::cluster.u32 ra, %0, %1; mbarrier.arrive.shared::cluster.b64 _, [ra];}" ::"r"(bar), "r"(cta) : "memory");
}
__device__ __forceinline__ void mbar_wait(uint32_t bar, uint32_t parity) {
  asm volatile(
      "{\n.reg .pred p;\n.reg .u32 c, t;\n"
      "mbarrier.try_wait.parity.shared::cta.b64 p, [%0], %1;\n@p bra DONE;\n"
      "mov.u32 c, %%clock;\n"
      "LAB_WAIT:\nmbarrier.try_wait.parity.shared::cta.b64 p, [%0], %1;\n@p bra DONE;\n"
      "mov.u32 t, %%clock;\nsub.u32 t, t, c;\nsetp.lt.u32 p, t, 0x40000000;\n@p bra LAB_WAIT;\ntrap;\nDONE:\n}" ::"r"(bar), "r"(parity) : "memory");
}
__device__ __forceinline__ void bar_sync(int id, int n) { asm volatile("bar.sync %0, %1;" ::"r"(id), "r"(n) : "memory"); }
__device__ __forceinline__ void bar_arrive(int id, int n) { asm volatile("bar.arrive %0, %1;" ::"r"(id), "r"(n) : "memory"); }
__device__ __forceinline__ void wg_fence() { asm volatile("wgmma.fence.sync.aligned;" ::: "memory"); }
__device__ __forceinline__ void wg_commit() { asm volatile("wgmma.commit_group.sync.aligned;" ::: "memory"); }
template <int N> __device__ __forceinline__ void wg_wait() { asm volatile("wgmma.wait_group.sync.aligned %0;" ::"n"(N) : "memory"); }
__device__ __forceinline__ void tma2d(uint32_t dst, const CUtensorMap* tm, uint32_t bar, int c0, int c1) {
  asm volatile("cp.async.bulk.tensor.2d.shared::cluster.global.mbarrier::complete_tx::bytes [%0], [%1,{%3,%4}], [%2];" ::"r"(dst), "l"(tm), "r"(bar), "r"(c0), "r"(c1) : "memory");
}
__device__ __forceinline__ void tma2d_mc(uint32_t dst, const CUtensorMap* tm, uint32_t bar, int c0, int c1) {
  asm volatile("cp.async.bulk.tensor.2d.shared::cluster.global.mbarrier::complete_tx::bytes.multicast::cluster [%0], [%1,{%3,%4}], [%2], %5;" ::"r"(dst), "l"(tm), "r"(bar), "r"(c0), "r"(c1), "h"((uint16_t)3) : "memory");
}
__device__ __forceinline__ void l2_prefetch_line(const void* p) { asm volatile("prefetch.global.L2 [%0];" ::"l"(p)); }
__device__ __forceinline__ uint64_t desc(uint32_t lo, uint32_t hi) { return ((uint64_t)hi << 32) | lo; }
constexpr uint32_t DHI_SW128 = (1024 >> 4) | (1u << 30);
constexpr uint32_t DHI_NONE = (128 >> 4);
constexpr uint32_t DLO_HS = (HS_LBO >> 4) << 16;
constexpr uint32_t DLO_MN = (8192 >> 4) << 16;
constexpr uint32_t DLO_K = 1u << 16;
__device__ __forceinline__ float tanh_fast(float x) { float y; asm("tanh.approx.f32 %0, %1;" : "=f"(y) : "f"(x)); return y; }
__device__ __forceinline__ uint32_t pack_bf16(float lo, float hi) { uint32_t r; asm("cvt.rn.bf16x2.f32 %0, %1, %2;" : "=r"(r) : "f"(hi), "f"(lo)); return r; }
__device__ __forceinline__ float rbf(float x) { return __uint_as_float(pack_bf16(0.f, x)); }
__device__ __forceinline__ void mma16816(float (&c)[4], uint32_t a0, uint32_t a1, uint32_t a2, uint32_t a3, uint32_t b0, uint32_t b1) {
  asm volatile("mma.sync.aligned.m16n8k16.row.col.f32.bf16.bf16.f32 {%0,%1,%2,%3}, {%4,%5,%6,%7}, {%8,%9}, {%0,%1,%2,%3};"
               : "+f"(c[0]), "+f"(c[1]), "+f"(c[2]), "+f"(c[3]) : "r"(a0), "r"(a1), "r"(a2), "r"(a3), "r"(b0), "r"(b1));
}
__device__ __forceinline__ void sts128(uint32_t a, uint32_t x, uint32_t y, uint32_t z, uint32_t w) {
  asm volatile("st.shared.v4.b32 [%0], {%1,%2,%3,%4};" ::"r"(a), "r"(x), "r"(y), "r"(z), "r"(w) : "memory");
}
__device__ __forceinline__ void sts64f(uint32_t a, float x, float y) { asm volatile("st.shared.v2.f32 [%0], {%1,%2};" ::"r"(a), "f"(x), "f"(y) : "memory"); }
__device__ __forceinline__ float2 lds64f(uint32_t a) { float2 v; asm volatile("ld.shared.v2.f32 {%0,%1}, [%2];" : "=f"(v.x), "=f"(v.y) : "r"(a) : "memory"); return v; }
__device__ __forceinline__ uint32_t lds32(uint32_t a) { uint32_t v; asm volatile("ld.shared.b32 %0, [%1];" : "=r"(v) : "r"(a) : "memory"); return v; }
__device__ __forceinline__ void lds128(uint32_t a, uint32_t& x, uint32_t& y, uint32_t& z, uint32_t& w) {
  asm volatile("ld.shared.v4.b32 {%0,%1,%2,%3}, [%4];" : "=r"(x), "=r"(y), "=r"(z), "=r"(w) : "r"(a) : "memory");
}
__device__ __forceinline__ void lds128_inplace(uint32_t a, uint32_t& x, uint32_t& y, uint32_t& z, uint32_t& w) {
  asm volatile("{.reg .pred p; .reg .u32 n; mov.u32 n, %%ntid.y; setp.ne.u32 p, n, 0; @p ld.shared.v4.b32 {%0,%1,%2,%3}, [%4];}" : "+r"(x), "+r"(y), "+r"(z), "+r"(w) : "r"(a) : "memory");
}
__device__ __forceinline__ float bflo(uint32_t v) { return __uint_as_float(v << 16); }
__device__ __forceinline__ float bfhi(uint32_t v) { return __uint_as_float(v & 0xffff0000u); }
template <int N> __device__ __forceinline__ void keep(float (&a)[N]) {
#pragma unroll
  for (int i = 0; i < N; i++) asm volatile("" : "+f"(a[i])::"memory");
}

__global__ void __cluster_dims__(2, 1, 1) __launch_bounds__(384, 1) fused_kernel(const __grid_constant__ Params prm) {
  extern __shared__ __align__(1024) uint8_t smem[];
  const int warp = __shfl_sync(0xffffffffu, threadIdx.x >> 5, 0);
  const uint32_t sb0 = (uint32_t)__cvta_generic_to_shared(smem);
  const int j = blockIdx.x & 7, m = blockIdx.x >> 3, rank = j & 1;
  auto smem_base = [&]() { return __shfl_sync(0xffffffffu, sb0 + (threadIdx.x & 31), 0); };

  if (threadIdx.x == 320) asm volatile("prefetch.tensormap [%0];" ::"l"(&prm.tx) : "memory");
  if (warp == 0) {
    if (elect()) {
#pragma unroll
      for (int i = B_X8; i >= B_X; i--) mbar_init(sb0 + OFF_BAR + 8 * i, 1);
      asm volatile("fence.mbarrier_init.release.cluster;" ::: "memory");
    }
    __syncwarp();
  }
  asm volatile("barrier.cluster.arrive.relaxed.aligned;" ::: "memory");
  if (warp == 0) {
    const uint32_t xb = sb0 + OFF_BAR;
    if (elect()) {
      mbar_expect(xb + 8 * B_X8, 16384);
      tma2d(sb0, &prm.tx, xb + 8 * B_X8, 512, m * 128);
      tma2d(sb0 + 8192, &prm.tx, xb + 8 * B_X8, 512, m * 128 + 64);
#pragma unroll
      for (int i = 0; i < 4; i++) {
        mbar_expect(xb + 8 * (B_X + i), 16384);
        tma2d(sb0 + OFF_H + i * 16384, &prm.tx, xb + 8 * (B_X + i), i * 128, m * 128);
        tma2d(sb0 + OFF_H + i * 16384 + 8192, &prm.tx, xb + 8 * (B_X + i), i * 128 + 64, m * 128);
      }
    }
    __syncwarp();
  }
  asm volatile("barrier.cluster.wait.aligned;" ::: "memory");
  if (warp == 8 || warp == 9) {
    if (elect()) {
      if (warp == 8) {
#pragma unroll
        for (int i = 0; i < B_X; i++) mbar_init(sb0 + OFF_BAR + 8 * i, i >= B_EMPTY ? 2 : 1);
      } else {
#pragma unroll
        for (int i = B_X8 + 1; i < B_COUNT; i++) mbar_init(sb0 + OFF_BAR + 8 * i, (i >= B_SFULL && i < B_SFULL + 2) ? 4 : (i == B_RING || i == B_RING + 1) ? 2 : 1);
        if (sb0 & 1023) __trap();
      }
      asm volatile("fence.mbarrier_init.release.cluster;" ::: "memory");
    }
    __syncwarp();
  }
  if (warp == 0) {
    const uint32_t xb = sb0 + OFF_BAR;
    const bool e = elect();
#pragma unroll
    for (int i = 0; i < 4; i++) {
      const int kb = i * 2 + rank;
      if (e) { mbar_expect(xb + 8 * (B_X + 4 + i), 16384); tma2d_mc(sb0 + OFF_H + 65536 + kb * 8192, &prm.tx, xb + 8 * (B_X + 4 + i), kb * 64, m * 128 + 64); }
    }
    __syncwarp();
  }
  asm volatile("barrier.cluster.arrive.relaxed.aligned;\nbarrier.cluster.wait.aligned;" ::: "memory");

  if (warp >= 8) {
    asm volatile("setmaxnreg.dec.sync.aligned.u32 24;");
    if (warp == 8) {
      const uint32_t sb = smem_base(), bars = sb + OFF_BAR;
      bool e;
      int s = 0, nst = NST + 2; uint32_t ph = 1;
      uint32_t dst, fb;
      auto acquire = [&](uint32_t bytes) {
        mbar_wait(bars + 8 * (B_EMPTY + s), ph);
        fb = bars + 8 * (B_FULL + s); dst = sb + s * SLOT;
        e = elect();
        if (e) mbar_expect(fb, bytes);
        if (++s == nst) { s = 0; ph ^= 1; }
      };
      auto box = [&](const CUtensorMap* t, uint32_t o, int a, int b) { if (e) tma2d(dst + o, t, fb, a, b); };
      auto hs_rem = [&](uint32_t o) {
        if (e) asm volatile("cp.async.bulk.shared::cluster.global.mbarrier::complete_tx::bytes [%0], [%1], %2, [%3];" ::"r"(dst + o),
                            "l"(&g_hs[blockIdx.x][2 * HS_MAIN]), "r"(2 * HS_REM), "r"(fb) : "memory");
      };
      const int lane = threadIdx.x & 31;
      const char* pf = lane < 8 ? (const char*)(lane & 4 ? prm.wu : prm.wg) + ((size_t)(m * 4 + (lane & 3)) * kF + j * 576) * 2
                     : lane < 12 ? (const char*)prm.wd + (size_t)j * 576 * 1152 + (m * 324 + (lane & 3)) * 128
                                 : (const char*)(lane & 1 ? prm.cim : prm.cre) + (size_t)blockIdx.x * 5184;
      int pk = 0, pleft = 81;
      auto prefetch = [&]() {
        if (pleft > 0) {
          if (lane < 14) l2_prefetch_line(pf);
          pf += lane < 8 ? (pk == 8 ? 128 - 8 * 64 * kF * 2 : 64 * kF * 2) : lane < 12 ? 512 : 64;
          pk = pk == 8 ? 0 : pk + 1;
          pleft--;
        }
      };
      mbar_wait(bars + 8 * B_X8, 0);
      e = elect();
#pragma unroll 1
      for (int kb = 0; kb < 8; kb++) {
        fb = bars + 8 * (B_BU + (kb >> 2));
        if (e) { if ((kb & 3) == 0) mbar_expect(fb, 4 * 9216); tma2d(sb + OFF_BU0 + kb * 9216, &prm.tBre, fb, kb * 64, j * 72); }
      }
      bar_sync(NB_XDONE, 160);
      fb = bars + 8 * (B_BU + 2);
      if (e) { mbar_expect(fb, 5 * 9216); tma2d(sb + OFF_BU1, &prm.tBre, fb, 512, j * 72); }
#pragma unroll 1
      for (int kb = 0; kb < 4; kb++) if (e) tma2d(sb + OFF_BU1 + (kb + 1) * 9216, &prm.tBim, fb, kb * 64, j * 72);
      for (int i = 0; i < PFD / 2; i++) prefetch();
      bar_sync(NB_XDONE + 1, 160);
      fb = bars + 8 * (B_BU + 3);
      if (e) mbar_expect(fb, 5 * 9216);
#pragma unroll 1
      for (int kb = 4; kb < 9; kb++) if (e) tma2d(sb + OFF_BU2 + (kb - 4) * 9216, &prm.tBim, fb, kb * 64, j * 72);
      for (int i = PFD / 2; i < PFD; i++) prefetch();
      mbar_wait(bars + 8 * B_RING, 0);
      for (int c = 0; c < 9; c++) {
        const int col = j * 576 + c * 64;
#pragma unroll 1
        for (int kb = 0; kb < 9; kb++) {
          if (kb == 6 && c == 0) mbar_wait(bars + 8 * (B_RING + 1), 0);
          if (kb == 6 && c == 3) nst = 7;
          if (kb == 5 && c == 7) nst = 6;
          acquire(16384); box(&prm.tWg, 0, col, kb * 64); box(&prm.tWu, 8192, col, kb * 64); prefetch();
        }
      }
      auto half_tile = [&](int n0) {
#pragma unroll 1
        for (int kp = 0; kp < 4; kp++) { acquire(16384); box(&prm.tWd, 0, n0, j * 576 + kp * 128); box(&prm.tWd, 8192, n0, j * 576 + kp * 128 + 64); }
        acquire(8192 + 2048 + 2 * HS_REM); box(&prm.tWd, 0, n0, j * 576 + 512); box(&prm.tCre8, 8192, j * 72 + 64, n0); box(&prm.tCim8, 9216, j * 72 + 64, n0); hs_rem(10240);
        acquire(16384); box(&prm.tCre, 0, j * 72, n0); box(&prm.tCim, 8192, j * 72, n0);
      };
      mbar_wait(bars + 8 * B_PARK, 0);
      asm volatile("fence.proxy.async.global;" ::: "memory");
      if (rank) half_tile(512);
#pragma unroll 1
      for (int t = 0; t < 4 - rank; t++) {
        const int n0 = ((rank ^ t ^ 1) & 1) * 256 + (((t >> 1) ^ (j >> 1)) & 1) * 128;
#pragma unroll 1
        for (int kb = 0; kb < 9; kb++) {
          if (rank ? (t == 0 && kb == 5) : (t == 1 && kb == 1)) nst = NST + 1;
          if (t == 1 && kb == (rank ? 1 : 7)) nst = NST + 2;
          if (kb == 3 && t == 0 && rank) mbar_wait(bars + 8 * B_HFREE, 0);
          acquire(16384); box(&prm.tWd, 0, n0, j * 576 + kb * 64); box(&prm.tWd, 8192, n0 + 64, j * 576 + kb * 64);
        }
        if (t == 0) mbar_wait(bars + 8 * B_HFREE, 0);
        acquire(16384); box(&prm.tCre, 0, j * 72, n0); box(&prm.tCre, 8192, j * 72, n0 + 64);
        acquire(16384); box(&prm.tCim, 0, j * 72, n0); box(&prm.tCim, 8192, j * 72, n0 + 64);
        acquire(4096 + 2 * HS_REM); hs_rem(4096);
        box(&prm.tCre8, 0, j * 72 + 64, n0); box(&prm.tCre8, 1024, j * 72 + 64, n0 + 64);
        box(&prm.tCim8, 2048, j * 72 + 64, n0); box(&prm.tCim8, 3072, j * 72 + 64, n0 + 64);
      }
      if (!rank) half_tile(512);
      else {
#pragma unroll 1
        for (int hh = 0; hh < 2; hh++) half_tile(256 + (((j >> 1) ^ 1) & 1) * 128 + hh * 64);
      }
    } else {
      const uint32_t sb = smem_base(), bars = sb + OFF_BAR;
      const int p = min((int)threadIdx.x - 288, 71);
      if (threadIdx.x < 288 + 10) asm volatile("prefetch.tensormap [%0];" ::"l"(&prm.tBre + (threadIdx.x - 288)) : "memory");
      if (warp == 10) {
        const int l = threadIdx.x & 31;
        const char* q = (const char*)(l & 1 ? prm.bim : prm.bre) + (size_t)blockIdx.x * 5184;
        mbar_wait(bars + 8 * B_X8, 0);
#pragma unroll
        for (int i = 0; i < 3; i++) if (i * 16 + (l >> 1) < 42) l2_prefetch_line(q + min((i * 16 + (l >> 1)) * 128, 5183));
      }
      const unsigned epoch = *(volatile unsigned*)&g_epoch[blockIdx.x];
      {
        const int pg = j * 72 + p;
        const float lr = __bfloat162float(prm.lre[pg]), li = __bfloat162float(prm.lim[pg]);
        const float dt = rbf(expf(__bfloat162float(prm.ldt[pg])));
        const float ea = expf(dt * lr);
        float sn, cs;
        sincosf(dt * li, &sn, &cs);
        const float ar = ea * cs, ai = ea * sn;
        float br = ar, bi = ai;
#pragma unroll
        for (int k = 0; k < 6; k++) { const float t = br * br - bi * bi; bi = 2.f * br * bi; br = t; }
        const float nr = ar - 1.f, den = 4.f / (lr * lr + li * li);
        sts64f(sb + OFF_CONST + p * 8, ar, ai);
        sts64f(sb + OFF_CONST + 576 + p * 8, br, bi);
        sts64f(sb + OFF_CONST + 1152 + p * 8, (nr * lr + ai * li) * den, (ai * lr - nr * li) * den);
      }
      bar_sync(NB_DUMP, 352);
      {
        const int lane = threadIdx.x & 31;
        const int half = warp == 11 ? (lane >> 2) & 1 : warp - 9;
        const uint32_t cu = sb + OFF_CONST + (warp == 11 ? 32 + (lane & 3) : lane) * 16;
        uint32_t a0 = sb + OFF_DUMP + half * HS_BYTES + (warp == 11 ? 16 : lane >> 2) * HS_LBO + (lane & 3) * 4;
        asm volatile("" : "+r"(a0));
        const uint32_t di = warp == 11 ? HS_LBO : 8 * HS_LBO;
        float a[4], h[4] = {0.f, 0.f, 0.f, 0.f};
        auto ld4 = [&](uint32_t ad, float (&v)[4]) { asm volatile("ld.shared.v4.f32 {%0,%1,%2,%3}, [%4];" : "=f"(v[0]), "=f"(v[1]), "=f"(v[2]), "=f"(v[3]) : "r"(ad) : "memory"); };
        auto cfma = [&](const float (&c)[4], float r0, float i0, float r1, float i1) {
          const float n0 = fmaf(c[0], h[0], fmaf(-c[1], h[1], r0)), n1 = fmaf(c[2], h[2], fmaf(-c[3], h[3], r1));
          h[1] = fmaf(c[0], h[1], fmaf(c[1], h[0], i0)); h[3] = fmaf(c[2], h[3], fmaf(c[3], h[2], i1));
          h[0] = n0; h[2] = n1;
        };
        ld4(cu, a);
#pragma unroll 1
        for (uint32_t ad = a0; ad != a0 + 1024; ad += 64) {
          uint32_t wr[4], wi[4];
#pragma unroll
          for (int k = 0; k < 4; k++) { wr[k] = lds32(ad + k * 16); wi[k] = lds32(ad + di + k * 16); }
#pragma unroll
          for (int k = 0; k < 4; k++) cfma(a, bflo(wr[k]), bflo(wi[k]), bfhi(wr[k]), bfhi(wi[k]));
        }
        if (half == 0) sts128(cu + 1728, __float_as_uint(h[0]), __float_as_uint(h[1]), __float_as_uint(h[2]), __float_as_uint(h[3]));
        bar_sync(NB_SCAN, 96);
        if (half == 1 && m < 15) {
          float b[4], s1[4] = {h[0], h[1], h[2], h[3]};
          ld4(cu + 576, b); ld4(cu + 1728, h);
          cfma(b, s1[0], s1[1], s1[2], s1[3]);
          uint2* gp = &g_S[epoch & 1][m][j][(cu - sb - OFF_CONST) >> 3];
          asm volatile("st.relaxed.gpu.global.v2.b64 [%0], {%1,%2};" ::"l"(gp), "l"(~(((uint64_t)__float_as_uint(h[1]) << 32) | __float_as_uint(h[0]))),
                       "l"(~(((uint64_t)__float_as_uint(h[3]) << 32) | __float_as_uint(h[2]))) : "memory");
        }
        __syncwarp();
        g_S[(epoch & 1) ^ 1][m][j][p] = make_uint2(0u, 0u);
        {
          const float2 b = lds64f(sb + OFF_CONST + 576 + p * 8);
          const float br = b.x * b.x - b.y * b.y, bi = 2.f * b.x * b.y;
          float hr = 0.f, hi = 0.f;
          const uint2* sp = &g_S[epoch & 1][0][j][p];
#pragma unroll 1
          for (int left = m; left > 0; left -= 3, sp += 3 * 768) {
            uint32_t v[3][2];
            int spins = 0;
            uint32_t ok;
            do {
#pragma unroll
              for (int k = 0; k < 3; k++) {
                v[k][0] = v[k][1] = 0xffffffffu;
                if (k < left) asm volatile("ld.relaxed.gpu.global.v2.b32 {%0,%1}, [%2];" : "=r"(v[k][0]), "=r"(v[k][1]) : "l"(sp + k * 768) : "memory");
              }
              ok = min(min(min(v[0][0], v[0][1]), min(v[1][0], v[1][1])), min(v[2][0], v[2][1]));
              if (++spins > (1 << 22)) __trap();
            } while (ok == 0u);
#pragma unroll
            for (int k = 0; k < 3; k++)
              if (k < left) { const float nr = fmaf(br, hr, fmaf(-bi, hi, __uint_as_float(~v[k][0]))); hi = fmaf(br, hi, fmaf(bi, hr, __uint_as_float(~v[k][1]))); hr = nr; }
          }
          sts64f(sb + OFF_CONST + p * 8, hr, hi);
        }
        __syncwarp();
        bar_sync(NB_SCAN, 96);
        ld4(cu, h);
        uint32_t cr, ci, cn;
        {
          float b[4], s0[4];
          ld4(cu + 576, b); ld4(cu + 1728, s0);
          if (half == 1) cfma(b, s0[0], s0[1], s0[2], s0[3]);
          ld4(cu + 1152, b);
          cr = pack_bf16(b[0], b[2]); ci = pack_bf16(b[1], b[3]); cn = ci ^ 0x80008000u;
        }
        h[1] = -h[1]; h[3] = -h[3];
        __syncwarp();
#pragma unroll 1
        for (uint32_t ad = a0; ad != a0 + 1024; ad += 32) {
          uint32_t wr[2], wi[2];
#pragma unroll
          for (int k = 0; k < 2; k++) { wr[k] = lds32(ad + k * 16); wi[k] = lds32(ad + di + k * 16); }
#pragma unroll
          for (int k = 0; k < 2; k++) {
            const float n0 = fmaf(a[0], h[0], fmaf(a[1], h[1], bflo(wr[k]))), n1 = fmaf(a[2], h[2], fmaf(a[3], h[3], bfhi(wr[k])));
            h[1] = fmaf(a[0], h[1], fmaf(-a[1], h[0], -bflo(wi[k]))); h[3] = fmaf(a[2], h[3], fmaf(-a[3], h[2], -bfhi(wi[k])));
            h[0] = n0; h[2] = n1;
            const uint32_t hr = pack_bf16(h[0], h[2]), hn = pack_bf16(h[1], h[3]);
            uint32_t o0, o1;
            asm("{.reg .b32 t; mul.rn.bf16x2 t, %2, %4; fma.rn.bf16x2 %0, %1, %3, t;}" : "=r"(o0) : "r"(hr), "r"(hn), "r"(cr), "r"(ci));
            asm("{.reg .b32 t; mul.rn.bf16x2 t, %1, %4; fma.rn.bf16x2 %0, %2, %3, t;}" : "=r"(o1) : "r"(hr), "r"(hn), "r"(cr), "r"(cn));
            asm volatile("st.shared.b32 [%0], %1;" ::"r"(ad + k * 16), "r"(o0) : "memory");
            asm volatile("st.shared.b32 [%0], %1;" ::"r"(ad + di + k * 16), "r"(o1) : "memory");
          }
        }
        asm volatile("fence.proxy.async.shared::cta;" ::: "memory");
      }
      bar_sync(NB_SCAN, 96);
      const bool lead = elect();
      if (warp == 9) {
        if (lead) {
#pragma unroll 1
          for (int i = 0; i < 10; i++) {
            const int w = i & 1, c4 = i >> 1;
            asm volatile("cp.async.bulk.global.shared::cta.bulk_group [%0], [%1], %2;" ::"l"(&g_hs[blockIdx.x][c4 < 4 ? w * HS_MAIN + c4 * 4 * HS_LBO : 2 * HS_MAIN + w * HS_REM]),
                         "r"(sb + OFF_DUMP + w * HS_BYTES + c4 * 4 * HS_LBO), "r"(c4 < 4 ? 4 * HS_LBO : HS_REM) : "memory");
            asm volatile("cp.async.bulk.commit_group;\ncp.async.bulk.wait_group.read 0;" ::: "memory");
          }
          mbar_arrive(bars + 8 * B_SCAN);
        }
        __syncwarp();
      }
      if (warp == 9) {
        if (lead) {
          __threadfence();
          asm volatile("red.release.gpu.global.add.u32 [%0], 1;" ::"l"(&g_ready[m]) : "memory");
          g_epoch[blockIdx.x] = epoch + 1u;
          asm volatile("cp.async.bulk.wait_group 0;" ::: "memory");
          mbar_arrive(bars + 8 * B_PARK);
        }
        __syncwarp();
        bar_sync(NB_HFREE, 288);
        if (lead) {
          mbar_arrive(bars + 8 * B_HFREE);
          mbar_expect(bars + 8 * B_HSFULL, 2 * HS_MAIN);
          asm volatile("cp.async.bulk.shared::cluster.global.mbarrier::complete_tx::bytes [%0], [%1], %2, [%3];" ::"r"(sb + OFF_HS),
                       "l"(&g_hs[blockIdx.x][0]), "r"(2 * HS_MAIN), "r"(bars + 8 * B_HSFULL) : "memory");
          for (int w = 0; w < 2; w++) mbar_arrive_cta(bars + 8 * (B_RFREE + w), rank ^ 1);
        }
        __syncwarp();
      } else {
        const int w = warp - 10;
        {
          const unsigned target = 8u * (epoch + 1u);
          int spins = 0;
          unsigned v;
          do {
            if (spins) __nanosleep(500);
            asm volatile("ld.relaxed.gpu.global.u32 %0, [%1];" : "=r"(v) : "l"(&g_ready[m]) : "memory");
            if (++spins > (1 << 21)) __trap();
          } while ((int)(v - target) < 0);
          asm volatile("fence.acq_rel.gpu;" ::: "memory");
          asm volatile("fence.proxy.async.global;" ::: "memory");
        }
        const uint32_t stg = sb + OFF_STG + w * 32768;
        const int nu = 5 + rank;
#pragma unroll 1
        for (int u = 0; u < nu; u++) {
          const int t = u - rank;
          if (t == 0 || t == 2) {
            if (elect()) mbar_expect(bars + 8 * (B_RFULL + w), 16384);
            mbar_wait(bars + 8 * (B_SFULL + w), u & 1);
            mbar_wait(bars + 8 * (B_RFREE + w), t >> 1);
            if (elect())
              asm volatile("{.reg .b32 ra, rb; mapa.shared::cluster.u32 ra, %0, %3; mapa.shared::cluster.u32 rb, %2, %3;\n"
                           "cp.async.bulk.shared::cluster.shared::cta.mbarrier::complete_tx::bytes [ra], [%1], 16384, [rb];}" ::"r"(stg + 16384),
                           "r"(stg), "r"(bars + 8 * (B_RFULL + w)), "r"(rank ^ 1) : "memory");
            mbar_wait(bars + 8 * (B_RFULL + w), t >> 1);
            if (elect()) mbar_arrive_cta(bars + 8 * (B_SFREE + w), rank ^ 1);
          } else {
            mbar_wait(bars + 8 * (B_SFULL + w), u & 1);
            const bool d = u == (rank ? 0 : 4), hf = rank && u >= 4;
            const int n0 = d ? 512 : rank * 256 + (((min(t, 3) >> 1) ^ (j >> 1)) & 1) * 128 + (u == 5 ? 64 : 0);
            const uint32_t src = d && !rank ? sb + w * SLOT : stg + (u == 5 ? 16384 : 0);
            if (elect()) {
#pragma unroll 1
              for (int b = 0; b < (d || hf ? 2 : 4); b++) {
                asm volatile("cp.reduce.async.bulk.tensor.4d.global.shared::cta.add.tile.bulk_group [%0, {%1,%2,%2,%3}], [%4];" ::"l"(&prm.tOut), "r"(n0 + b * 32), "r"(0),
                             "r"(m * 16 + w * 8), "r"(src + b * 8192) : "memory");
                asm volatile("cp.async.bulk.commit_group;" ::: "memory");
                if (u < nu - 1) asm volatile("cp.async.bulk.wait_group.read 0;" ::: "memory");
              }
              if (u < 3) {
                asm volatile("cp.async.bulk.wait_group.read 0;" ::: "memory");
                mbar_arrive(bars + 8 * (B_SFREE + w));
                if (t == 1) mbar_arrive_cta(bars + 8 * (B_RFREE + w), rank ^ 1);
              }
              if (u == nu - 1) asm volatile("cp.async.bulk.wait_group.read 0;" ::: "memory");
            }
          }
          __syncwarp();
        }
      }
    }
  } else {
    asm volatile("setmaxnreg.inc.sync.aligned.u32 240;");
    const uint32_t sb = smem_base(), bars = sb + OFF_BAR;
    const int wg = warp >> 2, w4 = warp & 3;
    const int lane = threadIdx.x & 31, g = lane >> 2, q = lane & 3;
    const uint32_t hw = sb + OFF_H + wg * 65536;

    int s = 0, nst = NST + 2; uint32_t ph = 0;
    auto release = [&](int st) { if (w4 == 0) { if (elect()) mbar_arrive(bars + 8 * (B_EMPTY + st)); } };
    const uint32_t dring = (sb & 0x3FFFF) >> 4;
    uint32_t dlo; int prev = 0;
    auto stage_begin = [&]() { mbar_wait(bars + 8 * (B_FULL + s), ph); dlo = dring + s * (SLOT >> 4); wg_fence(); };
    auto advance = [&]() { if (++s == nst) { s = 0; ph ^= 1; } };
    auto stage_end = [&](bool rel) {
      wg_commit();
      if (rel) { wg_wait<1>(); release(prev); }
      prev = s;
      advance();
    };

    uint32_t xa[144];
    uint32_t xr[18], dk[9];
    uint32_t rh[2], cc[2];
#pragma unroll
    for (int i = 0; i < 9; i++) dk[i] = __ldg((const uint32_t*)(prm.dskip + j * 72 + i * 8 + q * 2));
    {
      const int r = w4 * 16 + (lane & 7) + ((lane >> 3) & 1) * 8;
      const uint32_t ro = r * 128, cx = ((lane >> 4) ^ (lane & 7)) << 4;
      float s1[2][4] = {};
      auto load = [&](int kb, uint32_t base) {
#pragma unroll
        for (int kk = 0; kk < 4; kk++) {
          const int i = (kb * 4 + kk) * 4;
          asm volatile("ldmatrix.sync.aligned.m8n8.x4.shared.b16 {%0,%1,%2,%3}, [%4];"
                       : "=r"(xa[i]), "=r"(xa[i + 1]), "=r"(xa[i + 2]), "=r"(xa[i + 3]) : "r"(base + ro + (cx ^ (kk << 5))) : "memory");
        }
      };
      const uint32_t b0 = (g & 1) ? 0u : 0x3f803f80u, b1 = b0 ^ 0x3f803f80u;
      auto sums = [&](int kb) {
#pragma unroll
        for (int kk = 0; kk < 4; kk++) {
          const int i = (kb * 4 + kk) * 4;
          uint32_t a[4];
#pragma unroll
          for (int e = 0; e < 2; e++) {
            asm("mul.rn.bf16x2 %0, %1, %1;" : "=r"(a[e]) : "r"(xa[i + e]));
            asm("add.rn.bf16x2 %0, %1, %2;" : "=r"(a[2 + e]) : "r"(xa[i + e]), "r"(xa[i + 2 + e]));
            asm("fma.rn.bf16x2 %0, %1, %1, %0;" : "+r"(a[e]) : "r"(xa[i + 2 + e]));
          }
          mma16816(s1[kk & 1], a[0], a[1], a[2], a[3], b0, b1);
        }
      };
#pragma unroll
      for (int i = 0; i < 9; i++) {
        const int c8 = j * 9 + i, kb = c8 >> 3;
        xr[2 * i] = (kb < 8 ? hw + kb * 8192 : sb + wg * 8192) + (w4 * 16 + g) * 128 + (((c8 & 7) ^ g) << 4) + q * 4;
        asm volatile("" : "+r"(xr[2 * i]));
      }
      mbar_wait(bars + 8 * B_X8, 0);
      load(8, sb + wg * 8192);
      auto pin = [&]() { asm volatile("{.reg .pred p; .reg .u32 c, z; mov.u32 c, %clock; mov.u32 z, %ntid.y; setp.eq.u32 p, z, 0; @p st.shared.u32 [c], c;}" ::: "memory"); };
#pragma unroll
      for (int kp = 0; kp < 4; kp++) {
        mbar_wait(bars + 8 * (B_X + wg * 4 + kp), 0);
        load(2 * kp, hw + 2 * kp * 8192);
        load(2 * kp + 1, hw + (2 * kp + 1) * 8192);
        if (kp == 3) {
#pragma unroll
          for (int i = 0; i < 9; i++) { xr[2 * i + 1] = lds32(xr[2 * i] + 1024); xr[2 * i] = lds32(xr[2 * i]); }
        }
        if (kp == 0) sums(8); else { sums(2 * kp - 2); sums(2 * kp - 1); }
      }
      asm volatile("fence.proxy.async.shared::cta;" ::: "memory");
      bar_arrive(NB_XDONE + wg, 160);
      if (wg == 1) bar_arrive(NB_STATS, 256);
      pin();
      sums(6);
      sums(7);
      pin();
#pragma unroll
      for (int e = 0; e < 2; e++) {
        const float mu = (s1[0][2 * e + 1] + s1[1][2 * e + 1]) * (1.f / kD);
        const float var = fmaxf(fmaf(-mu, mu, (s1[0][2 * e] + s1[1][2 * e]) * (1.f / kD)), 0.f);
        float sd, r;
        asm("sqrt.approx.ftz.f32 %0, %1;" : "=f"(sd) : "f"(rbf(rbf(var) + 1e-5f)));
        asm("rcp.approx.ftz.f32 %0, %1;" : "=f"(r) : "f"(rbf(sd)));
        rh[e] = pack_bf16(0.5f * r, 0.5f * r);
        r = -mu * bfhi(rh[e]);
        cc[e] = pack_bf16(r, r);
      }
    }

    auto normalise = [&](int kb) {
#pragma unroll
      for (int i = 0; i < 16; i++) asm("fma.rn.bf16x2 %0, %0, %1, %2;" : "+r"(xa[16 * kb + (i >> 3) + 2 * (i & 7)]) : "r"(rh[i >> 3]), "r"(cc[i >> 3]));
    };
    {
      float ab[36];
      float* op = prm.out + (size_t)(m * 128 + wg * 64 + w4 * 16 + g) * kD + j * 72 + q * 2;
      auto residual = [&](int i) {
        asm volatile("add.rn.bf16x2 %0, %0, %0;" : "+r"(dk[i]));
#pragma unroll
        for (int e = 0; e < 2; e++) {
          uint32_t t;
          asm("fma.rn.bf16x2 %0, %1, %2, %3;" : "=r"(t) : "r"(xr[2 * i + e]), "r"(rh[e]), "r"(cc[e]));
          asm("fma.rn.bf16x2 %0, %0, %1, %2;" : "+r"(t) : "r"(dk[i]), "r"(xr[2 * i + e]));
          *(float2*)(op + e * 8 * kD + i * 8) = make_float2(bflo(t), bfhi(t));
        }
      };
      const uint32_t da = sb + OFF_DUMP + wg * HS_BYTES + (w4 * 16 + g) * 16 + q * 4;
      auto dump = [&](int im) {
#pragma unroll
        for (int i = 0; i < 18; i++)
          asm volatile("st.shared.b32 [%0], %1;" ::"r"(da + (i < 16 ? 8 * im + (i >> 1) : 16 + im) * HS_LBO + (i & 1) * 128), "r"(pack_bf16(ab[2 * i], ab[2 * i + 1])) : "memory");
      };
      auto bu = [&](int kb, uint32_t off) {
        wg_fence();
#pragma unroll
        for (int kk = 0; kk < 4; kk++) { const int i = (kb * 4 + kk) * 4; wgmma_n72_rs_tb0(ab, xa[i], xa[i + 1], xa[i + 2], xa[i + 3], desc((dring + (off >> 4) + kk * 2) + DLO_K, DHI_SW128), (kb | kk) != 0); }
        wg_commit();
      };
      normalise(0);
      if (wg == 0) {
#pragma unroll
        for (int kb = 1; kb < 9; kb++) normalise(kb);
        bar_sync(NB_STATS, 256);
      }
#pragma unroll
      for (int kb = 0; kb < 9; kb++) {
        if ((kb & 3) == 0) mbar_wait(bars + 8 * (B_BU + (kb >> 2)), 0);
        bu(kb, kb < 8 ? OFF_BU0 + kb * 9216 : OFF_BU1);
        if (wg == 0) residual(kb);
        else if (kb < 8) normalise(kb + 1);
      }
      wg_wait<0>();
      if (w4 == 0) { if (elect()) mbar_arrive(bars + 8 * B_RING); }
      keep(ab);
      dump(0);
#pragma unroll
      for (int kb = 0; kb < 9; kb++) {
        if (kb == 4) mbar_wait(bars + 8 * (B_BU + 3), 0);
        bu(kb, kb < 4 ? OFF_BU1 + (kb + 1) * 9216 : OFF_BU2 + (kb - 4) * 9216);
        if (wg == 1) residual(kb);
        if (kb == 5) { wg_wait<2>(); if (w4 == 0) { if (elect()) mbar_arrive(bars + 8 * (B_RING + 1)); } }
      }
      wg_wait<0>();
      keep(ab);
      dump(1);
      bar_arrive(NB_DUMP, 352);
    }

    float acc[64];
    {
      const uint32_t ha = sb + OFF_H + (threadIdx.x & 127) * 16, hblk = wg ? HBLK1 : HBLK0;
      auto glu = [&](int i) {
        return pack_bf16(fmaf(acc[32 + 2 * i], tanh_fast(acc[2 * i]), acc[32 + 2 * i]), fmaf(acc[33 + 2 * i], tanh_fast(acc[2 * i + 1]), acc[33 + 2 * i]));
      };
      for (int c = 0; c < 8; c++) {
        if (wg == 1) bar_sync(NB_SKEW, 256);
#pragma unroll
        for (int kb = 0; kb < 9; kb++) {
          if (kb == 6 && c == 3) nst = 7;
          if (kb == 5 && c == 7) nst = 6;
          stage_begin();
#pragma unroll
          for (int kk = 0; kk < 4; kk++) { const int i = (kb * 4 + kk) * 4; wgmma_n128_rs_tb1(acc, xa[i], xa[i + 1], xa[i + 2], xa[i + 3], desc((dlo + kk * 128) + DLO_MN, DHI_SW128), (kb | kk) != 0); }
          if (kb == SKEW - 1 && wg == 0) bar_arrive(NB_SKEW, 256);
          if (kb == 8 && (c == 3 || c == 4 || c == 7)) mbar_wait(bars + 8 * (c == 4 ? B_SCAN : c == 3 ? B_EMPTY + 7 : B_EMPTY + 6), c == 3);
          stage_end(kb > 0);
        }
        wg_wait<0>();
        release(prev);
        keep(acc);
        const uint32_t hc = ha + ((hblk >> (4 * c)) & 15) * 8192;
#pragma unroll
        for (int i = 0; i < 4; i++) sts128(hc + i * 2048, glu(4 * i), glu(4 * i + 1), glu(4 * i + 2), glu(4 * i + 3));
      }
      if (wg == 1) bar_sync(NB_SKEW, 256);
#pragma unroll
      for (int kb = 0; kb < 9; kb++) {
        stage_begin();
#pragma unroll
        for (int kk = 0; kk < 4; kk++) { const int i = (kb * 4 + kk) * 4; wgmma_n128_rs_tb1(acc, xa[i], xa[i + 1], xa[i + 2], xa[i + 3], desc((dlo + kk * 128) + DLO_MN, DHI_SW128), (kb | kk) != 0); }
        if (kb == SKEW - 1 && wg == 0) bar_arrive(NB_SKEW, 256);
        stage_end(kb > 0);
        if (kb > 0) {
          const uint32_t hc = ha + ((hblk >> (4 * (kb - 1))) & 15) * 8192;
#pragma unroll
          for (int i = 4 * (kb - 1); i < 4 * kb; i++) lds128_inplace(hc + (i & 3) * 2048, xa[4 * i], xa[4 * i + 1], xa[4 * i + 2], xa[4 * i + 3]);
        }
      }
      asm volatile("fence.proxy.async.shared::cta;" ::: "memory");
      bar_arrive(NB_HFREE, 288);
      wg_wait<0>();
      release(prev);
      keep(acc);
#pragma unroll
      for (int i = 0; i < 16; i++) xa[128 + i] = glu(i);
    }

    const uint32_t dhs = (((sb + OFF_HS + wg * HS_MAIN) & 0x3FFFF) >> 4) | DLO_HS, drem = DLO_HS + wg * (HS_REM >> 4);
    const int rp = (g >> 2) + 2 * (g & 3);
    const uint32_t so = w4 * 2048 + rp * 128 + (q & 1) * 8, sx = ((q >> 1) ^ rp) << 4;
    const uint32_t rcv = sb + OFF_STG + wg * 32768 + 16384 + w4 * 2048 + lane * 16;
    auto staged = [&]() {
      asm volatile("fence.proxy.async.shared::cta;" ::: "memory");
      __syncwarp();
      if (elect()) mbar_arrive(bars + 8 * (B_SFULL + wg));
    };
    auto half_tile = [&](const bool first, const int kind) {
      float a2[32];
      if (wg == 1) { if (!first) staged(); bar_sync(NB_SKEW, 256); }
      const uint32_t ph0 = ph;
      uint32_t d4;
#pragma unroll
      for (int kp = 0; kp < 5; kp++) {
        stage_begin();
#pragma unroll
        for (int kk = 0; kk < (kp < 4 ? 8 : 4); kk++) { const int i = (kp * 8 + kk) * 4; wgmma_n64_rs_tb1(a2, xa[i], xa[i + 1], xa[i + 2], xa[i + 3], desc((dlo + kk * 128) + DLO_MN, DHI_SW128), (kp | kk) != 0); }
        if (kp == 2 && wg == 0) bar_arrive(NB_SKEW, 256);
        d4 = dlo;
        stage_end(kp > 0);
        if (kp == 0 && !first && wg == 0) staged();
      }
      if (first) mbar_wait(bars + 8 * B_HSFULL, 0);
      stage_begin();
#pragma unroll
      for (int kk = 0; kk < 8; kk++) wgmma_n64_ss_tb0(a2, desc(dhs + kk * (2 * HS_LBO >> 4), DHI_NONE), desc((dlo + (kk >> 2) * 512 + (kk & 3) * 2) + DLO_K, DHI_SW128), 1);
      wgmma_n64_ss_tb0(a2, desc(d4 + 640 + drem, DHI_NONE), desc((d4 + 512) | ((1024 >> 4) << 16), DHI_NONE), 1);
      wg_commit();
      if (!first) {
        if (kind == 1) mbar_wait(bars + 8 * (B_EMPTY + wg), ph0 ^ 1);
        if (kind == 2) { mbar_wait(bars + 8 * (B_SFREE + wg), 1); mbar_wait(bars + 8 * (B_RFULL + wg), 1); }
      }
      wg_wait<0>();
      release(prev); release(s); advance();
      keep(a2);
      if (!first && kind >= 2) {
#pragma unroll
        for (int i = 0; i < 4; i++) {
          uint32_t v[4];
          lds128(rcv + (kind & 1) * 8192 + i * 512, v[0], v[1], v[2], v[3]);
#pragma unroll
          for (int e = 0; e < 4; e++) { a2[8 * i + 2 * e] += bflo(v[e]); a2[8 * i + 2 * e + 1] += bfhi(v[e]); }
        }
        __syncwarp();
      }
      const uint32_t stg = (!first && kind == 1 ? sb + wg * SLOT : sb + OFF_STG + wg * 32768 + (kind == 3 ? 16384 : 0)) + so;
#pragma unroll
      for (int i = 0; i < 8; i++) {
        const uint32_t a = stg + (i >> 2) * 8192 + (sx ^ ((i & 3) << 5));
        sts64f(a, a2[4 * i], a2[4 * i + 1]);
        sts64f(a + 1024, a2[4 * i + 2], a2[4 * i + 3]);
      }
    };
    if (rank) half_tile(true, 0);
    for (int t = 0; t < 4 - rank; t++) {
      if (wg == 1) { if (t + rank > 0) staged(); bar_sync(NB_SKEW, 256); }
#pragma unroll
      for (int kb = 0; kb < 9; kb++) {
        if ((kb == 5 && t == 0 && rank) || (kb == 1 && t == 1)) nst = NST + 1;
        if (t == 1 && ((kb == 1 && rank) || kb == 7)) nst = NST + 2;
        stage_begin();
#pragma unroll
        for (int kk = 0; kk < 4; kk++) { const int i = (kb * 4 + kk) * 4; wgmma_n128_rs_tb1(acc, xa[i], xa[i + 1], xa[i + 2], xa[i + 3], desc((dlo + kk * 128) + DLO_MN, DHI_SW128), (kb | kk) != 0); }
        if (kb == SKEW - 1 && wg == 0) bar_arrive(NB_SKEW, 256);
        stage_end(kb > 0);
        if (kb == 3 && t + rank > 0 && wg == 0) staged();
      }
      if (t == 0) mbar_wait(bars + 8 * B_HSFULL, 0);
      stage_begin();
#pragma unroll
      for (int kk = 0; kk < 4; kk++) wgmma_n128_ss_tb0(acc, desc(dhs + kk * (2 * HS_LBO >> 4), DHI_NONE), desc((dlo + kk * 2) + DLO_K, DHI_SW128), 1);
      stage_end(true);
      stage_begin();
#pragma unroll
      for (int kk = 0; kk < 4; kk++) wgmma_n128_ss_tb0(acc, desc(dhs + (4 + kk) * (2 * HS_LBO >> 4), DHI_NONE), desc((dlo + kk * 2) + DLO_K, DHI_SW128), 1);
      const int s_im = s;
      advance();
      stage_begin();
      wgmma_n128_ss_tb0(acc, desc(dlo + 256 + drem, DHI_NONE), desc(dlo | ((2048 >> 4) << 16), DHI_NONE), 1);
      stage_end(true);
      if (t + rank > 0) mbar_wait(bars + 8 * (B_SFREE + wg), (t + rank - 1) & 1);
      if (t & 1) mbar_wait(bars + 8 * (B_RFULL + wg), t >> 1);
      wg_wait<0>();
      release(s_im); release(prev);
      keep(acc);
      if (t & 1) {
        const uint32_t stg = sb + OFF_STG + wg * 32768 + so;
#pragma unroll
        for (int hh = 0; hh < 2; hh++) {
#pragma unroll
          for (int i = 4 * hh; i < 4 * hh + 4; i++) {
            uint32_t v[4];
            lds128(rcv + hh * 8192 + (i & 3) * 512, v[0], v[1], v[2], v[3]);
#pragma unroll
            for (int e = 0; e < 4; e++) { acc[8 * i + 2 * e] += bflo(v[e]); acc[8 * i + 2 * e + 1] += bfhi(v[e]); }
          }
          __syncwarp();
#pragma unroll
          for (int i = 8 * hh; i < 8 * hh + 8; i++) {
            const uint32_t a = stg + (i >> 2) * 8192 + (sx ^ ((i & 3) << 5));
            sts64f(a, acc[4 * i], acc[4 * i + 1]);
            sts64f(a + 1024, acc[4 * i + 2], acc[4 * i + 3]);
          }
        }
      } else {
#pragma unroll
        for (int i = 0; i < 8; i++)
          sts128(rcv - 16384 + (i >> 2) * 8192 + (i & 3) * 512, pack_bf16(acc[8 * i], acc[8 * i + 1]), pack_bf16(acc[8 * i + 2], acc[8 * i + 3]),
                 pack_bf16(acc[8 * i + 4], acc[8 * i + 5]), pack_bf16(acc[8 * i + 6], acc[8 * i + 7]));
      }
    }
#pragma unroll 1
    for (int kind = 1 + rank; kind < 2 + 2 * rank; kind++) half_tile(false, kind);
    staged();
  }
}

typedef CUresult (*EncodeFn)(CUtensorMap*, CUtensorMapDataType, cuuint32_t, void*, const cuuint64_t*, const cuuint64_t*, const cuuint32_t*,
                             const cuuint32_t*, CUtensorMapInterleave, CUtensorMapSwizzle, CUtensorMapL2promotion, CUtensorMapFloatOOBfill);

void map2d(EncodeFn enc, CUtensorMap* tm, const void* p, uint64_t cols, uint64_t rows, uint32_t bc, uint32_t br, CUtensorMapSwizzle sw) {
  cuuint64_t gd[2] = {cols, rows}, gs[1] = {cols * 2};
  cuuint32_t bd[2] = {bc, br}, es[2] = {1, 1};
  enc(tm, CU_TENSOR_MAP_DATA_TYPE_BFLOAT16, 2, (void*)p, gd, gs, bd, es, CU_TENSOR_MAP_INTERLEAVE_NONE, sw,
      sw == CU_TENSOR_MAP_SWIZZLE_128B ? CU_TENSOR_MAP_L2_PROMOTION_L2_128B : CU_TENSOR_MAP_L2_PROMOTION_NONE, CU_TENSOR_MAP_FLOAT_OOB_FILL_NONE);
}

}

extern "C" void kernel_launch(void* const* d_in, const int* in_sizes, int n_in, void* d_out, int out_size) {
  (void)in_sizes; (void)n_in; (void)out_size;
  static EncodeFn enc = nullptr;
  if (!enc) {
    cudaDriverEntryPointQueryResult qr;
    cudaGetDriverEntryPoint("cuTensorMapEncodeTiled", (void**)&enc, cudaEnableDefault, &qr);
    cudaFuncSetAttribute(fused_kernel, cudaFuncAttributeMaxDynamicSharedMemorySize, SMEM_BYTES);
  }
  Params prm;
  const CUtensorMapSwizzle S128 = CU_TENSOR_MAP_SWIZZLE_128B;
  map2d(enc, &prm.tx, d_in[0], kD, kS, 64, 64, S128);
  map2d(enc, &prm.tBre, d_in[3], kD, 576, 64, 72, S128);
  map2d(enc, &prm.tBim, d_in[4], kD, 576, 64, 72, S128);
  map2d(enc, &prm.tCre, d_in[5], 576, kD, 64, 64, S128);
  map2d(enc, &prm.tCim, d_in[6], 576, kD, 64, 64, S128);
  map2d(enc, &prm.tCre8, d_in[5], 576, kD, 8, 64, CU_TENSOR_MAP_SWIZZLE_NONE);
  map2d(enc, &prm.tCim8, d_in[6], 576, kD, 8, 64, CU_TENSOR_MAP_SWIZZLE_NONE);
  map2d(enc, &prm.tWg, d_in[10], kF, kD, 64, 64, S128);
  map2d(enc, &prm.tWu, d_in[11], kF, kD, 64, 64, S128);
  map2d(enc, &prm.tWd, d_in[12], kD, kF, 64, 64, S128);
  {
    cuuint64_t gd[4] = {kD, 2, 4, kS / 8}, gs[3] = {4 * kD * 4, kD * 4, 8 * kD * 4};
    cuuint32_t bd[4] = {32, 2, 4, 8}, es[4] = {1, 1, 1, 1};
    enc(&prm.tOut, CU_TENSOR_MAP_DATA_TYPE_FLOAT32, 4, d_out, gd, gs, bd, es, CU_TENSOR_MAP_INTERLEAVE_NONE, S128, CU_TENSOR_MAP_L2_PROMOTION_NONE,
        CU_TENSOR_MAP_FLOAT_OOB_FILL_NONE);
  }
  prm.lre = (const __nv_bfloat16*)d_in[1];
  prm.lim = (const __nv_bfloat16*)d_in[2];
  prm.bre = (const __nv_bfloat16*)d_in[3];
  prm.bim = (const __nv_bfloat16*)d_in[4];
  prm.cre = (const __nv_bfloat16*)d_in[5];
  prm.cim = (const __nv_bfloat16*)d_in[6];
  prm.wg = (const __nv_bfloat16*)d_in[10];
  prm.wu = (const __nv_bfloat16*)d_in[11];
  prm.wd = (const __nv_bfloat16*)d_in[12];
  prm.ldt = (const __nv_bfloat16*)d_in[7];
  prm.dskip = (const __nv_bfloat16*)d_in[8];
  prm.out = (float*)d_out;

  fused_kernel<<<128, 384, SMEM_BYTES, cudaStreamPerThread>>>(prm);
}
```

```cpp
#include <cuda_runtime.h>
#include <cuda.h>
#include <cuda_bf16.h>
#include <stdint.h>

namespace {

constexpr int kS = 2048, kD = 576, kF = 4608;
constexpr int SKEW = 4;
constexpr int PFD = 18;
constexpr int NST = 6;
constexpr uint32_t SLOT = 16384;
constexpr uint32_t OFF_H = NST * SLOT;
constexpr uint32_t HS_LBO = 1040;
constexpr uint32_t HS_BYTES = 18 * HS_LBO;
constexpr uint32_t OFF_DUMP = OFF_H + 65536 - HS_BYTES;
constexpr uint32_t OFF_STG = OFF_H + 2 * SLOT;
constexpr uint32_t OFF_HS = OFF_STG + 65536;
constexpr uint32_t HS_MAIN = 16 * HS_LBO, HS_REM = 2 * HS_LBO;
constexpr uint32_t OFF_CONST = OFF_H + 131072;
constexpr uint32_t OFF_BAR = OFF_CONST + 4 * 576;
constexpr uint32_t SMEM_BYTES = OFF_BAR + 384 + 384;
static_assert(SMEM_BYTES <= 232448 && OFF_HS + 2 * HS_MAIN <= OFF_BAR, "smem");

enum { B_FULL = 0, B_EMPTY = NST + 2, B_X = 2 * NST + 4, B_X8 = B_X + 8, B_BU  , B_RING = B_BU + 4  , B_SCAN = B_RING + 2, B_PARK, B_HFREE, B_HSFULL, B_SFULL,
       B_SFREE = B_SFULL + 2, B_RFULL = B_SFREE + 2, B_RFREE = B_RFULL + 2, B_COUNT = B_RFREE + 2 };
static_assert(B_COUNT * 8 <= 384, "barriers");
enum { NB_SKEW = 1, NB_XDONE = 2  , NB_SCAN = 4, NB_DUMP = 5, NB_HFREE = 6, NB_STATS = 7 };
constexpr uint32_t HBLK0 = 0x07652CB4u, HBLK1 = 0x189A3DEFu;
constexpr uint32_t OFF_BU0 = SLOT, OFF_BU1 = OFF_H, OFF_BU2 = OFF_H + 65536 + 19456;
static_assert(OFF_BU1 + 5 * 9216 <= OFF_DUMP && OFF_BU2 >= OFF_DUMP + 2 * HS_BYTES && OFF_BU2 + 5 * 9216 <= OFF_CONST, "Bu tiles");

struct __align__(64) Params {
  CUtensorMap tx, tBre, tBim, tWg, tWu, tWd, tCre, tCim, tCre8, tCim8, tOut;
  const __nv_bfloat16 *lre, *lim, *bre, *bim, *cre, *cim, *ldt, *dskip, *wg, *wu, *wd;
  float* out;
};

__device__ unsigned g_epoch[128];
__device__ unsigned g_ready[16];
__device__ __align__(256) uint2 g_S[2][16][8][96];
__device__ __align__(128) uint8_t g_hs[128][2 * HS_BYTES];

__device__ __forceinline__ void wgmma_n72_rs_tb0(float (&d)[36], uint32_t a0, uint32_t a1, uint32_t a2, uint32_t a3, uint64_t db, int scale_d) {
  asm volatile("{\n.reg .pred p;\nsetp.ne.b32 p, %41, 0;\n"
    "wgmma.mma_async.sync.aligned.m64n72k16.f32.bf16.bf16 {"
    "%0, %1, %2, %3, %4, %5, %6, %7, %8, %9, %10, %11, %12, %13, %14, %15, "
    "%16, %17, %18, %19, %20, %21, %22, %23, %24, %25, %26, %27, %28, %29, %30, %31, "
    "%32, %33, %34, %35"
    "}, {%36, %37, %38, %39}, %40, p, 1, 1, 0;\n}\n"
    : "+f"(d[0]), "+f"(d[1]), "+f"(d[2]), "+f"(d[3]), "+f"(d[4]), "+f"(d[5]), "+f"(d[6]), "+f"(d[7]),
      "+f"(d[8]), "+f"(d[9]), "+f"(d[10]), "+f"(d[11]), "+f"(d[12]), "+f"(d[13]), "+f"(d[14]), "+f"(d[15]),
      "+f"(d[16]), "+f"(d[17]), "+f"(d[18]), "+f"(d[19]), "+f"(d[20]), "+f"(d[21]), "+f"(d[22]), "+f"(d[23]),
      "+f"(d[24]), "+f"(d[25]), "+f"(d[26]), "+f"(d[27]), "+f"(d[28]), "+f"(d[29]), "+f"(d[30]), "+f"(d[31]),
      "+f"(d[32]), "+f"(d[33]), "+f"(d[34]), "+f"(d[35])
    : "r"(a0), "r"(a1), "r"(a2), "r"(a3), "l"(db), "r"(scale_d));
}
__device__ __forceinline__ void wgmma_n128_rs_tb1(float (&d)[64], uint32_t a0, uint32_t a1, uint32_t a2, uint32_t a3, uint64_t db, int scale_d) {
  asm volatile("{\n.reg .pred p;\nsetp.ne.b32 p, %69, 0;\n"
    "wgmma.mma_async.sync.aligned.m64n128k16.f32.bf16.bf16 {"
    "%0, %1, %2, %3, %4, %5, %6, %7, %8, %9, %10, %11, %12, %13, %14, %15, "
    "%16, %17, %18, %19, %20, %21, %22, %23, %24, %25, %26, %27, %28, %29, %30, %31, "
    "%32, %33, %34, %35, %36, %37, %38, %39, %40, %41, %42, %43, %44, %45, %46, %47, "
    "%48, %49, %50, %51, %52, %53, %54, %55, %56, %57, %58, %59, %60, %61, %62, %63"
    "}, {%64, %65, %66, %67}, %68, p, 1, 1, 1;\n}\n"
    : "+f"(d[0]), "+f"(d[1]), "+f"(d[2]), "+f"(d[3]), "+f"(d[4]), "+f"(d[5]), "+f"(d[6]), "+f"(d[7]),
      "+f"(d[8]), "+f"(d[9]), "+f"(d[10]), "+f"(d[11]), "+f"(d[12]), "+f"(d[13]), "+f"(d[14]), "+f"(d[15]),
      "+f"(d[16]), "+f"(d[17]), "+f"(d[18]), "+f"(d[19]), "+f"(d[20]), "+f"(d[21]), "+f"(d[22]), "+f"(d[23]),
      "+f"(d[24]), "+f"(d[25]), "+f"(d[26]), "+f"(d[27]), "+f"(d[28]), "+f"(d[29]), "+f"(d[30]), "+f"(d[31]),
      "+f"(d[32]), "+f"(d[33]), "+f"(d[34]), "+f"(d[35]), "+f"(d[36]), "+f"(d[37]), "+f"(d[38]), "+f"(d[39]),
      "+f"(d[40]), "+f"(d[41]), "+f"(d[42]), "+f"(d[43]), "+f"(d[44]), "+f"(d[45]), "+f"(d[46]), "+f"(d[47]),
      "+f"(d[48]), "+f"(d[49]), "+f"(d[50]), "+f"(d[51]), "+f"(d[52]), "+f"(d[53]), "+f"(d[54]), "+f"(d[55]),
      "+f"(d[56]), "+f"(d[57]), "+f"(d[58]), "+f"(d[59]), "+f"(d[60]), "+f"(d[61]), "+f"(d[62]), "+f"(d[63])
    : "r"(a0), "r"(a1), "r"(a2), "r"(a3), "l"(db), "r"(scale_d));
}
__device__ __forceinline__ void wgmma_n128_ss_tb0(float (&d)[64], uint64_t da, uint64_t db, int scale_d) {
  asm volatile("{\n.reg .pred p;\nsetp.ne.b32 p, %66, 0;\n"
    "wgmma.mma_async.sync.aligned.m64n128k16.f32.bf16.bf16 {"
    "%0, %1, %2, %3, %4, %5, %6, %7, %8, %9, %10, %11, %12, %13, %14, %15, "
    "%16, %17, %18, %19, %20, %21, %22, %23, %24, %25, %26, %27, %28, %29, %30, %31, "
    "%32, %33, %34, %35, %36, %37, %38, %39, %40, %41, %42, %43, %44, %45, %46, %47, "
    "%48, %49, %50, %51, %52, %53, %54, %55, %56, %57, %58, %59, %60, %61, %62, %63"
    "}, %64, %65, p, 1, 1, 0, 0;\n}\n"
    : "+f"(d[0]), "+f"(d[1]), "+f"(d[2]), "+f"(d[3]), "+f"(d[4]), "+f"(d[5]), "+f"(d[6]), "+f"(d[7]),
      "+f"(d[8]), "+f"(d[9]), "+f"(d[10]), "+f"(d[11]), "+f"(d[12]), "+f"(d[13]), "+f"(d[14]), "+f"(d[15]),
      "+f"(d[16]), "+f"(d[17]), "+f"(d[18]), "+f"(d[19]), "+f"(d[20]), "+f"(d[21]), "+f"(d[22]), "+f"(d[23]),
      "+f"(d[24]), "+f"(d[25]), "+f"(d[26]), "+f"(d[27]), "+f"(d[28]), "+f"(d[29]), "+f"(d[30]), "+f"(d[31]),
      "+f"(d[32]), "+f"(d[33]), "+f"(d[34]), "+f"(d[35]), "+f"(d[36]), "+f"(d[37]), "+f"(d[38]), "+f"(d[39]),
      "+f"(d[40]), "+f"(d[41]), "+f"(d[42]), "+f"(d[43]), "+f"(d[44]), "+f"(d[45]), "+f"(d[46]), "+f"(d[47]),
      "+f"(d[48]), "+f"(d[49]), "+f"(d[50]), "+f"(d[51]), "+f"(d[52]), "+f"(d[53]), "+f"(d[54]), "+f"(d[55]),
      "+f"(d[56]), "+f"(d[57]), "+f"(d[58]), "+f"(d[59]), "+f"(d[60]), "+f"(d[61]), "+f"(d[62]), "+f"(d[63])
    : "l"(da), "l"(db), "r"(scale_d));
}
__device__ __forceinline__ void wgmma_n64_rs_tb1(float (&d)[32], uint32_t a0, uint32_t a1, uint32_t a2, uint32_t a3, uint64_t db, int scale_d) {
  asm volatile("{\n.reg .pred p;\nsetp.ne.b32 p, %37, 0;\n"
    "wgmma.mma_async.sync.aligned.m64n64k16.f32.bf16.bf16 {"
    "%0, %1, %2, %3, %4, %5, %6, %7, %8, %9, %10, %11, %12, %13, %14, %15, "
    "%16, %17, %18, %19, %20, %21, %22, %23, %24, %25, %26, %27, %28, %29, %30, %31"
    "}, {%32, %33, %34, %35}, %36, p, 1, 1, 1;\n}\n"
    : "+f"(d[0]), "+f"(d[1]), "+f"(d[2]), "+f"(d[3]), "+f"(d[4]), "+f"(d[5]), "+f"(d[6]), "+f"(d[7]),
      "+f"(d[8]), "+f"(d[9]), "+f"(d[10]), "+f"(d[11]), "+f"(d[12]), "+f"(d[13]), "+f"(d[14]), "+f"(d[15]),
      "+f"(d[16]), "+f"(d[17]), "+f"(d[18]), "+f"(d[19]), "+f"(d[20]), "+f"(d[21]), "+f"(d[22]), "+f"(d[23]),
      "+f"(d[24]), "+f"(d[25]), "+f"(d[26]), "+f"(d[27]), "+f"(d[28]), "+f"(d[29]), "+f"(d[30]), "+f"(d[31])
    : "r"(a0), "r"(a1), "r"(a2), "r"(a3), "l"(db), "r"(scale_d));
}
__device__ __forceinline__ void wgmma_n64_ss_tb0(float (&d)[32], uint64_t da, uint64_t db, int scale_d) {
  asm volatile("{\n.reg .pred p;\nsetp.ne.b32 p, %34, 0;\n"
    "wgmma.mma_async.sync.aligned.m64n64k16.f32.bf16.bf16 {"
    "%0, %1, %2, %3, %4, %5, %6, %7, %8, %9, %10, %11, %12, %13, %14, %15, "
    "%16, %17, %18, %19, %20, %21, %22, %23, %24, %25, %26, %27, %28, %29, %30, %31"
    "}, %32, %33, p, 1, 1, 0, 0;\n}\n"
    : "+f"(d[0]), "+f"(d[1]), "+f"(d[2]), "+f"(d[3]), "+f"(d[4]), "+f"(d[5]), "+f"(d[6]), "+f"(d[7]),
      "+f"(d[8]), "+f"(d[9]), "+f"(d[10]), "+f"(d[11]), "+f"(d[12]), "+f"(d[13]), "+f"(d[14]), "+f"(d[15]),
      "+f"(d[16]), "+f"(d[17]), "+f"(d[18]), "+f"(d[19]), "+f"(d[20]), "+f"(d[21]), "+f"(d[22]), "+f"(d[23]),
      "+f"(d[24]), "+f"(d[25]), "+f"(d[26]), "+f"(d[27]), "+f"(d[28]), "+f"(d[29]), "+f"(d[30]), "+f"(d[31])
    : "l"(da), "l"(db), "r"(scale_d));
}

__device__ __forceinline__ bool elect() {
  uint32_t p;
  asm volatile("{.reg .pred q; elect.sync _|q, 0xffffffff; selp.u32 %0,1,0,q;}" : "=r"(p));
  return p;
}
__device__ __forceinline__ void mbar_init(uint32_t bar, uint32_t cnt) { asm volatile("mbarrier.init.shared::cta.b64 [%0], %1;" ::"r"(bar), "r"(cnt) : "memory"); }
__device__ __forceinline__ void mbar_expect(uint32_t bar, uint32_t bytes) { asm volatile("mbarrier.arrive.expect_tx.shared::cta.b64 _, [%0], %1;" ::"r"(bar), "r"(bytes) : "memory"); }
__device__ __forceinline__ void mbar_arrive(uint32_t bar) { asm volatile("mbarrier.arrive.shared::cta.b64 _, [%0];" ::"r"(bar) : "memory"); }
__device__ __forceinline__ void mbar_arrive_cta(uint32_t bar, uint32_t cta) {
  asm volatile("{.reg .b32 ra; mapa.shared::cluster.u32 ra, %0, %1; mbarrier.arrive.shared::cluster.b64 _, [ra];}" ::"r"(bar), "r"(cta) : "memory");
}
__device__ __forceinline__ void mbar_wait(uint32_t bar, uint32_t parity) {
  asm volatile(
      "{\n.reg .pred p;\n.reg .u32 c, t;\n"
      "mbarrier.try_wait.parity.shared::cta.b64 p, [%0], %1;\n@p bra DONE;\n"
      "mov.u32 c, %%clock;\n"
      "LAB_WAIT:\nmbarrier.try_wait.parity.shared::cta.b64 p, [%0], %1;\n@p bra DONE;\n"
      "mov.u32 t, %%clock;\nsub.u32 t, t, c;\nsetp.lt.u32 p, t, 0x40000000;\n@p bra LAB_WAIT;\ntrap;\nDONE:\n}" ::"r"(bar), "r"(parity) : "memory");
}
__device__ __forceinline__ void bar_sync(int id, int n) { asm volatile("bar.sync %0, %1;" ::"r"(id), "r"(n) : "memory"); }
__device__ __forceinline__ void bar_arrive(int id, int n) { asm volatile("bar.arrive %0, %1;" ::"r"(id), "r"(n) : "memory"); }
__device__ __forceinline__ void wg_fence() { asm volatile("wgmma.fence.sync.aligned;" ::: "memory"); }
__device__ __forceinline__ void wg_commit() { asm volatile("wgmma.commit_group.sync.aligned;" ::: "memory"); }
template <int N> __device__ __forceinline__ void wg_wait() { asm volatile("wgmma.wait_group.sync.aligned %0;" ::"n"(N) : "memory"); }
__device__ __forceinline__ void tma2d(uint32_t dst, const CUtensorMap* tm, uint32_t bar, int c0, int c1) {
  asm volatile("cp.async.bulk.tensor.2d.shared::cluster.global.mbarrier::complete_tx::bytes [%0], [%1,{%3,%4}], [%2];" ::"r"(dst), "l"(tm), "r"(bar), "r"(c0), "r"(c1) : "memory");
}
__device__ __forceinline__ void tma2d_mc(uint32_t dst, const CUtensorMap* tm, uint32_t bar, int c0, int c1) {
  asm volatile("cp.async.bulk.tensor.2d.shared::cluster.global.mbarrier::complete_tx::bytes.multicast::cluster [%0], [%1,{%3,%4}], [%2], %5;" ::"r"(dst), "l"(tm), "r"(bar), "r"(c0), "r"(c1), "h"((uint16_t)3) : "memory");
}
__device__ __forceinline__ void l2_prefetch_line(const void* p) { asm volatile("prefetch.global.L2 [%0];" ::"l"(p)); }
__device__ __forceinline__ uint64_t desc(uint32_t lo, uint32_t hi) { return ((uint64_t)hi << 32) | lo; }
constexpr uint32_t DHI_SW128 = (1024 >> 4) | (1u << 30);
constexpr uint32_t DHI_NONE = (128 >> 4);
constexpr uint32_t DLO_HS = (HS_LBO >> 4) << 16;
constexpr uint32_t DLO_MN = (8192 >> 4) << 16;
constexpr uint32_t DLO_K = 1u << 16;
__device__ __forceinline__ float tanh_fast(float x) { float y; asm("tanh.approx.f32 %0, %1;" : "=f"(y) : "f"(x)); return y; }
__device__ __forceinline__ uint32_t pack_bf16(float lo, float hi) { uint32_t r; asm("cvt.rn.bf16x2.f32 %0, %1, %2;" : "=r"(r) : "f"(hi), "f"(lo)); return r; }
__device__ __forceinline__ float rbf(float x) { return __uint_as_float(pack_bf16(0.f, x)); }
__device__ __forceinline__ void mma16816(float (&c)[4], uint32_t a0, uint32_t a1, uint32_t a2, uint32_t a3, uint32_t b0, uint32_t b1) {
  asm volatile("mma.sync.aligned.m16n8k16.row.col.f32.bf16.bf16.f32 {%0,%1,%2,%3}, {%4,%5,%6,%7}, {%8,%9}, {%0,%1,%2,%3};"
               : "+f"(c[0]), "+f"(c[1]), "+f"(c[2]), "+f"(c[3]) : "r"(a0), "r"(a1), "r"(a2), "r"(a3), "r"(b0), "r"(b1));
}
__device__ __forceinline__ void sts128(uint32_t a, uint32_t x, uint32_t y, uint32_t z, uint32_t w) {
  asm volatile("st.shared.v4.b32 [%0], {%1,%2,%3,%4};" ::"r"(a), "r"(x), "r"(y), "r"(z), "r"(w) : "memory");
}
__device__ __forceinline__ void sts64f(uint32_t a, float x, float y) { asm volatile("st.shared.v2.f32 [%0], {%1,%2};" ::"r"(a), "f"(x), "f"(y) : "memory"); }
__device__ __forceinline__ float2 lds64f(uint32_t a) { float2 v; asm volatile("ld.shared.v2.f32 {%0,%1}, [%2];" : "=f"(v.x), "=f"(v.y) : "r"(a) : "memory"); return v; }
__device__ __forceinline__ uint32_t lds32(uint32_t a) { uint32_t v; asm volatile("ld.shared.b32 %0, [%1];" : "=r"(v) : "r"(a) : "memory"); return v; }
__device__ __forceinline__ void lds128(uint32_t a, uint32_t& x, uint32_t& y, uint32_t& z, uint32_t& w) {
  asm volatile("ld.shared.v4.b32 {%0,%1,%2,%3}, [%4];" : "=r"(x), "=r"(y), "=r"(z), "=r"(w) : "r"(a) : "memory");
}
__device__ __forceinline__ void lds128_inplace(uint32_t a, uint32_t& x, uint32_t& y, uint32_t& z, uint32_t& w) {
  asm volatile("{.reg .pred p; .reg .u32 n; mov.u32 n, %%ntid.y; setp.ne.u32 p, n, 0; @p ld.shared.v4.b32 {%0,%1,%2,%3}, [%4];}" : "+r"(x), "+r"(y), "+r"(z), "+r"(w) : "r"(a) : "memory");
}
__device__ __forceinline__ float bflo(uint32_t v) { return __uint_as_float(v << 16); }
__device__ __forceinline__ float bfhi(uint32_t v) { return __uint_as_float(v & 0xffff0000u); }
template <int N> __device__ __forceinline__ void keep(float (&a)[N]) {
#pragma unroll
  for (int i = 0; i < N; i++) asm volatile("" : "+f"(a[i])::"memory");
}

__global__ void __cluster_dims__(2, 1, 1) __launch_bounds__(384, 1) fused_kernel(const __grid_constant__ Params prm) {
  extern __shared__ __align__(1024) uint8_t smem[];
  const int warp = __shfl_sync(0xffffffffu, threadIdx.x >> 5, 0);
  const uint32_t sb0 = (uint32_t)__cvta_generic_to_shared(smem);
  const int j = blockIdx.x & 7, m = blockIdx.x >> 3, rank = j & 1;
  auto smem_base = [&]() { return __shfl_sync(0xffffffffu, sb0 + (threadIdx.x & 31), 0); };

  if (threadIdx.x == 320) asm volatile("prefetch.tensormap [%0];" ::"l"(&prm.tx) : "memory");
  if (warp == 0) {
    if (elect()) {
#pragma unroll
      for (int i = B_X8; i >= B_X; i--) mbar_init(sb0 + OFF_BAR + 8 * i, 1);
      asm volatile("fence.mbarrier_init.release.cluster;" ::: "memory");
    }
    __syncwarp();
  }
  asm volatile("barrier.cluster.arrive.relaxed.aligned;" ::: "memory");
  if (warp == 0) {
    const uint32_t xb = sb0 + OFF_BAR;
    if (elect()) {
      mbar_expect(xb + 8 * B_X8, 16384);
      tma2d(sb0, &prm.tx, xb + 8 * B_X8, 512, m * 128);
      tma2d(sb0 + 8192, &prm.tx, xb + 8 * B_X8, 512, m * 128 + 64);
#pragma unroll
      for (int i = 0; i < 4; i++) {
        mbar_expect(xb + 8 * (B_X + i), 16384);
        tma2d(sb0 + OFF_H + i * 16384, &prm.tx, xb + 8 * (B_X + i), i * 128, m * 128);
        tma2d(sb0 + OFF_H + i * 16384 + 8192, &prm.tx, xb + 8 * (B_X + i), i * 128 + 64, m * 128);
      }
    }
    __syncwarp();
  }
  asm volatile("barrier.cluster.wait.aligned;" ::: "memory");
  if (warp == 8 || warp == 9) {
    if (elect()) {
      if (warp == 8) {
#pragma unroll
        for (int i = 0; i < B_X; i++) mbar_init(sb0 + OFF_BAR + 8 * i, i >= B_EMPTY ? 2 : 1);
      } else {
#pragma unroll
        for (int i = B_X8 + 1; i < B_COUNT; i++) mbar_init(sb0 + OFF_BAR + 8 * i, (i >= B_SFULL && i < B_SFULL + 2) ? 4 : (i == B_RING || i == B_RING + 1) ? 2 : 1);
        if (sb0 & 1023) __trap();
      }
      asm volatile("fence.mbarrier_init.release.cluster;" ::: "memory");
    }
    __syncwarp();
  }
  if (warp == 0) {
    const uint32_t xb = sb0 + OFF_BAR;
    const bool e = elect();
#pragma unroll
    for (int i = 0; i < 4; i++) {
      const int kb = i * 2 + rank;
      if (e) { mbar_expect(xb + 8 * (B_X + 4 + i), 16384); tma2d_mc(sb0 + OFF_H + 65536 + kb * 8192, &prm.tx, xb + 8 * (B_X + 4 + i), kb * 64, m * 128 + 64); }
    }
    __syncwarp();
  }
  asm volatile("barrier.cluster.arrive.relaxed.aligned;\nbarrier.cluster.wait.aligned;" ::: "memory");

  if (warp >= 8) {
    asm volatile("setmaxnreg.dec.sync.aligned.u32 24;");
    if (warp == 8) {
      const uint32_t sb = smem_base(), bars = sb + OFF_BAR;
      bool e;
      int s = 0, nst = NST + 2; uint32_t ph = 1;
      uint32_t dst, fb;
      auto acquire = [&](uint32_t bytes) {
        mbar_wait(bars + 8 * (B_EMPTY + s), ph);
        fb = bars + 8 * (B_FULL + s); dst = sb + s * SLOT;
        e = elect();
        if (e) mbar_expect(fb, bytes);
        if (++s == nst) { s = 0; ph ^= 1; }
      };
      auto box = [&](const CUtensorMap* t, uint32_t o, int a, int b) { if (e) tma2d(dst + o, t, fb, a, b); };
      auto hs_rem = [&](uint32_t o) {
        if (e) asm volatile("cp.async.bulk.shared::cluster.global.mbarrier::complete_tx::bytes [%0], [%1], %2, [%3];" ::"r"(dst + o),
                            "l"(&g_hs[blockIdx.x][2 * HS_MAIN]), "r"(2 * HS_REM), "r"(fb) : "memory");
      };
      const int lane = threadIdx.x & 31;
      const char* pf = lane < 8 ? (const char*)(lane & 4 ? prm.wu : prm.wg) + ((size_t)(m * 4 + (lane & 3)) * kF + j * 576) * 2
                     : lane < 12 ? (const char*)prm.wd + (size_t)j * 576 * 1152 + (m * 324 + (lane & 3)) * 128
                                 : (const char*)(lane & 1 ? prm.cim : prm.cre) + (size_t)blockIdx.x * 5184;
      int pk = 0, pleft = 81;
      auto prefetch = [&]() {
        if (pleft > 0) {
          if (lane < 14) l2_prefetch_line(pf);
          pf += lane < 8 ? (pk == 8 ? 128 - 8 * 64 * kF * 2 : 64 * kF * 2) : lane < 12 ? 512 : 64;
          pk = pk == 8 ? 0 : pk + 1;
          pleft--;
        }
      };
      mbar_wait(bars + 8 * B_X8, 0);
      e = elect();
#pragma unroll 1
      for (int kb = 0; kb < 8; kb++) {
        fb = bars + 8 * (B_BU + (kb >> 2));
        if (e) { if ((kb & 3) == 0) mbar_expect(fb, 4 * 9216); tma2d(sb + OFF_BU0 + kb * 9216, &prm.tBre, fb, kb * 64, j * 72); }
      }
      bar_sync(NB_XDONE, 160);
      fb = bars + 8 * (B_BU + 2);
      if (e) { mbar_expect(fb, 5 * 9216); tma2d(sb + OFF_BU1, &prm.tBre, fb, 512, j * 72); }
#pragma unroll 1
      for (int kb = 0; kb < 4; kb++) if (e) tma2d(sb + OFF_BU1 + (kb + 1) * 9216, &prm.tBim, fb, kb * 64, j * 72);
      for (int i = 0; i < PFD / 2; i++) prefetch();
      bar_sync(NB_XDONE + 1, 160);
      fb = bars + 8 * (B_BU + 3);
      if (e) mbar_expect(fb, 5 * 9216);
#pragma unroll 1
      for (int kb = 4; kb < 9; kb++) if (e) tma2d(sb + OFF_BU2 + (kb - 4) * 9216, &prm.tBim, fb, kb * 64, j * 72);
      for (int i = PFD / 2; i < PFD; i++) prefetch();
      mbar_wait(bars + 8 * B_RING, 0);
      for (int c = 0; c < 9; c++) {
        const int col = j * 576 + c * 64;
#pragma unroll 1
        for (int kb = 0; kb < 9; kb++) {
          if (kb == 6 && c == 0) mbar_wait(bars + 8 * (B_RING + 1), 0);
          if (kb == 6 && c == 3) nst = 7;
          if (kb == 5 && c == 7) nst = 6;
          acquire(16384); box(&prm.tWg, 0, col, kb * 64); box(&prm.tWu, 8192, col, kb * 64); prefetch();
        }
      }
      auto half_tile = [&](int n0) {
#pragma unroll 1
        for (int kp = 0; kp < 4; kp++) { acquire(16384); box(&prm.tWd, 0, n0, j * 576 + kp * 128); box(&prm.tWd, 8192, n0, j * 576 + kp * 128 + 64); }
        acquire(8192 + 2048 + 2 * HS_REM); box(&prm.tWd, 0, n0, j * 576 + 512); box(&prm.tCre8, 8192, j * 72 + 64, n0); box(&prm.tCim8, 9216, j * 72 + 64, n0); hs_rem(10240);
        acquire(16384); box(&prm.tCre, 0, j * 72, n0); box(&prm.tCim, 8192, j * 72, n0);
      };
      mbar_wait(bars + 8 * B_PARK, 0);
      asm volatile("fence.proxy.async.global;" ::: "memory");
      if (rank) half_tile(512);
#pragma unroll 1
      for (int t = 0; t < 4 - rank; t++) {
        const int n0 = ((rank ^ t ^ 1) & 1) * 256 + (((t >> 1) ^ (j >> 1)) & 1) * 128;
#pragma unroll 1
        for (int kb = 0; kb < 9; kb++) {
          if (rank ? (t == 0 && kb == 5) : (t == 1 && kb == 1)) nst = NST + 1;
          if (t == 1 && kb == (rank ? 1 : 7)) nst = NST + 2;
          if (kb == 3 && t == 0 && rank) mbar_wait(bars + 8 * B_HFREE, 0);
          acquire(16384); box(&prm.tWd, 0, n0, j * 576 + kb * 64); box(&prm.tWd, 8192, n0 + 64, j * 576 + kb * 64);
        }
        if (t == 0) mbar_wait(bars + 8 * B_HFREE, 0);
        acquire(16384); box(&prm.tCre, 0, j * 72, n0); box(&prm.tCre, 8192, j * 72, n0 + 64);
        acquire(16384); box(&prm.tCim, 0, j * 72, n0); box(&prm.tCim, 8192, j * 72, n0 + 64);
        acquire(4096 + 2 * HS_REM); hs_rem(4096);
        box(&prm.tCre8, 0, j * 72 + 64, n0); box(&prm.tCre8, 1024, j * 72 + 64, n0 + 64);
        box(&prm.tCim8, 2048, j * 72 + 64, n0); box(&prm.tCim8, 3072, j * 72 + 64, n0 + 64);
      }
      if (!rank) half_tile(512);
      else {
#pragma unroll 1
        for (int hh = 0; hh < 2; hh++) half_tile(256 + (((j >> 1) ^ 1) & 1) * 128 + hh * 64);
      }
    } else {
      const uint32_t sb = smem_base(), bars = sb + OFF_BAR;
      const int p = min((int)threadIdx.x - 288, 71);
      if (threadIdx.x < 288 + 10) asm volatile("prefetch.tensormap [%0];" ::"l"(&prm.tBre + (threadIdx.x - 288)) : "memory");
      if (warp == 10) {
        const int l = threadIdx.x & 31;
        const char* q = (const char*)(l & 1 ? prm.bim : prm.bre) + (size_t)blockIdx.x * 5184;
        mbar_wait(bars + 8 * B_X8, 0);
#pragma unroll
        for (int i = 0; i < 3; i++) if (i * 16 + (l >> 1) < 42) l2_prefetch_line(q + min((i * 16 + (l >> 1)) * 128, 5183));
      }
      const unsigned epoch = *(volatile unsigned*)&g_epoch[blockIdx.x];
      {
        const int pg = j * 72 + p;
        const float lr = __bfloat162float(prm.lre[pg]), li = __bfloat162float(prm.lim[pg]);
        const float dt = rbf(expf(__bfloat162float(prm.ldt[pg])));
        const float ea = expf(dt * lr);
        float sn, cs;
        sincosf(dt * li, &sn, &cs);
        const float ar = ea * cs, ai = ea * sn;
        float br = ar, bi = ai;
#pragma unroll
        for (int k = 0; k < 6; k++) { const float t = br * br - bi * bi; bi = 2.f * br * bi; br = t; }
        const float nr = ar - 1.f, den = 4.f / (lr * lr + li * li);
        sts64f(sb + OFF_CONST + p * 8, ar, ai);
        sts64f(sb + OFF_CONST + 576 + p * 8, br, bi);
        sts64f(sb + OFF_CONST + 1152 + p * 8, (nr * lr + ai * li) * den, (ai * lr - nr * li) * den);
      }
      bar_sync(NB_DUMP, 352);
      {
        const int lane = threadIdx.x & 31;
        const int half = warp == 11 ? (lane >> 2) & 1 : warp - 9;
        const uint32_t cu = sb + OFF_CONST + (warp == 11 ? 32 + (lane & 3) : lane) * 16;
        uint32_t a0 = sb + OFF_DUMP + half * HS_BYTES + (warp == 11 ? 16 : lane >> 2) * HS_LBO + (lane & 3) * 4;
        asm volatile("" : "+r"(a0));
        const uint32_t di = warp == 11 ? HS_LBO : 8 * HS_LBO;
        float a[4], h[4] = {0.f, 0.f, 0.f, 0.f};
        auto ld4 = [&](uint32_t ad, float (&v)[4]) { asm volatile("ld.shared.v4.f32 {%0,%1,%2,%3}, [%4];" : "=f"(v[0]), "=f"(v[1]), "=f"(v[2]), "=f"(v[3]) : "r"(ad) : "memory"); };
        auto cfma = [&](const float (&c)[4], float r0, float i0, float r1, float i1) {
          const float n0 = fmaf(c[0], h[0], fmaf(-c[1], h[1], r0)), n1 = fmaf(c[2], h[2], fmaf(-c[3], h[3], r1));
          h[1] = fmaf(c[0], h[1], fmaf(c[1], h[0], i0)); h[3] = fmaf(c[2], h[3], fmaf(c[3], h[2], i1));
          h[0] = n0; h[2] = n1;
        };
        ld4(cu, a);
#pragma unroll 1
        for (uint32_t ad = a0; ad != a0 + 1024; ad += 64) {
          uint32_t wr[4], wi[4];
#pragma unroll
          for (int k = 0; k < 4; k++) { wr[k] = lds32(ad + k * 16); wi[k] = lds32(ad + di + k * 16); }
#pragma unroll
          for (int k = 0; k < 4; k++) cfma(a, bflo(wr[k]), bflo(wi[k]), bfhi(wr[k]), bfhi(wi[k]));
        }
        if (half == 0) sts128(cu + 1728, __float_as_uint(h[0]), __float_as_uint(h[1]), __float_as_uint(h[2]), __float_as_uint(h[3]));
        bar_sync(NB_SCAN, 96);
        if (half == 1 && m < 15) {
          float b[4], s1[4] = {h[0], h[1], h[2], h[3]};
          ld4(cu + 576, b); ld4(cu + 1728, h);
          cfma(b, s1[0], s1[1], s1[2], s1[3]);
          uint2* gp = &g_S[epoch & 1][m][j][(cu - sb - OFF_CONST) >> 3];
          asm volatile("st.relaxed.gpu.global.v2.b64 [%0], {%1,%2};" ::"l"(gp), "l"(~(((uint64_t)__float_as_uint(h[1]) << 32) | __float_as_uint(h[0]))),
                       "l"(~(((uint64_t)__float_as_uint(h[3]) << 32) | __float_as_uint(h[2]))) : "memory");
        }
        __syncwarp();
        g_S[(epoch & 1) ^ 1][m][j][p] = make_uint2(0u, 0u);
        {
          const float2 b = lds64f(sb + OFF_CONST + 576 + p * 8);
          const float br = b.x * b.x - b.y * b.y, bi = 2.f * b.x * b.y;
          float hr = 0.f, hi = 0.f;
          const uint2* sp = &g_S[epoch & 1][0][j][p];
#pragma unroll 1
          for (int left = m; left > 0; left -= 3, sp += 3 * 768) {
            uint32_t v[3][2];
            int spins = 0;
            uint32_t ok;
            do {
#pragma unroll
              for (int k = 0; k < 3; k++) {
                v[k][0] = v[k][1] = 0xffffffffu;
                if (k < left) asm volatile("ld.relaxed.gpu.global.v2.b32 {%0,%1}, [%2];" : "=r"(v[k][0]), "=r"(v[k][1]) : "l"(sp + k * 768) : "memory");
              }
              ok = min(min(min(v[0][0], v[0][1]), min(v[1][0], v[1][1])), min(v[2][0], v[2][1]));
              if (++spins > (1 << 22)) __trap();
            } while (ok == 0u);
#pragma unroll
            for (int k = 0; k < 3; k++)
              if (k < left) { const float nr = fmaf(br, hr, fmaf(-bi, hi, __uint_as_float(~v[k][0]))); hi = fmaf(br, hi, fmaf(bi, hr, __uint_as_float(~v[k][1]))); hr = nr; }
          }
          sts64f(sb + OFF_CONST + p * 8, hr, hi);
        }
        __syncwarp();
        bar_sync(NB_SCAN, 96);
        ld4(cu, h);
        uint32_t cr, ci, cn;
        {
          float b[4], s0[4];
          ld4(cu + 576, b); ld4(cu + 1728, s0);
          if (half == 1) cfma(b, s0[0], s0[1], s0[2], s0[3]);
          ld4(cu + 1152, b);
          cr = pack_bf16(b[0], b[2]); ci = pack_bf16(b[1], b[3]); cn = ci ^ 0x80008000u;
        }
        h[1] = -h[1]; h[3] = -h[3];
        __syncwarp();
#pragma unroll 1
        for (uint32_t ad = a0; ad != a0 + 1024; ad += 32) {
          uint32_t wr[2], wi[2];
#pragma unroll
          for (int k = 0; k < 2; k++) { wr[k] = lds32(ad + k * 16); wi[k] = lds32(ad + di + k * 16); }
#pragma unroll
          for (int k = 0; k < 2; k++) {
            const float n0 = fmaf(a[0], h[0], fmaf(a[1], h[1], bflo(wr[k]))), n1 = fmaf(a[2], h[2], fmaf(a[3], h[3], bfhi(wr[k])));
            h[1] = fmaf(a[0], h[1], fmaf(-a[1], h[0], -bflo(wi[k]))); h[3] = fmaf(a[2], h[3], fmaf(-a[3], h[2], -bfhi(wi[k])));
            h[0] = n0; h[2] = n1;
            const uint32_t hr = pack_bf16(h[0], h[2]), hn = pack_bf16(h[1], h[3]);
            uint32_t o0, o1;
            asm("{.reg .b32 t; mul.rn.bf16x2 t, %2, %4; fma.rn.bf16x2 %0, %1, %3, t;}" : "=r"(o0) : "r"(hr), "r"(hn), "r"(cr), "r"(ci));
            asm("{.reg .b32 t; mul.rn.bf16x2 t, %1, %4; fma.rn.bf16x2 %0, %2, %3, t;}" : "=r"(o1) : "r"(hr), "r"(hn), "r"(cr), "r"(cn));
            asm volatile("st.shared.b32 [%0], %1;" ::"r"(ad + k * 16), "r"(o0) : "memory");
            asm volatile("st.shared.b32 [%0], %1;" ::"r"(ad + di + k * 16), "r"(o1) : "memory");
          }
        }
        asm volatile("fence.proxy.async.shared::cta;" ::: "memory");
      }
      bar_sync(NB_SCAN, 96);
      const bool lead = elect();
      if (warp == 9) {
        if (lead) {
#pragma unroll 1
          for (int i = 0; i < 10; i++) {
            const int w = i & 1, c4 = i >> 1;
            asm volatile("cp.async.bulk.global.shared::cta.bulk_group [%0], [%1], %2;" ::"l"(&g_hs[blockIdx.x][c4 < 4 ? w * HS_MAIN + c4 * 4 * HS_LBO : 2 * HS_MAIN + w * HS_REM]),
                         "r"(sb + OFF_DUMP + w * HS_BYTES + c4 * 4 * HS_LBO), "r"(c4 < 4 ? 4 * HS_LBO : HS_REM) : "memory");
            asm volatile("cp.async.bulk.commit_group;\ncp.async.bulk.wait_group.read 0;" ::: "memory");
          }
          mbar_arrive(bars + 8 * B_SCAN);
        }
        __syncwarp();
      }
      if (warp == 9) {
        if (lead) {
          __threadfence();
          asm volatile("red.release.gpu.global.add.u32 [%0], 1;" ::"l"(&g_ready[m]) : "memory");
          g_epoch[blockIdx.x] = epoch + 1u;
          asm volatile("cp.async.bulk.wait_group 0;" ::: "memory");
          mbar_arrive(bars + 8 * B_PARK);
        }
        __syncwarp();
        bar_sync(NB_HFREE, 288);
        if (lead) {
          mbar_arrive(bars + 8 * B_HFREE);
          mbar_expect(bars + 8 * B_HSFULL, 2 * HS_MAIN);
          asm volatile("cp.async.bulk.shared::cluster.global.mbarrier::complete_tx::bytes [%0], [%1], %2, [%3];" ::"r"(sb + OFF_HS),
                       "l"(&g_hs[blockIdx.x][0]), "r"(2 * HS_MAIN), "r"(bars + 8 * B_HSFULL) : "memory");
          for (int w = 0; w < 2; w++) mbar_arrive_cta(bars + 8 * (B_RFREE + w), rank ^ 1);
        }
        __syncwarp();
      } else {
        const int w = warp - 10;
        {
          const unsigned target = 8u * (epoch + 1u);
          int spins = 0;
          unsigned v;
          do {
            if (spins) __nanosleep(500);
            asm volatile("ld.relaxed.gpu.global.u32 %0, [%1];" : "=r"(v) : "l"(&g_ready[m]) : "memory");
            if (++spins > (1 << 21)) __trap();
          } while ((int)(v - target) < 0);
          asm volatile("fence.acq_rel.gpu;" ::: "memory");
          asm volatile("fence.proxy.async.global;" ::: "memory");
        }
        const uint32_t stg = sb + OFF_STG + w * 32768;
        const int nu = 5 + rank;
#pragma unroll 1
        for (int u = 0; u < nu; u++) {
          const int t = u - rank;
          if (t == 0 || t == 2) {
            if (elect()) mbar_expect(bars + 8 * (B_RFULL + w), 16384);
            mbar_wait(bars + 8 * (B_SFULL + w), u & 1);
            mbar_wait(bars + 8 * (B_RFREE + w), t >> 1);
            if (elect())
              asm volatile("{.reg .b32 ra, rb; mapa.shared::cluster.u32 ra, %0, %3; mapa.shared::cluster.u32 rb, %2, %3;\n"
                           "cp.async.bulk.shared::cluster.shared::cta.mbarrier::complete_tx::bytes [ra], [%1], 16384, [rb];}" ::"r"(stg + 16384),
                           "r"(stg), "r"(bars + 8 * (B_RFULL + w)), "r"(rank ^ 1) : "memory");
            mbar_wait(bars + 8 * (B_RFULL + w), t >> 1);
            if (elect()) mbar_arrive_cta(bars + 8 * (B_SFREE + w), rank ^ 1);
          } else {
            mbar_wait(bars + 8 * (B_SFULL + w), u & 1);
            const bool d = u == (rank ? 0 : 4), hf = rank && u >= 4;
            const int n0 = d ? 512 : rank * 256 + (((min(t, 3) >> 1) ^ (j >> 1)) & 1) * 128 + (u == 5 ? 64 : 0);
            const uint32_t src = d && !rank ? sb + w * SLOT : stg + (u == 5 ? 16384 : 0);
            if (elect()) {
#pragma unroll 1
              for (int b = 0; b < (d || hf ? 2 : 4); b++) {
                asm volatile("cp.reduce.async.bulk.tensor.4d.global.shared::cta.add.tile.bulk_group [%0, {%1,%2,%2,%3}], [%4];" ::"l"(&prm.tOut), "r"(n0 + b * 32), "r"(0),
                             "r"(m * 16 + w * 8), "r"(src + b * 8192) : "memory");
                asm volatile("cp.async.bulk.commit_group;" ::: "memory");
                if (u < nu - 1) asm volatile("cp.async.bulk.wait_group.read 0;" ::: "memory");
              }
              if (u < 3) {
                asm volatile("cp.async.bulk.wait_group.read 0;" ::: "memory");
                mbar_arrive(bars + 8 * (B_SFREE + w));
                if (t == 1) mbar_arrive_cta(bars + 8 * (B_RFREE + w), rank ^ 1);
              }
              if (u == nu - 1) asm volatile("cp.async.bulk.wait_group.read 0;" ::: "memory");
            }
          }
          __syncwarp();
        }
      }
    }
  } else {
    asm volatile("setmaxnreg.inc.sync.aligned.u32 240;");
    const uint32_t sb = smem_base(), bars = sb + OFF_BAR;
    const int wg = warp >> 2, w4 = warp & 3;
    const int lane = threadIdx.x & 31, g = lane >> 2, q = lane & 3;
    const uint32_t hw = sb + OFF_H + wg * 65536;

    int s = 0, nst = NST + 2; uint32_t ph = 0;
    auto release = [&](int st) { if (w4 == 0) { if (elect()) mbar_arrive(bars + 8 * (B_EMPTY + st)); } };
    const uint32_t dring = (sb & 0x3FFFF) >> 4;
    uint32_t dlo; int prev = 0;
    auto stage_begin = [&]() { mbar_wait(bars + 8 * (B_FULL + s), ph); dlo = dring + s * (SLOT >> 4); wg_fence(); };
    auto advance = [&]() { if (++s == nst) { s = 0; ph ^= 1; } };
    auto stage_end = [&](bool rel) {
      wg_commit();
      if (rel) { wg_wait<1>(); release(prev); }
      prev = s;
      advance();
    };

    uint32_t xa[144];
    uint32_t xr[18], dk[9];
    uint32_t rh[2], cc[2];
#pragma unroll
    for (int i = 0; i < 9; i++) dk[i] = __ldg((const uint32_t*)(prm.dskip + j * 72 + i * 8 + q * 2));
    {
      const int r = w4 * 16 + (lane & 7) + ((lane >> 3) & 1) * 8;
      const uint32_t ro = r * 128, cx = ((lane >> 4) ^ (lane & 7)) << 4;
      float s1[2][4] = {};
      auto load = [&](int kb, uint32_t base) {
#pragma unroll
        for (int kk = 0; kk < 4; kk++) {
          const int i = (kb * 4 + kk) * 4;
          asm volatile("ldmatrix.sync.aligned.m8n8.x4.shared.b16 {%0,%1,%2,%3}, [%4];"
                       : "=r"(xa[i]), "=r"(xa[i + 1]), "=r"(xa[i + 2]), "=r"(xa[i + 3]) : "r"(base + ro + (cx ^ (kk << 5))) : "memory");
        }
      };
      float s2[4] = {}, s3[4] = {};
      auto sums = [&](int kb) {
#pragma unroll
        for (int kk = 0; kk < 4; kk += 2) {
          const int i = (kb * 4 + kk) * 4;
          uint32_t a[8];
#pragma unroll
          for (int e = 0; e < 8; e++) asm("mul.rn.bf16x2 %0, %1, %1;" : "=r"(a[e]) : "r"(xa[i + e]));
          mma16816(s3, a[4], a[5], a[6], a[7], 0x3f803f80u, 0x3f803f80u);
          mma16816(s1[0], xa[i], xa[i + 1], xa[i + 2], xa[i + 3], 0x3f803f80u, 0x3f803f80u);
          mma16816(s2, a[0], a[1], a[2], a[3], 0x3f803f80u, 0x3f803f80u);
          mma16816(s1[1], xa[i + 4], xa[i + 5], xa[i + 6], xa[i + 7], 0x3f803f80u, 0x3f803f80u);
        }
      };
#pragma unroll
      for (int i = 0; i < 9; i++) {
        const int c8 = j * 9 + i, kb = c8 >> 3;
        xr[2 * i] = (kb < 8 ? hw + kb * 8192 : sb + wg * 8192) + (w4 * 16 + g) * 128 + (((c8 & 7) ^ g) << 4) + q * 4;
        asm volatile("" : "+r"(xr[2 * i]));
      }
      mbar_wait(bars + 8 * B_X8, 0);
      load(8, sb + wg * 8192);
      auto pin = [&]() { asm volatile("{.reg .pred p; .reg .u32 c, z; mov.u32 c, %clock; mov.u32 z, %ntid.y; setp.eq.u32 p, z, 0; @p st.shared.u32 [c], c;}" ::: "memory"); };
#pragma unroll
      for (int kp = 0; kp < 4; kp++) {
        mbar_wait(bars + 8 * (B_X + wg * 4 + kp), 0);
        load(2 * kp, hw + 2 * kp * 8192);
        load(2 * kp + 1, hw + (2 * kp + 1) * 8192);
        if (kp == 3) {
#pragma unroll
          for (int i = 0; i < 9; i++) { xr[2 * i + 1] = lds32(xr[2 * i] + 1024); xr[2 * i] = lds32(xr[2 * i]); }
        }
        if (kp == 0) sums(8); else { sums(2 * kp - 2); sums(2 * kp - 1); }
      }
      asm volatile("fence.proxy.async.shared::cta;" ::: "memory");
      bar_arrive(NB_XDONE + wg, 160);
      if (wg == 1) bar_arrive(NB_STATS, 256);
      pin();
      sums(6);
      sums(7);
      pin();
#pragma unroll
      for (int e = 0; e < 2; e++) {
        const float mu = (s1[0][2 * e + 1] + s1[1][2 * e + 1]) * (1.f / kD);
        const float var = fmaxf(fmaf(-mu, mu, (s2[2 * e] + s3[2 * e]) * (1.f / kD)), 0.f);
        float sd, r;
        asm("sqrt.approx.ftz.f32 %0, %1;" : "=f"(sd) : "f"(rbf(rbf(var) + 1e-5f)));
        asm("rcp.approx.ftz.f32 %0, %1;" : "=f"(r) : "f"(rbf(sd)));
        rh[e] = pack_bf16(0.5f * r, 0.5f * r);
        cc[e] = pack_bf16(mu, mu);
      }
    }

    auto normalise = [&](int kb) {
#pragma unroll
      for (int i = 0; i < 16; i++) asm("{.reg .b32 d; sub.rn.bf16x2 d, %0, %2; mul.rn.bf16x2 %0, d, %1;}" : "+r"(xa[16 * kb + (i >> 3) + 2 * (i & 7)]) : "r"(rh[i >> 3]), "r"(cc[i >> 3]));
    };
    {
      float ab[36];
      float* op = prm.out + (size_t)(m * 128 + wg * 64 + w4 * 16 + g) * kD + j * 72 + q * 2;
      auto residual = [&](int i) {
        asm volatile("add.rn.bf16x2 %0, %0, %0;" : "+r"(dk[i]));
#pragma unroll
        for (int e = 0; e < 2; e++) {
          uint32_t t;
          asm("{.reg .b32 d; sub.rn.bf16x2 d, %1, %3; mul.rn.bf16x2 %0, d, %2;}" : "=r"(t) : "r"(xr[2 * i + e]), "r"(rh[e]), "r"(cc[e]));
          asm("fma.rn.bf16x2 %0, %0, %1, %2;" : "+r"(t) : "r"(dk[i]), "r"(xr[2 * i + e]));
          *(float2*)(op + e * 8 * kD + i * 8) = make_float2(bflo(t), bfhi(t));
        }
      };
      const uint32_t da = sb + OFF_DUMP + wg * HS_BYTES + (w4 * 16 + g) * 16 + q * 4;
      auto dump = [&](int im) {
#pragma unroll
        for (int i = 0; i < 18; i++)
          asm volatile("st.shared.b32 [%0], %1;" ::"r"(da + (i < 16 ? 8 * im + (i >> 1) : 16 + im) * HS_LBO + (i & 1) * 128), "r"(pack_bf16(ab[2 * i], ab[2 * i + 1])) : "memory");
      };
      auto bu = [&](int kb, uint32_t off) {
        wg_fence();
#pragma unroll
        for (int kk = 0; kk < 4; kk++) { const int i = (kb * 4 + kk) * 4; wgmma_n72_rs_tb0(ab, xa[i], xa[i + 1], xa[i + 2], xa[i + 3], desc((dring + (off >> 4) + kk * 2) + DLO_K, DHI_SW128), (kb | kk) != 0); }
        wg_commit();
      };
      normalise(0);
      if (wg == 0) {
#pragma unroll
        for (int kb = 1; kb < 9; kb++) normalise(kb);
        bar_sync(NB_STATS, 256);
      }
#pragma unroll
      for (int kb = 0; kb < 9; kb++) {
        if ((kb & 3) == 0) mbar_wait(bars + 8 * (B_BU + (kb >> 2)), 0);
        bu(kb, kb < 8 ? OFF_BU0 + kb * 9216 : OFF_BU1);
        if (wg == 0) residual(kb);
        else if (kb < 8) normalise(kb + 1);
      }
      wg_wait<0>();
      if (w4 == 0) { if (elect()) mbar_arrive(bars + 8 * B_RING); }
      keep(ab);
      dump(0);
#pragma unroll
      for (int kb = 0; kb < 9; kb++) {
        if (kb == 4) mbar_wait(bars + 8 * (B_BU + 3), 0);
        bu(kb, kb < 4 ? OFF_BU1 + (kb + 1) * 9216 : OFF_BU2 + (kb - 4) * 9216);
        if (wg == 1) residual(kb);
        if (kb == 5) { wg_wait<2>(); if (w4 == 0) { if (elect()) mbar_arrive(bars + 8 * (B_RING + 1)); } }
      }
      wg_wait<0>();
      keep(ab);
      dump(1);
      bar_arrive(NB_DUMP, 352);
    }

    float acc[64];
    {
      const uint32_t ha = sb + OFF_H + (threadIdx.x & 127) * 16, hblk = wg ? HBLK1 : HBLK0;
      auto glu = [&](int i) {
        return pack_bf16(fmaf(acc[32 + 2 * i], tanh_fast(acc[2 * i]), acc[32 + 2 * i]), fmaf(acc[33 + 2 * i], tanh_fast(acc[2 * i + 1]), acc[33 + 2 * i]));
      };
      for (int c = 0; c < 8; c++) {
        if (wg == 1) bar_sync(NB_SKEW, 256);
#pragma unroll
        for (int kb = 0; kb < 9; kb++) {
          if (kb == 6 && c == 3) nst = 7;
          if (kb == 5 && c == 7) nst = 6;
          stage_begin();
#pragma unroll
          for (int kk = 0; kk < 4; kk++) { const int i = (kb * 4 + kk) * 4; wgmma_n128_rs_tb1(acc, xa[i], xa[i + 1], xa[i + 2], xa[i + 3], desc((dlo + kk * 128) + DLO_MN, DHI_SW128), (kb | kk) != 0); }
          if (kb == SKEW - 1 && wg == 0) bar_arrive(NB_SKEW, 256);
          if (kb == 8 && (c == 3 || c == 4 || c == 7)) mbar_wait(bars + 8 * (c == 4 ? B_SCAN : c == 3 ? B_EMPTY + 7 : B_EMPTY + 6), c == 3);
          stage_end(kb > 0);
        }
        wg_wait<0>();
        release(prev);
        keep(acc);
        const uint32_t hc = ha + ((hblk >> (4 * c)) & 15) * 8192;
#pragma unroll
        for (int i = 0; i < 4; i++) sts128(hc + i * 2048, glu(4 * i), glu(4 * i + 1), glu(4 * i + 2), glu(4 * i + 3));
      }
      if (wg == 1) bar_sync(NB_SKEW, 256);
#pragma unroll
      for (int kb = 0; kb < 9; kb++) {
        stage_begin();
#pragma unroll
        for (int kk = 0; kk < 4; kk++) { const int i = (kb * 4 + kk) * 4; wgmma_n128_rs_tb1(acc, xa[i], xa[i + 1], xa[i + 2], xa[i + 3], desc((dlo + kk * 128) + DLO_MN, DHI_SW128), (kb | kk) != 0); }
        if (kb == SKEW - 1 && wg == 0) bar_arrive(NB_SKEW, 256);
        stage_end(kb > 0);
        if (kb > 0) {
          const uint32_t hc = ha + ((hblk >> (4 * (kb - 1))) & 15) * 8192;
#pragma unroll
          for (int i = 4 * (kb - 1); i < 4 * kb; i++) lds128_inplace(hc + (i & 3) * 2048, xa[4 * i], xa[4 * i + 1], xa[4 * i + 2], xa[4 * i + 3]);
        }
      }
      asm volatile("fence.proxy.async.shared::cta;" ::: "memory");
      bar_arrive(NB_HFREE, 288);
      wg_wait<0>();
      release(prev);
      keep(acc);
#pragma unroll
      for (int i = 0; i < 16; i++) xa[128 + i] = glu(i);
    }

    const uint32_t dhs = (((sb + OFF_HS + wg * HS_MAIN) & 0x3FFFF) >> 4) | DLO_HS, drem = DLO_HS + wg * (HS_REM >> 4);
    const int rp = (g >> 2) + 2 * (g & 3);
    const uint32_t so = w4 * 2048 + rp * 128 + (q & 1) * 8, sx = ((q >> 1) ^ rp) << 4;
    const uint32_t rcv = sb + OFF_STG + wg * 32768 + 16384 + w4 * 2048 + lane * 16;
    auto staged = [&]() {
      asm volatile("fence.proxy.async.shared::cta;" ::: "memory");
      __syncwarp();
      if (elect()) mbar_arrive(bars + 8 * (B_SFULL + wg));
    };
    auto half_tile = [&](const bool first, const int kind) {
      float a2[32];
      if (wg == 1) { if (!first) staged(); bar_sync(NB_SKEW, 256); }
      const uint32_t ph0 = ph;
      uint32_t d4;
#pragma unroll
      for (int kp = 0; kp < 5; kp++) {
        stage_begin();
#pragma unroll
        for (int kk = 0; kk < (kp < 4 ? 8 : 4); kk++) { const int i = (kp * 8 + kk) * 4; wgmma_n64_rs_tb1(a2, xa[i], xa[i + 1], xa[i + 2], xa[i + 3], desc((dlo + kk * 128) + DLO_MN, DHI_SW128), (kp | kk) != 0); }
        if (kp == 2 && wg == 0) bar_arrive(NB_SKEW, 256);
        d4 = dlo;
        stage_end(kp > 0);
        if (kp == 0 && !first && wg == 0) staged();
      }
      if (first) mbar_wait(bars + 8 * B_HSFULL, 0);
      stage_begin();
#pragma unroll
      for (int kk = 0; kk < 8; kk++) wgmma_n64_ss_tb0(a2, desc(dhs + kk * (2 * HS_LBO >> 4), DHI_NONE), desc((dlo + (kk >> 2) * 512 + (kk & 3) * 2) + DLO_K, DHI_SW128), 1);
      wgmma_n64_ss_tb0(a2, desc(d4 + 640 + drem, DHI_NONE), desc((d4 + 512) | ((1024 >> 4) << 16), DHI_NONE), 1);
      wg_commit();
      if (!first) {
        if (kind == 1) mbar_wait(bars + 8 * (B_EMPTY + wg), ph0 ^ 1);
        if (kind == 2) { mbar_wait(bars + 8 * (B_SFREE + wg), 1); mbar_wait(bars + 8 * (B_RFULL + wg), 1); }
      }
      wg_wait<0>();
      release(prev); release(s); advance();
      keep(a2);
      if (!first && kind >= 2) {
#pragma unroll
        for (int i = 0; i < 4; i++) {
          uint32_t v[4];
          lds128(rcv + (kind & 1) * 8192 + i * 512, v[0], v[1], v[2], v[3]);
#pragma unroll
          for (int e = 0; e < 4; e++) { a2[8 * i + 2 * e] += bflo(v[e]); a2[8 * i + 2 * e + 1] += bfhi(v[e]); }
        }
        __syncwarp();
      }
      const uint32_t stg = (!first && kind == 1 ? sb + wg * SLOT : sb + OFF_STG + wg * 32768 + (kind == 3 ? 16384 : 0)) + so;
#pragma unroll
      for (int i = 0; i < 8; i++) {
        const uint32_t a = stg + (i >> 2) * 8192 + (sx ^ ((i & 3) << 5));
        sts64f(a, a2[4 * i], a2[4 * i + 1]);
        sts64f(a + 1024, a2[4 * i + 2], a2[4 * i + 3]);
      }
    };
    if (rank) half_tile(true, 0);
    for (int t = 0; t < 4 - rank; t++) {
      if (wg == 1) { if (t + rank > 0) staged(); bar_sync(NB_SKEW, 256); }
#pragma unroll
      for (int kb = 0; kb < 9; kb++) {
        if ((kb == 5 && t == 0 && rank) || (kb == 1 && t == 1)) nst = NST + 1;
        if (t == 1 && ((kb == 1 && rank) || kb == 7)) nst = NST + 2;
        stage_begin();
#pragma unroll
        for (int kk = 0; kk < 4; kk++) { const int i = (kb * 4 + kk) * 4; wgmma_n128_rs_tb1(acc, xa[i], xa[i + 1], xa[i + 2], xa[i + 3], desc((dlo + kk * 128) + DLO_MN, DHI_SW128), (kb | kk) != 0); }
        if (kb == SKEW - 1 && wg == 0) bar_arrive(NB_SKEW, 256);
        stage_end(kb > 0);
        if (kb == 3 && t + rank > 0 && wg == 0) staged();
      }
      if (t == 0) mbar_wait(bars + 8 * B_HSFULL, 0);
      stage_begin();
#pragma unroll
      for (int kk = 0; kk < 4; kk++) wgmma_n128_ss_tb0(acc, desc(dhs + kk * (2 * HS_LBO >> 4), DHI_NONE), desc((dlo + kk * 2) + DLO_K, DHI_SW128), 1);
      stage_end(true);
      stage_begin();
#pragma unroll
      for (int kk = 0; kk < 4; kk++) wgmma_n128_ss_tb0(acc, desc(dhs + (4 + kk) * (2 * HS_LBO >> 4), DHI_NONE), desc((dlo + kk * 2) + DLO_K, DHI_SW128), 1);
      const int s_im = s;
      advance();
      stage_begin();
      wgmma_n128_ss_tb0(acc, desc(dlo + 256 + drem, DHI_NONE), desc(dlo | ((2048 >> 4) << 16), DHI_NONE), 1);
      stage_end(true);
      if (t + rank > 0) mbar_wait(bars + 8 * (B_SFREE + wg), (t + rank - 1) & 1);
      if (t & 1) mbar_wait(bars + 8 * (B_RFULL + wg), t >> 1);
      wg_wait<0>();
      release(s_im); release(prev);
      keep(acc);
      if (t & 1) {
        const uint32_t stg = sb + OFF_STG + wg * 32768 + so;
#pragma unroll
        for (int hh = 0; hh < 2; hh++) {
#pragma unroll
          for (int i = 4 * hh; i < 4 * hh + 4; i++) {
            uint32_t v[4];
            lds128(rcv + hh * 8192 + (i & 3) * 512, v[0], v[1], v[2], v[3]);
#pragma unroll
            for (int e = 0; e < 4; e++) { acc[8 * i + 2 * e] += bflo(v[e]); acc[8 * i + 2 * e + 1] += bfhi(v[e]); }
          }
          __syncwarp();
#pragma unroll
          for (int i = 8 * hh; i < 8 * hh + 8; i++) {
            const uint32_t a = stg + (i >> 2) * 8192 + (sx ^ ((i & 3) << 5));
            sts64f(a, acc[4 * i], acc[4 * i + 1]);
            sts64f(a + 1024, acc[4 * i + 2], acc[4 * i + 3]);
          }
        }
      } else {
#pragma unroll
        for (int i = 0; i < 8; i++)
          sts128(rcv - 16384 + (i >> 2) * 8192 + (i & 3) * 512, pack_bf16(acc[8 * i], acc[8 * i + 1]), pack_bf16(acc[8 * i + 2], acc[8 * i + 3]),
                 pack_bf16(acc[8 * i + 4], acc[8 * i + 5]), pack_bf16(acc[8 * i + 6], acc[8 * i + 7]));
      }
    }
#pragma unroll 1
    for (int kind = 1 + rank; kind < 2 + 2 * rank; kind++) half_tile(false, kind);
    staged();
  }
}

typedef CUresult (*EncodeFn)(CUtensorMap*, CUtensorMapDataType, cuuint32_t, void*, const cuuint64_t*, const cuuint64_t*, const cuuint32_t*,
                             const cuuint32_t*, CUtensorMapInterleave, CUtensorMapSwizzle, CUtensorMapL2promotion, CUtensorMapFloatOOBfill);

void map2d(EncodeFn enc, CUtensorMap* tm, const void* p, uint64_t cols, uint64_t rows, uint32_t bc, uint32_t br, CUtensorMapSwizzle sw) {
  cuuint64_t gd[2] = {cols, rows}, gs[1] = {cols * 2};
  cuuint32_t bd[2] = {bc, br}, es[2] = {1, 1};
  enc(tm, CU_TENSOR_MAP_DATA_TYPE_BFLOAT16, 2, (void*)p, gd, gs, bd, es, CU_TENSOR_MAP_INTERLEAVE_NONE, sw,
      sw == CU_TENSOR_MAP_SWIZZLE_128B ? CU_TENSOR_MAP_L2_PROMOTION_L2_128B : CU_TENSOR_MAP_L2_PROMOTION_NONE, CU_TENSOR_MAP_FLOAT_OOB_FILL_NONE);
}

}

extern "C" void kernel_launch(void* const* d_in, const int* in_sizes, int n_in, void* d_out, int out_size) {
  (void)in_sizes; (void)n_in; (void)out_size;
  static EncodeFn enc = nullptr;
  if (!enc) {
    cudaDriverEntryPointQueryResult qr;
    cudaGetDriverEntryPoint("cuTensorMapEncodeTiled", (void**)&enc, cudaEnableDefault, &qr);
    cudaFuncSetAttribute(fused_kernel, cudaFuncAttributeMaxDynamicSharedMemorySize, SMEM_BYTES);
  }
  Params prm;
  const CUtensorMapSwizzle S128 = CU_TENSOR_MAP_SWIZZLE_128B;
  map2d(enc, &prm.tx, d_in[0], kD, kS, 64, 64, S128);
  map2d(enc, &prm.tBre, d_in[3], kD, 576, 64, 72, S128);
  map2d(enc, &prm.tBim, d_in[4], kD, 576, 64, 72, S128);
  map2d(enc, &prm.tCre, d_in[5], 576, kD, 64, 64, S128);
  map2d(enc, &prm.tCim, d_in[6], 576, kD, 64, 64, S128);
  map2d(enc, &prm.tCre8, d_in[5], 576, kD, 8, 64, CU_TENSOR_MAP_SWIZZLE_NONE);
  map2d(enc, &prm.tCim8, d_in[6], 576, kD, 8, 64, CU_TENSOR_MAP_SWIZZLE_NONE);
  map2d(enc, &prm.tWg, d_in[10], kF, kD, 64, 64, S128);
  map2d(enc, &prm.tWu, d_in[11], kF, kD, 64, 64, S128);
  map2d(enc, &prm.tWd, d_in[12], kD, kF, 64, 64, S128);
  {
    cuuint64_t gd[4] = {kD, 2, 4, kS / 8}, gs[3] = {4 * kD * 4, kD * 4, 8 * kD * 4};
    cuuint32_t bd[4] = {32, 2, 4, 8}, es[4] = {1, 1, 1, 1};
    enc(&prm.tOut, CU_TENSOR_MAP_DATA_TYPE_FLOAT32, 4, d_out, gd, gs, bd, es, CU_TENSOR_MAP_INTERLEAVE_NONE, S128, CU_TENSOR_MAP_L2_PROMOTION_NONE,
        CU_TENSOR_MAP_FLOAT_OOB_FILL_NONE);
  }
  prm.lre = (const __nv_bfloat16*)d_in[1];
  prm.lim = (const __nv_bfloat16*)d_in[2];
  prm.bre = (const __nv_bfloat16*)d_in[3];
  prm.bim = (const __nv_bfloat16*)d_in[4];
  prm.cre = (const __nv_bfloat16*)d_in[5];
  prm.cim = (const __nv_bfloat16*)d_in[6];
  prm.wg = (const __nv_bfloat16*)d_in[10];
  prm.wu = (const __nv_bfloat16*)d_in[11];
  prm.wd = (const __nv_bfloat16*)d_in[12];
  prm.ldt = (const __nv_bfloat16*)d_in[7];
  prm.dskip = (const __nv_bfloat16*)d_in[8];
  prm.out = (float*)d_out;

  fused_kernel<<<128, 384, SMEM_BYTES, cudaStreamPerThread>>>(prm);
}
```

```cpp
#include <cuda_runtime.h>
#include <cuda.h>
#include <cuda_bf16.h>
#include <stdint.h>

namespace {

constexpr int kS = 2048, kD = 576, kF = 4608;
constexpr int SKEW = 4;
constexpr int PFD = 18;
constexpr int NST = 6;
constexpr uint32_t SLOT = 16384;
constexpr uint32_t OFF_H = NST * SLOT;
constexpr uint32_t HS_LBO = 1040;
constexpr uint32_t HS_BYTES = 18 * HS_LBO;
constexpr uint32_t OFF_DUMP = OFF_H + 65536 - HS_BYTES;
constexpr uint32_t OFF_STG = OFF_H + 2 * SLOT;
constexpr uint32_t OFF_HS = OFF_STG + 65536;
constexpr uint32_t HS_MAIN = 16 * HS_LBO, HS_REM = 2 * HS_LBO;
constexpr uint32_t OFF_CONST = OFF_H + 131072;
constexpr uint32_t OFF_BAR = OFF_CONST + 4 * 576;
constexpr uint32_t SMEM_BYTES = OFF_BAR + 384 + 384;
static_assert(SMEM_BYTES <= 232448 && OFF_HS + 2 * HS_MAIN <= OFF_BAR, "smem");

enum { B_FULL = 0, B_EMPTY = NST + 2, B_X = 2 * NST + 4, B_X8 = B_X + 8, B_BU  , B_RING = B_BU + 4  , B_SCAN = B_RING + 2  , B_PARK = B_SCAN + 2, B_HFREE, B_HSFULL, B_SFULL,
       B_SFREE = B_SFULL + 2, B_RFULL = B_SFREE + 2, B_RFREE = B_RFULL + 2, B_COUNT = B_RFREE + 2 };
static_assert(B_COUNT * 8 <= 384, "barriers");
enum { NB_SKEW = 1, NB_XDONE = 2  , NB_SCAN = 4, NB_DUMP = 5, NB_HFREE = 6, NB_STATS = 7 };
constexpr uint32_t HBLK0 = 0x07652CB4u, HBLK1 = 0x189A3DEFu;
constexpr uint32_t OFF_BU0 = SLOT, OFF_BU1 = OFF_H, OFF_BU2 = OFF_H + 65536 + 19456;
static_assert(OFF_BU1 + 5 * 9216 <= OFF_DUMP && OFF_BU2 >= OFF_DUMP + 2 * HS_BYTES && OFF_BU2 + 5 * 9216 <= OFF_CONST, "Bu tiles");

struct __align__(64) Params {
  CUtensorMap tx, tBre, tBim, tWg, tWu, tWd, tCre, tCim, tCre8, tCim8, tOut;
  const __nv_bfloat16 *lre, *lim, *bre, *bim, *cre, *cim, *ldt, *dskip, *wg, *wu, *wd;
  float* out;
};

__device__ unsigned g_epoch[128];
__device__ unsigned g_ready[16];
__device__ __align__(256) uint2 g_S[2][16][8][96];
__device__ __align__(128) uint8_t g_hs[128][2 * HS_BYTES];

__device__ __forceinline__ void wgmma_n72_rs_tb0(float (&d)[36], uint32_t a0, uint32_t a1, uint32_t a2, uint32_t a3, uint64_t db, int scale_d) {
  asm volatile("{\n.reg .pred p;\nsetp.ne.b32 p, %41, 0;\n"
    "wgmma.mma_async.sync.aligned.m64n72k16.f32.bf16.bf16 {"
    "%0, %1, %2, %3, %4, %5, %6, %7, %8, %9, %10, %11, %12, %13, %14, %15, "
    "%16, %17, %18, %19, %20, %21, %22, %23, %24, %25, %26, %27, %28, %29, %30, %31, "
    "%32, %33, %34, %35"
    "}, {%36, %37, %38, %39}, %40, p, 1, 1, 0;\n}\n"
    : "+f"(d[0]), "+f"(d[1]), "+f"(d[2]), "+f"(d[3]), "+f"(d[4]), "+f"(d[5]), "+f"(d[6]), "+f"(d[7]),
      "+f"(d[8]), "+f"(d[9]), "+f"(d[10]), "+f"(d[11]), "+f"(d[12]), "+f"(d[13]), "+f"(d[14]), "+f"(d[15]),
      "+f"(d[16]), "+f"(d[17]), "+f"(d[18]), "+f"(d[19]), "+f"(d[20]), "+f"(d[21]), "+f"(d[22]), "+f"(d[23]),
      "+f"(d[24]), "+f"(d[25]), "+f"(d[26]), "+f"(d[27]), "+f"(d[28]), "+f"(d[29]), "+f"(d[30]), "+f"(d[31]),
      "+f"(d[32]), "+f"(d[33]), "+f"(d[34]), "+f"(d[35])
    : "r"(a0), "r"(a1), "r"(a2), "r"(a3), "l"(db), "r"(scale_d));
}
__device__ __forceinline__ void wgmma_n128_rs_tb1(float (&d)[64], uint32_t a0, uint32_t a1, uint32_t a2, uint32_t a3, uint64_t db, int scale_d) {
  asm volatile("{\n.reg .pred p;\nsetp.ne.b32 p, %69, 0;\n"
    "wgmma.mma_async.sync.aligned.m64n128k16.f32.bf16.bf16 {"
    "%0, %1, %2, %3, %4, %5, %6, %7, %8, %9, %10, %11, %12, %13, %14, %15, "
    "%16, %17, %18, %19, %20, %21, %22, %23, %24, %25, %26, %27, %28, %29, %30, %31, "
    "%32, %33, %34, %35, %36, %37, %38, %39, %40, %41, %42, %43, %44, %45, %46, %47, "
    "%48, %49, %50, %51, %52, %53, %54, %55, %56, %57, %58, %59, %60, %61, %62, %63"
    "}, {%64, %65, %66, %67}, %68, p, 1, 1, 1;\n}\n"
    : "+f"(d[0]), "+f"(d[1]), "+f"(d[2]), "+f"(d[3]), "+f"(d[4]), "+f"(d[5]), "+f"(d[6]), "+f"(d[7]),
      "+f"(d[8]), "+f"(d[9]), "+f"(d[10]), "+f"(d[11]), "+f"(d[12]), "+f"(d[13]), "+f"(d[14]), "+f"(d[15]),
      "+f"(d[16]), "+f"(d[17]), "+f"(d[18]), "+f"(d[19]), "+f"(d[20]), "+f"(d[21]), "+f"(d[22]), "+f"(d[23]),
      "+f"(d[24]), "+f"(d[25]), "+f"(d[26]), "+f"(d[27]), "+f"(d[28]), "+f"(d[29]), "+f"(d[30]), "+f"(d[31]),
      "+f"(d[32]), "+f"(d[33]), "+f"(d[34]), "+f"(d[35]), "+f"(d[36]), "+f"(d[37]), "+f"(d[38]), "+f"(d[39]),
      "+f"(d[40]), "+f"(d[41]), "+f"(d[42]), "+f"(d[43]), "+f"(d[44]), "+f"(d[45]), "+f"(d[46]), "+f"(d[47]),
      "+f"(d[48]), "+f"(d[49]), "+f"(d[50]), "+f"(d[51]), "+f"(d[52]), "+f"(d[53]), "+f"(d[54]), "+f"(d[55]),
      "+f"(d[56]), "+f"(d[57]), "+f"(d[58]), "+f"(d[59]), "+f"(d[60]), "+f"(d[61]), "+f"(d[62]), "+f"(d[63])
    : "r"(a0), "r"(a1), "r"(a2), "r"(a3), "l"(db), "r"(scale_d));
}
__device__ __forceinline__ void wgmma_n128_ss_tb0(float (&d)[64], uint64_t da, uint64_t db, int scale_d) {
  asm volatile("{\n.reg .pred p;\nsetp.ne.b32 p, %66, 0;\n"
    "wgmma.mma_async.sync.aligned.m64n128k16.f32.bf16.bf16 {"
    "%0, %1, %2, %3, %4, %5, %6, %7, %8, %9, %10, %11, %12, %13, %14, %15, "
    "%16, %17, %18, %19, %20, %21, %22, %23, %24, %25, %26, %27, %28, %29, %30, %31, "
    "%32, %33, %34, %35, %36, %37, %38, %39, %40, %41, %42, %43, %44, %45, %46, %47, "
    "%48, %49, %50, %51, %52, %53, %54, %55, %56, %57, %58, %59, %60, %61, %62, %63"
    "}, %64, %65, p, 1, 1, 0, 0;\n}\n"
    : "+f"(d[0]), "+f"(d[1]), "+f"(d[2]), "+f"(d[3]), "+f"(d[4]), "+f"(d[5]), "+f"(d[6]), "+f"(d[7]),
      "+f"(d[8]), "+f"(d[9]), "+f"(d[10]), "+f"(d[11]), "+f"(d[12]), "+f"(d[13]), "+f"(d[14]), "+f"(d[15]),
      "+f"(d[16]), "+f"(d[17]), "+f"(d[18]), "+f"(d[19]), "+f"(d[20]), "+f"(d[21]), "+f"(d[22]), "+f"(d[23]),
      "+f"(d[24]), "+f"(d[25]), "+f"(d[26]), "+f"(d[27]), "+f"(d[28]), "+f"(d[29]), "+f"(d[30]), "+f"(d[31]),
      "+f"(d[32]), "+f"(d[33]), "+f"(d[34]), "+f"(d[35]), "+f"(d[36]), "+f"(d[37]), "+f"(d[38]), "+f"(d[39]),
      "+f"(d[40]), "+f"(d[41]), "+f"(d[42]), "+f"(d[43]), "+f"(d[44]), "+f"(d[45]), "+f"(d[46]), "+f"(d[47]),
      "+f"(d[48]), "+f"(d[49]), "+f"(d[50]), "+f"(d[51]), "+f"(d[52]), "+f"(d[53]), "+f"(d[54]), "+f"(d[55]),
      "+f"(d[56]), "+f"(d[57]), "+f"(d[58]), "+f"(d[59]), "+f"(d[60]), "+f"(d[61]), "+f"(d[62]), "+f"(d[63])
    : "l"(da), "l"(db), "r"(scale_d));
}
__device__ __forceinline__ void wgmma_n64_rs_tb1(float (&d)[32], uint32_t a0, uint32_t a1, uint32_t a2, uint32_t a3, uint64_t db, int scale_d) {
  asm volatile("{\n.reg .pred p;\nsetp.ne.b32 p, %37, 0;\n"
    "wgmma.mma_async.sync.aligned.m64n64k16.f32.bf16.bf16 {"
    "%0, %1, %2, %3, %4, %5, %6, %7, %8, %9, %10, %11, %12, %13, %14, %15, "
    "%16, %17, %18, %19, %20, %21, %22, %23, %24, %25, %26, %27, %28, %29, %30, %31"
    "}, {%32, %33, %34, %35}, %36, p, 1, 1, 1;\n}\n"
    : "+f"(d[0]), "+f"(d[1]), "+f"(d[2]), "+f"(d[3]), "+f"(d[4]), "+f"(d[5]), "+f"(d[6]), "+f"(d[7]),
      "+f"(d[8]), "+f"(d[9]), "+f"(d[10]), "+f"(d[11]), "+f"(d[12]), "+f"(d[13]), "+f"(d[14]), "+f"(d[15]),
      "+f"(d[16]), "+f"(d[17]), "+f"(d[18]), "+f"(d[19]), "+f"(d[20]), "+f"(d[21]), "+f"(d[22]), "+f"(d[23]),
      "+f"(d[24]), "+f"(d[25]), "+f"(d[26]), "+f"(d[27]), "+f"(d[28]), "+f"(d[29]), "+f"(d[30]), "+f"(d[31])
    : "r"(a0), "r"(a1), "r"(a2), "r"(a3), "l"(db), "r"(scale_d));
}
__device__ __forceinline__ void wgmma_n64_ss_tb0(float (&d)[32], uint64_t da, uint64_t db, int scale_d) {
  asm volatile("{\n.reg .pred p;\nsetp.ne.b32 p, %34, 0;\n"
    "wgmma.mma_async.sync.aligned.m64n64k16.f32.bf16.bf16 {"
    "%0, %1, %2, %3, %4, %5, %6, %7, %8, %9, %10, %11, %12, %13, %14, %15, "
    "%16, %17, %18, %19, %20, %21, %22, %23, %24, %25, %26, %27, %28, %29, %30, %31"
    "}, %32, %33, p, 1, 1, 0, 0;\n}\n"
    : "+f"(d[0]), "+f"(d[1]), "+f"(d[2]), "+f"(d[3]), "+f"(d[4]), "+f"(d[5]), "+f"(d[6]), "+f"(d[7]),
      "+f"(d[8]), "+f"(d[9]), "+f"(d[10]), "+f"(d[11]), "+f"(d[12]), "+f"(d[13]), "+f"(d[14]), "+f"(d[15]),
      "+f"(d[16]), "+f"(d[17]), "+f"(d[18]), "+f"(d[19]), "+f"(d[20]), "+f"(d[21]), "+f"(d[22]), "+f"(d[23]),
      "+f"(d[24]), "+f"(d[25]), "+f"(d[26]), "+f"(d[27]), "+f"(d[28]), "+f"(d[29]), "+f"(d[30]), "+f"(d[31])
    : "l"(da), "l"(db), "r"(scale_d));
}

__device__ __forceinline__ bool elect() {
  uint32_t p;
  asm volatile("{.reg .pred q; elect.sync _|q, 0xffffffff; selp.u32 %0,1,0,q;}" : "=r"(p));
  return p;
}
__device__ __forceinline__ void mbar_init(uint32_t bar, uint32_t cnt) { asm volatile("mbarrier.init.shared::cta.b64 [%0], %1;" ::"r"(bar), "r"(cnt) : "memory"); }
__device__ __forceinline__ void mbar_expect(uint32_t bar, uint32_t bytes) { asm volatile("mbarrier.arrive.expect_tx.shared::cta.b64 _, [%0], %1;" ::"r"(bar), "r"(bytes) : "memory"); }
__device__ __forceinline__ void mbar_arrive(uint32_t bar) { asm volatile("mbarrier.arrive.shared::cta.b64 _, [%0];" ::"r"(bar) : "memory"); }
__device__ __forceinline__ void mbar_arrive_cta(uint32_t bar, uint32_t cta) {
  asm volatile("{.reg .b32 ra; mapa.shared::cluster.u32 ra, %0, %1; mbarrier.arrive.shared::cluster.b64 _, [ra];}" ::"r"(bar), "r"(cta) : "memory");
}
__device__ __forceinline__ void mbar_wait(uint32_t bar, uint32_t parity) {
  asm volatile(
      "{\n.reg .pred p;\n.reg .u32 c, t;\n"
      "mbarrier.try_wait.parity.shared::cta.b64 p, [%0], %1;\n@p bra DONE;\n"
      "mov.u32 c, %%clock;\n"
      "LAB_WAIT:\nmbarrier.try_wait.parity.shared::cta.b64 p, [%0], %1;\n@p bra DONE;\n"
      "mov.u32 t, %%clock;\nsub.u32 t, t, c;\nsetp.lt.u32 p, t, 0x40000000;\n@p bra LAB_WAIT;\ntrap;\nDONE:\n}" ::"r"(bar), "r"(parity) : "memory");
}
__device__ __forceinline__ void bar_sync(int id, int n) { asm volatile("bar.sync %0, %1;" ::"r"(id), "r"(n) : "memory"); }
__device__ __forceinline__ void bar_arrive(int id, int n) { asm volatile("bar.arrive %0, %1;" ::"r"(id), "r"(n) : "memory"); }
__device__ __forceinline__ void wg_fence() { asm volatile("wgmma.fence.sync.aligned;" ::: "memory"); }
__device__ __forceinline__ void wg_commit() { asm volatile("wgmma.commit_group.sync.aligned;" ::: "memory"); }
template <int N> __device__ __forceinline__ void wg_wait() { asm volatile("wgmma.wait_group.sync.aligned %0;" ::"n"(N) : "memory"); }
__device__ __forceinline__ void tma2d(uint32_t dst, const CUtensorMap* tm, uint32_t bar, int c0, int c1) {
  asm volatile("cp.async.bulk.tensor.2d.shared::cluster.global.mbarrier::complete_tx::bytes [%0], [%1,{%3,%4}], [%2];" ::"r"(dst), "l"(tm), "r"(bar), "r"(c0), "r"(c1) : "memory");
}
__device__ __forceinline__ void tma2d_mc(uint32_t dst, const CUtensorMap* tm, uint32_t bar, int c0, int c1) {
  asm volatile("cp.async.bulk.tensor.2d.shared::cluster.global.mbarrier::complete_tx::bytes.multicast::cluster [%0], [%1,{%3,%4}], [%2], %5;" ::"r"(dst), "l"(tm), "r"(bar), "r"(c0), "r"(c1), "h"((uint16_t)3) : "memory");
}
__device__ __forceinline__ void l2_prefetch_line(const void* p) { asm volatile("prefetch.global.L2 [%0];" ::"l"(p)); }
__device__ __forceinline__ uint64_t desc(uint32_t lo, uint32_t hi) { return ((uint64_t)hi << 32) | lo; }
constexpr uint32_t DHI_SW128 = (1024 >> 4) | (1u << 30);
constexpr uint32_t DHI_NONE = (128 >> 4);
constexpr uint32_t DLO_HS = (HS_LBO >> 4) << 16;
constexpr uint32_t DLO_MN = (8192 >> 4) << 16;
constexpr uint32_t DLO_K = 1u << 16;
__device__ __forceinline__ float tanh_fast(float x) { float y; asm("tanh.approx.f32 %0, %1;" : "=f"(y) : "f"(x)); return y; }
__device__ __forceinline__ uint32_t pack_bf16(float lo, float hi) { uint32_t r; asm("cvt.rn.bf16x2.f32 %0, %1, %2;" : "=r"(r) : "f"(hi), "f"(lo)); return r; }
__device__ __forceinline__ float rbf(float x) { return __uint_as_float(pack_bf16(0.f, x)); }
__device__ __forceinline__ void mma16816(float (&c)[4], uint32_t a0, uint32_t a1, uint32_t a2, uint32_t a3, uint32_t b0, uint32_t b1) {
  asm volatile("mma.sync.aligned.m16n8k16.row.col.f32.bf16.bf16.f32 {%0,%1,%2,%3}, {%4,%5,%6,%7}, {%8,%9}, {%0,%1,%2,%3};"
               : "+f"(c[0]), "+f"(c[1]), "+f"(c[2]), "+f"(c[3]) : "r"(a0), "r"(a1), "r"(a2), "r"(a3), "r"(b0), "r"(b1));
}
__device__ __forceinline__ void sts128(uint32_t a, uint32_t x, uint32_t y, uint32_t z, uint32_t w) {
  asm volatile("st.shared.v4.b32 [%0], {%1,%2,%3,%4};" ::"r"(a), "r"(x), "r"(y), "r"(z), "r"(w) : "memory");
}
__device__ __forceinline__ void sts64f(uint32_t a, float x, float y) { asm volatile("st.shared.v2.f32 [%0], {%1,%2};" ::"r"(a), "f"(x), "f"(y) : "memory"); }
__device__ __forceinline__ float2 lds64f(uint32_t a) { float2 v; asm volatile("ld.shared.v2.f32 {%0,%1}, [%2];" : "=f"(v.x), "=f"(v.y) : "r"(a) : "memory"); return v; }
__device__ __forceinline__ uint32_t lds32(uint32_t a) { uint32_t v; asm volatile("ld.shared.b32 %0, [%1];" : "=r"(v) : "r"(a) : "memory"); return v; }
__device__ __forceinline__ void lds128(uint32_t a, uint32_t& x, uint32_t& y, uint32_t& z, uint32_t& w) {
  asm volatile("ld.shared.v4.b32 {%0,%1,%2,%3}, [%4];" : "=r"(x), "=r"(y), "=r"(z), "=r"(w) : "r"(a) : "memory");
}
__device__ __forceinline__ void lds128_inplace(uint32_t a, uint32_t& x, uint32_t& y, uint32_t& z, uint32_t& w) {
  asm volatile("{.reg .pred p; .reg .u32 n; mov.u32 n, %%ntid.y; setp.ne.u32 p, n, 0; @p ld.shared.v4.b32 {%0,%1,%2,%3}, [%4];}" : "+r"(x), "+r"(y), "+r"(z), "+r"(w) : "r"(a) : "memory");
}
__device__ __forceinline__ float bflo(uint32_t v) { return __uint_as_float(v << 16); }
__device__ __forceinline__ float bfhi(uint32_t v) { return __uint_as_float(v & 0xffff0000u); }
template <int N> __device__ __forceinline__ void keep(float (&a)[N]) {
#pragma unroll
  for (int i = 0; i < N; i++) asm volatile("" : "+f"(a[i])::"memory");
}

__global__ void __cluster_dims__(2, 1, 1) __launch_bounds__(384, 1) fused_kernel(const __grid_constant__ Params prm) {
  extern __shared__ __align__(1024) uint8_t smem[];
  const int warp = __shfl_sync(0xffffffffu, threadIdx.x >> 5, 0);
  const uint32_t sb0 = (uint32_t)__cvta_generic_to_shared(smem);
  const int j = blockIdx.x & 7, m = blockIdx.x >> 3, rank = j & 1;
  auto smem_base = [&]() { return __shfl_sync(0xffffffffu, sb0 + (threadIdx.x & 31), 0); };

  if (threadIdx.x == 320) asm volatile("prefetch.tensormap [%0];" ::"l"(&prm.tx) : "memory");
  if (warp == 0) {
    if (elect()) {
#pragma unroll
      for (int i = B_X8; i >= B_X; i--) mbar_init(sb0 + OFF_BAR + 8 * i, 1);
      asm volatile("fence.mbarrier_init.release.cluster;" ::: "memory");
    }
    __syncwarp();
  }
  asm volatile("barrier.cluster.arrive.relaxed.aligned;" ::: "memory");
  if (warp == 0) {
    const uint32_t xb = sb0 + OFF_BAR;
    if (elect()) {
      mbar_expect(xb + 8 * B_X8, 16384);
      tma2d(sb0, &prm.tx, xb + 8 * B_X8, 512, m * 128);
      tma2d(sb0 + 8192, &prm.tx, xb + 8 * B_X8, 512, m * 128 + 64);
#pragma unroll
      for (int i = 0; i < 4; i++) {
        mbar_expect(xb + 8 * (B_X + i), 16384);
        tma2d(sb0 + OFF_H + i * 16384, &prm.tx, xb + 8 * (B_X + i), i * 128, m * 128);
        tma2d(sb0 + OFF_H + i * 16384 + 8192, &prm.tx, xb + 8 * (B_X + i), i * 128 + 64, m * 128);
      }
    }
    __syncwarp();
  }
  asm volatile("barrier.cluster.wait.aligned;" ::: "memory");
  if (warp == 8 || warp == 9) {
    if (elect()) {
      if (warp == 8) {
#pragma unroll
        for (int i = 0; i < B_X; i++) mbar_init(sb0 + OFF_BAR + 8 * i, i >= B_EMPTY ? 2 : 1);
      } else {
#pragma unroll
        for (int i = B_X8 + 1; i < B_COUNT; i++) mbar_init(sb0 + OFF_BAR + 8 * i, (i >= B_SFULL && i < B_SFULL + 2) ? 4 : (i == B_RING || i == B_RING + 1) ? 2 : 1);
        if (sb0 & 1023) __trap();
      }
      asm volatile("fence.mbarrier_init.release.cluster;" ::: "memory");
    }
    __syncwarp();
  }
  if (warp == 0) {
    const uint32_t xb = sb0 + OFF_BAR;
    const bool e = elect();
#pragma unroll
    for (int i = 0; i < 4; i++) {
      const int kb = i * 2 + rank;
      if (e) { mbar_expect(xb + 8 * (B_X + 4 + i), 16384); tma2d_mc(sb0 + OFF_H + 65536 + kb * 8192, &prm.tx, xb + 8 * (B_X + 4 + i), kb * 64, m * 128 + 64); }
    }
    __syncwarp();
  }
  asm volatile("barrier.cluster.arrive.relaxed.aligned;\nbarrier.cluster.wait.aligned;" ::: "memory");

  if (warp >= 8) {
    asm volatile("setmaxnreg.dec.sync.aligned.u32 24;");
    if (warp == 8) {
      const uint32_t sb = smem_base(), bars = sb + OFF_BAR;
      bool e;
      int s = 0, nst = NST + 2; uint32_t ph = 1;
      uint32_t dst, fb;
      auto acquire = [&](uint32_t bytes) {
        mbar_wait(bars + 8 * (B_EMPTY + s), ph);
        fb = bars + 8 * (B_FULL + s); dst = sb + s * SLOT;
        e = elect();
        if (e) mbar_expect(fb, bytes);
        if (++s == nst) { s = 0; ph ^= 1; }
      };
      auto box = [&](const CUtensorMap* t, uint32_t o, int a, int b) { if (e) tma2d(dst + o, t, fb, a, b); };
      auto hs_rem = [&](uint32_t o) {
        if (e) asm volatile("cp.async.bulk.shared::cluster.global.mbarrier::complete_tx::bytes [%0], [%1], %2, [%3];" ::"r"(dst + o),
                            "l"(&g_hs[blockIdx.x][2 * HS_MAIN]), "r"(2 * HS_REM), "r"(fb) : "memory");
      };
      const int lane = threadIdx.x & 31;
      const char* pf = lane < 8 ? (const char*)(lane & 4 ? prm.wu : prm.wg) + ((size_t)(m * 4 + (lane & 3)) * kF + j * 576) * 2
                     : lane < 12 ? (const char*)prm.wd + (size_t)j * 576 * 1152 + (m * 324 + (lane & 3)) * 128
                                 : (const char*)(lane & 1 ? prm.cim : prm.cre) + (size_t)blockIdx.x * 5184;
      int pk = 0, pleft = 81;
      auto prefetch = [&]() {
        if (pleft > 0) {
          if (lane < 14) l2_prefetch_line(pf);
          pf += lane < 8 ? (pk == 8 ? 128 - 8 * 64 * kF * 2 : 64 * kF * 2) : lane < 12 ? 512 : 64;
          pk = pk == 8 ? 0 : pk + 1;
          pleft--;
        }
      };
      mbar_wait(bars + 8 * B_X8, 0);
      e = elect();
#pragma unroll 1
      for (int kb = 0; kb < 8; kb++) {
        fb = bars + 8 * (B_BU + (kb >> 2));
        if (e) { if ((kb & 3) == 0) mbar_expect(fb, 4 * 9216); tma2d(sb + OFF_BU0 + kb * 9216, &prm.tBre, fb, kb * 64, j * 72); }
      }
      bar_sync(NB_XDONE, 160);
      fb = bars + 8 * (B_BU + 2);
      if (e) { mbar_expect(fb, 5 * 9216); tma2d(sb + OFF_BU1, &prm.tBre, fb, 512, j * 72); }
#pragma unroll 1
      for (int kb = 0; kb < 4; kb++) if (e) tma2d(sb + OFF_BU1 + (kb + 1) * 9216, &prm.tBim, fb, kb * 64, j * 72);
      for (int i = 0; i < PFD / 2; i++) prefetch();
      bar_sync(NB_XDONE + 1, 160);
      fb = bars + 8 * (B_BU + 3);
      if (e) mbar_expect(fb, 5 * 9216);
#pragma unroll 1
      for (int kb = 4; kb < 9; kb++) if (e) tma2d(sb + OFF_BU2 + (kb - 4) * 9216, &prm.tBim, fb, kb * 64, j * 72);
      for (int i = PFD / 2; i < PFD; i++) prefetch();
      mbar_wait(bars + 8 * B_RING, 0);
      for (int c = 0; c < 9; c++) {
        const int col = j * 576 + c * 64;
#pragma unroll 1
        for (int kb = 0; kb < 9; kb++) {
          if (kb == 6 && c == 0) mbar_wait(bars + 8 * (B_RING + 1), 0);
          if (kb == 6 && c == 3) nst = 7;
          if (kb == 5 && c == 7) nst = 6;
          acquire(16384); box(&prm.tWg, 0, col, kb * 64); box(&prm.tWu, 8192, col, kb * 64); prefetch();
        }
      }
      auto half_tile = [&](int n0) {
#pragma unroll 1
        for (int kp = 0; kp < 4; kp++) { acquire(16384); box(&prm.tWd, 0, n0, j * 576 + kp * 128); box(&prm.tWd, 8192, n0, j * 576 + kp * 128 + 64); }
        acquire(8192 + 2048 + 2 * HS_REM); box(&prm.tWd, 0, n0, j * 576 + 512); box(&prm.tCre8, 8192, j * 72 + 64, n0); box(&prm.tCim8, 9216, j * 72 + 64, n0); hs_rem(10240);
        acquire(16384); box(&prm.tCre, 0, j * 72, n0); box(&prm.tCim, 8192, j * 72, n0);
      };
      mbar_wait(bars + 8 * B_PARK, 0);
      asm volatile("fence.proxy.async.global;" ::: "memory");
      if (rank) half_tile(512);
#pragma unroll 1
      for (int t = 0; t < 4 - rank; t++) {
        const int n0 = ((rank ^ t ^ 1) & 1) * 256 + (((t >> 1) ^ (j >> 1)) & 1) * 128;
#pragma unroll 1
        for (int kb = 0; kb < 9; kb++) {
          if (rank ? (t == 0 && kb == 5) : (t == 1 && kb == 1)) nst = NST + 1;
          if (t == 1 && kb == (rank ? 1 : 7)) nst = NST + 2;
          if (kb == 3 && t == 0 && rank) mbar_wait(bars + 8 * B_HFREE, 0);
          acquire(16384); box(&prm.tWd, 0, n0, j * 576 + kb * 64); box(&prm.tWd, 8192, n0 + 64, j * 576 + kb * 64);
        }
        if (t == 0) mbar_wait(bars + 8 * B_HFREE, 0);
        acquire(16384); box(&prm.tCre, 0, j * 72, n0); box(&prm.tCre, 8192, j * 72, n0 + 64);
        acquire(16384); box(&prm.tCim, 0, j * 72, n0); box(&prm.tCim, 8192, j * 72, n0 + 64);
        acquire(4096 + 2 * HS_REM); hs_rem(4096);
        box(&prm.tCre8, 0, j * 72 + 64, n0); box(&prm.tCre8, 1024, j * 72 + 64, n0 + 64);
        box(&prm.tCim8, 2048, j * 72 + 64, n0); box(&prm.tCim8, 3072, j * 72 + 64, n0 + 64);
      }
      if (!rank) half_tile(512);
      else {
#pragma unroll 1
        for (int hh = 0; hh < 2; hh++) half_tile(256 + (((j >> 1) ^ 1) & 1) * 128 + hh * 64);
      }
    } else {
      const uint32_t sb = smem_base(), bars = sb + OFF_BAR;
      const int p = min((int)threadIdx.x - 288, 71);
      if (threadIdx.x < 288 + 10) asm volatile("prefetch.tensormap [%0];" ::"l"(&prm.tBre + (threadIdx.x - 288)) : "memory");
      if (warp == 10) {
        const int l = threadIdx.x & 31;
        const char* q = (const char*)(l & 1 ? prm.bim : prm.bre) + (size_t)blockIdx.x * 5184;
        mbar_wait(bars + 8 * B_X8, 0);
#pragma unroll
        for (int i = 0; i < 3; i++) if (i * 16 + (l >> 1) < 42) l2_prefetch_line(q + min((i * 16 + (l >> 1)) * 128, 5183));
      }
      const unsigned epoch = *(volatile unsigned*)&g_epoch[blockIdx.x];
      {
        const int pg = j * 72 + p;
        const float lr = __bfloat162float(prm.lre[pg]), li = __bfloat162float(prm.lim[pg]);
        const float dt = rbf(expf(__bfloat162float(prm.ldt[pg])));
        const float ea = expf(dt * lr);
        float sn, cs;
        sincosf(dt * li, &sn, &cs);
        const float ar = ea * cs, ai = ea * sn;
        float br = ar, bi = ai;
#pragma unroll
        for (int k = 0; k < 6; k++) { const float t = br * br - bi * bi; bi = 2.f * br * bi; br = t; }
        const float nr = ar - 1.f, den = 4.f / (lr * lr + li * li);
        sts64f(sb + OFF_CONST + p * 8, ar, ai);
        sts64f(sb + OFF_CONST + 576 + p * 8, br, bi);
        sts64f(sb + OFF_CONST + 1152 + p * 8, (nr * lr + ai * li) * den, (ai * lr - nr * li) * den);
      }
      bar_sync(NB_DUMP, 352);
      {
        const int lane = threadIdx.x & 31;
        const int half = warp == 11 ? (lane >> 2) & 1 : warp - 9;
        const uint32_t cu = sb + OFF_CONST + (warp == 11 ? 32 + (lane & 3) : lane) * 16;
        uint32_t a0 = sb + OFF_DUMP + half * HS_BYTES + (warp == 11 ? 16 : lane >> 2) * HS_LBO + (lane & 3) * 4;
        asm volatile("" : "+r"(a0));
        const uint32_t di = warp == 11 ? HS_LBO : 8 * HS_LBO;
        float a[4], h[4] = {0.f, 0.f, 0.f, 0.f};
        auto ld4 = [&](uint32_t ad, float (&v)[4]) { asm volatile("ld.shared.v4.f32 {%0,%1,%2,%3}, [%4];" : "=f"(v[0]), "=f"(v[1]), "=f"(v[2]), "=f"(v[3]) : "r"(ad) : "memory"); };
        auto cfma = [&](const float (&c)[4], float r0, float i0, float r1, float i1) {
          const float n0 = fmaf(c[0], h[0], fmaf(-c[1], h[1], r0)), n1 = fmaf(c[2], h[2], fmaf(-c[3], h[3], r1));
          h[1] = fmaf(c[0], h[1], fmaf(c[1], h[0], i0)); h[3] = fmaf(c[2], h[3], fmaf(c[3], h[2], i1));
          h[0] = n0; h[2] = n1;
        };
        ld4(cu, a);
#pragma unroll 1
        for (uint32_t ad = a0; ad != a0 + 1024; ad += 64) {
          uint32_t wr[4], wi[4];
#pragma unroll
          for (int k = 0; k < 4; k++) { wr[k] = lds32(ad + k * 16); wi[k] = lds32(ad + di + k * 16); }
#pragma unroll
          for (int k = 0; k < 4; k++) cfma(a, bflo(wr[k]), bflo(wi[k]), bfhi(wr[k]), bfhi(wi[k]));
        }
        if (half == 0) sts128(cu + 1728, __float_as_uint(h[0]), __float_as_uint(h[1]), __float_as_uint(h[2]), __float_as_uint(h[3]));
        bar_sync(NB_SCAN, 96);
        if (half == 1 && m < 15) {
          float b[4], s1[4] = {h[0], h[1], h[2], h[3]};
          ld4(cu + 576, b); ld4(cu + 1728, h);
          cfma(b, s1[0], s1[1], s1[2], s1[3]);
          uint2* gp = &g_S[epoch & 1][m][j][(cu - sb - OFF_CONST) >> 3];
          asm volatile("st.relaxed.gpu.global.v2.b64 [%0], {%1,%2};" ::"l"(gp), "l"(~(((uint64_t)__float_as_uint(h[1]) << 32) | __float_as_uint(h[0]))),
                       "l"(~(((uint64_t)__float_as_uint(h[3]) << 32) | __float_as_uint(h[2]))) : "memory");
        }
        __syncwarp();
        g_S[(epoch & 1) ^ 1][m][j][p] = make_uint2(0u, 0u);
        {
          const float2 b = lds64f(sb + OFF_CONST + 576 + p * 8);
          const float br = b.x * b.x - b.y * b.y, bi = 2.f * b.x * b.y;
          float hr = 0.f, hi = 0.f;
          const uint2* sp = &g_S[epoch & 1][0][j][p];
#pragma unroll 1
          for (int left = m; left > 0; left -= 3, sp += 3 * 768) {
            uint32_t v[3][2];
            int spins = 0;
            uint32_t ok;
            do {
#pragma unroll
              for (int k = 0; k < 3; k++) {
                v[k][0] = v[k][1] = 0xffffffffu;
                if (k < left) asm volatile("ld.relaxed.gpu.global.v2.b32 {%0,%1}, [%2];" : "=r"(v[k][0]), "=r"(v[k][1]) : "l"(sp + k * 768) : "memory");
              }
              ok = min(min(min(v[0][0], v[0][1]), min(v[1][0], v[1][1])), min(v[2][0], v[2][1]));
              if (++spins > (1 << 22)) __trap();
            } while (ok == 0u);
#pragma unroll
            for (int k = 0; k < 3; k++)
              if (k < left) { const float nr = fmaf(br, hr, fmaf(-bi, hi, __uint_as_float(~v[k][0]))); hi = fmaf(br, hi, fmaf(bi, hr, __uint_as_float(~v[k][1]))); hr = nr; }
          }
          sts64f(sb + OFF_CONST + p * 8, hr, hi);
        }
        __syncwarp();
        bar_sync(NB_SCAN, 96);
        ld4(cu, h);
        uint32_t cr, ci, cn;
        {
          float b[4], s0[4];
          ld4(cu + 576, b); ld4(cu + 1728, s0);
          if (half == 1) cfma(b, s0[0], s0[1], s0[2], s0[3]);
          ld4(cu + 1152, b);
          cr = pack_bf16(b[0], b[2]); ci = pack_bf16(b[1], b[3]); cn = ci ^ 0x80008000u;
        }
        h[1] = -h[1]; h[3] = -h[3];
        __syncwarp();
#pragma unroll 1
        for (uint32_t ad = a0; ad != a0 + 1024; ad += 32) {
          uint32_t wr[2], wi[2];
#pragma unroll
          for (int k = 0; k < 2; k++) { wr[k] = lds32(ad + k * 16); wi[k] = lds32(ad + di + k * 16); }
#pragma unroll
          for (int k = 0; k < 2; k++) {
            const float n0 = fmaf(a[0], h[0], fmaf(a[1], h[1], bflo(wr[k]))), n1 = fmaf(a[2], h[2], fmaf(a[3], h[3], bfhi(wr[k])));
            h[1] = fmaf(a[0], h[1], fmaf(-a[1], h[0], -bflo(wi[k]))); h[3] = fmaf(a[2], h[3], fmaf(-a[3], h[2], -bfhi(wi[k])));
            h[0] = n0; h[2] = n1;
            const uint32_t hr = pack_bf16(h[0], h[2]), hn = pack_bf16(h[1], h[3]);
            uint32_t o0, o1;
            asm("{.reg .b32 t; mul.rn.bf16x2 t, %2, %4; fma.rn.bf16x2 %0, %1, %3, t;}" : "=r"(o0) : "r"(hr), "r"(hn), "r"(cr), "r"(ci));
            asm("{.reg .b32 t; mul.rn.bf16x2 t, %1, %4; fma.rn.bf16x2 %0, %2, %3, t;}" : "=r"(o1) : "r"(hr), "r"(hn), "r"(cr), "r"(cn));
            asm volatile("st.shared.b32 [%0], %1;" ::"r"(ad + k * 16), "r"(o0) : "memory");
            asm volatile("st.shared.b32 [%0], %1;" ::"r"(ad + di + k * 16), "r"(o1) : "memory");
          }
        }
        asm volatile("fence.proxy.async.shared::cta;" ::: "memory");
      }
      bar_sync(NB_SCAN, 96);
      const bool lead = elect();
      if (warp == 9) {
        if (lead) {
#pragma unroll 1
          for (int i = 0; i < 10; i++) {
            const int pc = (0x8654321970ull >> (4 * i)) & 15, w = pc & 1, c4 = pc >> 1;
            asm volatile("cp.async.bulk.global.shared::cta.bulk_group [%0], [%1], %2;" ::"l"(&g_hs[blockIdx.x][c4 < 4 ? w * HS_MAIN + c4 * 4 * HS_LBO : 2 * HS_MAIN + w * HS_REM]),
                         "r"(sb + OFF_DUMP + w * HS_BYTES + c4 * 4 * HS_LBO), "r"(c4 < 4 ? 4 * HS_LBO : HS_REM) : "memory");
            asm volatile("cp.async.bulk.commit_group;\ncp.async.bulk.wait_group.read 0;" ::: "memory");
            if (i == 2) mbar_arrive(bars + 8 * B_SCAN);
          }
          mbar_arrive(bars + 8 * (B_SCAN + 1));
        }
        __syncwarp();
      }
      if (warp == 9) {
        if (lead) {
          __threadfence();
          asm volatile("red.release.gpu.global.add.u32 [%0], 1;" ::"l"(&g_ready[m]) : "memory");
          g_epoch[blockIdx.x] = epoch + 1u;
          asm volatile("cp.async.bulk.wait_group 0;" ::: "memory");
          mbar_arrive(bars + 8 * B_PARK);
        }
        __syncwarp();
        bar_sync(NB_HFREE, 288);
        if (lead) {
          mbar_arrive(bars + 8 * B_HFREE);
          mbar_expect(bars + 8 * B_HSFULL, 2 * HS_MAIN);
          asm volatile("cp.async.bulk.shared::cluster.global.mbarrier::complete_tx::bytes [%0], [%1], %2, [%3];" ::"r"(sb + OFF_HS),
                       "l"(&g_hs[blockIdx.x][0]), "r"(2 * HS_MAIN), "r"(bars + 8 * B_HSFULL) : "memory");
          for (int w = 0; w < 2; w++) mbar_arrive_cta(bars + 8 * (B_RFREE + w), rank ^ 1);
        }
        __syncwarp();
      } else {
        const int w = warp - 10;
        {
          const unsigned target = 8u * (epoch + 1u);
          int spins = 0;
          unsigned v;
          do {
            if (spins) __nanosleep(500);
            asm volatile("ld.relaxed.gpu.global.u32 %0, [%1];" : "=r"(v) : "l"(&g_ready[m]) : "memory");
            if (++spins > (1 << 21)) __trap();
          } while ((int)(v - target) < 0);
          asm volatile("fence.acq_rel.gpu;" ::: "memory");
          asm volatile("fence.proxy.async.global;" ::: "memory");
        }
        const uint32_t stg = sb + OFF_STG + w * 32768;
        const int nu = 5 + rank;
#pragma unroll 1
        for (int u = 0; u < nu; u++) {
          const int t = u - rank;
          if (t == 0 || t == 2) {
            if (elect()) mbar_expect(bars + 8 * (B_RFULL + w), 16384);
            mbar_wait(bars + 8 * (B_SFULL + w), u & 1);
            mbar_wait(bars + 8 * (B_RFREE + w), t >> 1);
            if (elect())
              asm volatile("{.reg .b32 ra, rb; mapa.shared::cluster.u32 ra, %0, %3; mapa.shared::cluster.u32 rb, %2, %3;\n"
                           "cp.async.bulk.shared::cluster.shared::cta.mbarrier::complete_tx::bytes [ra], [%1], 16384, [rb];}" ::"r"(stg + 16384),
                           "r"(stg), "r"(bars + 8 * (B_RFULL + w)), "r"(rank ^ 1) : "memory");
            mbar_wait(bars + 8 * (B_RFULL + w), t >> 1);
            if (elect()) mbar_arrive_cta(bars + 8 * (B_SFREE + w), rank ^ 1);
          } else {
            mbar_wait(bars + 8 * (B_SFULL + w), u & 1);
            const bool d = u == (rank ? 0 : 4), hf = rank && u >= 4;
            const int n0 = d ? 512 : rank * 256 + (((min(t, 3) >> 1) ^ (j >> 1)) & 1) * 128 + (u == 5 ? 64 : 0);
            const uint32_t src = d && !rank ? sb + w * SLOT : stg + (u == 5 ? 16384 : 0);
            if (elect()) {
#pragma unroll 1
              for (int b = 0; b < (d || hf ? 2 : 4); b++) {
                asm volatile("cp.reduce.async.bulk.tensor.4d.global.shared::cta.add.tile.bulk_group [%0, {%1,%2,%2,%3}], [%4];" ::"l"(&prm.tOut), "r"(n0 + b * 32), "r"(0),
                             "r"(m * 16 + w * 8), "r"(src + b * 8192) : "memory");
                asm volatile("cp.async.bulk.commit_group;" ::: "memory");
                if (u < nu - 1) asm volatile("cp.async.bulk.wait_group.read 0;" ::: "memory");
              }
              if (u < 3) {
                asm volatile("cp.async.bulk.wait_group.read 0;" ::: "memory");
                mbar_arrive(bars + 8 * (B_SFREE + w));
                if (t == 1) mbar_arrive_cta(bars + 8 * (B_RFREE + w), rank ^ 1);
              }
              if (u == nu - 1) asm volatile("cp.async.bulk.wait_group.read 0;" ::: "memory");
            }
          }
          __syncwarp();
        }
      }
    }
  } else {
    asm volatile("setmaxnreg.inc.sync.aligned.u32 240;");
    const uint32_t sb = smem_base(), bars = sb + OFF_BAR;
    const int wg = warp >> 2, w4 = warp & 3;
    const int lane = threadIdx.x & 31, g = lane >> 2, q = lane & 3;
    const uint32_t hw = sb + OFF_H + wg * 65536;

    int s = 0, nst = NST + 2; uint32_t ph = 0;
    auto release = [&](int st) { if (w4 == 0) { if (elect()) mbar_arrive(bars + 8 * (B_EMPTY + st)); } };
    const uint32_t dring = (sb & 0x3FFFF) >> 4;
    uint32_t dlo; int prev = 0;
    auto stage_begin = [&]() { mbar_wait(bars + 8 * (B_FULL + s), ph); dlo = dring + s * (SLOT >> 4); wg_fence(); };
    auto advance = [&]() { if (++s == nst) { s = 0; ph ^= 1; } };
    auto stage_end = [&](bool rel) {
      wg_commit();
      if (rel) { wg_wait<1>(); release(prev); }
      prev = s;
      advance();
    };

    uint32_t xa[144];
    uint32_t xr[18], dk[9];
    uint32_t rh[2], cc[2];
#pragma unroll
    for (int i = 0; i < 9; i++) dk[i] = __ldg((const uint32_t*)(prm.dskip + j * 72 + i * 8 + q * 2));
    {
      const int r = w4 * 16 + (lane & 7) + ((lane >> 3) & 1) * 8;
      const uint32_t ro = r * 128, cx = ((lane >> 4) ^ (lane & 7)) << 4;
      float s1[2][4] = {};
      auto load = [&](int kb, uint32_t base) {
#pragma unroll
        for (int kk = 0; kk < 4; kk++) {
          const int i = (kb * 4 + kk) * 4;
          asm volatile("ldmatrix.sync.aligned.m8n8.x4.shared.b16 {%0,%1,%2,%3}, [%4];"
                       : "=r"(xa[i]), "=r"(xa[i + 1]), "=r"(xa[i + 2]), "=r"(xa[i + 3]) : "r"(base + ro + (cx ^ (kk << 5))) : "memory");
        }
      };
      float s2[4] = {}, s3[4] = {};
      auto sums = [&](int kb) {
#pragma unroll
        for (int kk = 0; kk < 4; kk += 2) {
          const int i = (kb * 4 + kk) * 4;
          uint32_t a[8];
#pragma unroll
          for (int e = 0; e < 8; e++) asm("mul.rn.bf16x2 %0, %1, %1;" : "=r"(a[e]) : "r"(xa[i + e]));
          mma16816(s3, a[4], a[5], a[6], a[7], 0x3f803f80u, 0x3f803f80u);
          mma16816(s1[0], xa[i], xa[i + 1], xa[i + 2], xa[i + 3], 0x3f803f80u, 0x3f803f80u);
          mma16816(s2, a[0], a[1], a[2], a[3], 0x3f803f80u, 0x3f803f80u);
          mma16816(s1[1], xa[i + 4], xa[i + 5], xa[i + 6], xa[i + 7], 0x3f803f80u, 0x3f803f80u);
        }
      };
#pragma unroll
      for (int i = 0; i < 9; i++) {
        const int c8 = j * 9 + i, kb = c8 >> 3;
        xr[2 * i] = (kb < 8 ? hw + kb * 8192 : sb + wg * 8192) + (w4 * 16 + g) * 128 + (((c8 & 7) ^ g) << 4) + q * 4;
        asm volatile("" : "+r"(xr[2 * i]));
      }
      mbar_wait(bars + 8 * B_X8, 0);
      load(8, sb + wg * 8192);
      auto pin = [&]() { asm volatile("{.reg .pred p; .reg .u32 c, z; mov.u32 c, %clock; mov.u32 z, %ntid.y; setp.eq.u32 p, z, 0; @p st.shared.u32 [c], c;}" ::: "memory"); };
#pragma unroll
      for (int kp = 0; kp < 4; kp++) {
        mbar_wait(bars + 8 * (B_X + wg * 4 + kp), 0);
        load(2 * kp, hw + 2 * kp * 8192);
        load(2 * kp + 1, hw + (2 * kp + 1) * 8192);
        if (kp == 3) {
#pragma unroll
          for (int i = 0; i < 9; i++) { xr[2 * i + 1] = lds32(xr[2 * i] + 1024); xr[2 * i] = lds32(xr[2 * i]); }
        }
        if (kp == 0) sums(8); else { sums(2 * kp - 2); sums(2 * kp - 1); }
      }
      asm volatile("fence.proxy.async.shared::cta;" ::: "memory");
      bar_arrive(NB_XDONE + wg, 160);
      if (wg == 1) bar_arrive(NB_STATS, 256);
      pin();
      sums(6);
      sums(7);
      pin();
#pragma unroll
      for (int e = 0; e < 2; e++) {
        const float mu = (s1[0][2 * e + 1] + s1[1][2 * e + 1]) * (1.f / kD);
        const float var = fmaxf(fmaf(-mu, mu, (s2[2 * e] + s3[2 * e]) * (1.f / kD)), 0.f);
        float sd, r;
        asm("sqrt.approx.ftz.f32 %0, %1;" : "=f"(sd) : "f"(rbf(rbf(var) + 1e-5f)));
        asm("rcp.approx.ftz.f32 %0, %1;" : "=f"(r) : "f"(rbf(sd)));
        rh[e] = pack_bf16(0.5f * r, 0.5f * r);
        cc[e] = pack_bf16(mu, mu);
      }
    }

    auto normalise = [&](int kb) {
#pragma unroll
      for (int i = 0; i < 16; i++) asm("{.reg .b32 d; sub.rn.bf16x2 d, %0, %2; mul.rn.bf16x2 %0, d, %1;}" : "+r"(xa[16 * kb + (i >> 3) + 2 * (i & 7)]) : "r"(rh[i >> 3]), "r"(cc[i >> 3]));
    };
    {
      float ab[36];
      float* op = prm.out + (size_t)(m * 128 + wg * 64 + w4 * 16 + g) * kD + j * 72 + q * 2;
      auto residual = [&](int i) {
        asm volatile("add.rn.bf16x2 %0, %0, %0;" : "+r"(dk[i]));
#pragma unroll
        for (int e = 0; e < 2; e++) {
          uint32_t t;
          asm("{.reg .b32 d; sub.rn.bf16x2 d, %1, %3; mul.rn.bf16x2 %0, d, %2;}" : "=r"(t) : "r"(xr[2 * i + e]), "r"(rh[e]), "r"(cc[e]));
          asm("fma.rn.bf16x2 %0, %0, %1, %2;" : "+r"(t) : "r"(dk[i]), "r"(xr[2 * i + e]));
          *(float2*)(op + e * 8 * kD + i * 8) = make_float2(bflo(t), bfhi(t));
        }
      };
      const uint32_t da = sb + OFF_DUMP + wg * HS_BYTES + (w4 * 16 + g) * 16 + q * 4;
      auto dump = [&](int im) {
#pragma unroll
        for (int i = 0; i < 18; i++)
          asm volatile("st.shared.b32 [%0], %1;" ::"r"(da + (i < 16 ? 8 * im + (i >> 1) : 16 + im) * HS_LBO + (i & 1) * 128), "r"(pack_bf16(ab[2 * i], ab[2 * i + 1])) : "memory");
      };
      auto bu = [&](int kb, uint32_t off) {
        wg_fence();
#pragma unroll
        for (int kk = 0; kk < 4; kk++) { const int i = (kb * 4 + kk) * 4; wgmma_n72_rs_tb0(ab, xa[i], xa[i + 1], xa[i + 2], xa[i + 3], desc((dring + (off >> 4) + kk * 2) + DLO_K, DHI_SW128), (kb | kk) != 0); }
        wg_commit();
      };
      normalise(0);
      if (wg == 0) {
#pragma unroll
        for (int kb = 1; kb < 9; kb++) normalise(kb);
        bar_sync(NB_STATS, 256);
      }
#pragma unroll
      for (int kb = 0; kb < 9; kb++) {
        if ((kb & 3) == 0) mbar_wait(bars + 8 * (B_BU + (kb >> 2)), 0);
        bu(kb, kb < 8 ? OFF_BU0 + kb * 9216 : OFF_BU1);
        if (wg == 0) residual(kb);
        else if (kb < 8) normalise(kb + 1);
      }
      wg_wait<0>();
      if (w4 == 0) { if (elect()) mbar_arrive(bars + 8 * B_RING); }
      keep(ab);
      dump(0);
#pragma unroll
      for (int kb = 0; kb < 9; kb++) {
        if (kb == 4) mbar_wait(bars + 8 * (B_BU + 3), 0);
        bu(kb, kb < 4 ? OFF_BU1 + (kb + 1) * 9216 : OFF_BU2 + (kb - 4) * 9216);
        if (wg == 1) residual(kb);
        if (kb == 5) { wg_wait<2>(); if (w4 == 0) { if (elect()) mbar_arrive(bars + 8 * (B_RING + 1)); } }
      }
      wg_wait<0>();
      keep(ab);
      dump(1);
      bar_arrive(NB_DUMP, 352);
    }

    float acc[64];
    {
      const uint32_t ha = sb + OFF_H + (threadIdx.x & 127) * 16, hblk = wg ? HBLK1 : HBLK0;
      auto glu = [&](int i) {
        return pack_bf16(fmaf(acc[32 + 2 * i], tanh_fast(acc[2 * i]), acc[32 + 2 * i]), fmaf(acc[33 + 2 * i], tanh_fast(acc[2 * i + 1]), acc[33 + 2 * i]));
      };
      for (int c = 0; c < 8; c++) {
        if (wg == 1) bar_sync(NB_SKEW, 256);
#pragma unroll
        for (int kb = 0; kb < 9; kb++) {
          if (kb == 6 && c == 3) nst = 7;
          if (kb == 5 && c == 7) nst = 6;
          stage_begin();
#pragma unroll
          for (int kk = 0; kk < 4; kk++) { const int i = (kb * 4 + kk) * 4; wgmma_n128_rs_tb1(acc, xa[i], xa[i + 1], xa[i + 2], xa[i + 3], desc((dlo + kk * 128) + DLO_MN, DHI_SW128), (kb | kk) != 0); }
          if (kb == SKEW - 1 && wg == 0) bar_arrive(NB_SKEW, 256);
          if (kb == 8 && c >= 3 && c != 6) mbar_wait(bars + 8 * (c == 3 ? B_EMPTY + 7 : c == 7 ? B_EMPTY + 6 : B_SCAN - 4 + c), c == 3);
          stage_end(kb > 0);
        }
        wg_wait<0>();
        release(prev);
        keep(acc);
        const uint32_t hc = ha + ((hblk >> (4 * c)) & 15) * 8192;
#pragma unroll
        for (int i = 0; i < 4; i++) sts128(hc + i * 2048, glu(4 * i), glu(4 * i + 1), glu(4 * i + 2), glu(4 * i + 3));
      }
      if (wg == 1) bar_sync(NB_SKEW, 256);
#pragma unroll
      for (int kb = 0; kb < 9; kb++) {
        stage_begin();
#pragma unroll
        for (int kk = 0; kk < 4; kk++) { const int i = (kb * 4 + kk) * 4; wgmma_n128_rs_tb1(acc, xa[i], xa[i + 1], xa[i + 2], xa[i + 3], desc((dlo + kk * 128) + DLO_MN, DHI_SW128), (kb | kk) != 0); }
        if (kb == SKEW - 1 && wg == 0) bar_arrive(NB_SKEW, 256);
        stage_end(kb > 0);
        if (kb > 0) {
          const uint32_t hc = ha + ((hblk >> (4 * (kb - 1))) & 15) * 8192;
#pragma unroll
          for (int i = 4 * (kb - 1); i < 4 * kb; i++) lds128_inplace(hc + (i & 3) * 2048, xa[4 * i], xa[4 * i + 1], xa[4 * i + 2], xa[4 * i + 3]);
        }
      }
      asm volatile("fence.proxy.async.shared::cta;" ::: "memory");
      bar_arrive(NB_HFREE, 288);
      wg_wait<0>();
      release(prev);
      keep(acc);
#pragma unroll
      for (int i = 0; i < 16; i++) xa[128 + i] = glu(i);
    }

    const uint32_t dhs = (((sb + OFF_HS + wg * HS_MAIN) & 0x3FFFF) >> 4) | DLO_HS, drem = DLO_HS + wg * (HS_REM >> 4);
    const int rp = (g >> 2) + 2 * (g & 3);
    const uint32_t so = w4 * 2048 + rp * 128 + (q & 1) * 8, sx = ((q >> 1) ^ rp) << 4;
    const uint32_t rcv = sb + OFF_STG + wg * 32768 + 16384 + w4 * 2048 + lane * 16;
    auto staged = [&]() {
      asm volatile("fence.proxy.async.shared::cta;" ::: "memory");
      __syncwarp();
      if (elect()) mbar_arrive(bars + 8 * (B_SFULL + wg));
    };
    auto half_tile = [&](const bool first, const int kind) {
      float a2[32];
      if (wg == 1) { if (!first) staged(); bar_sync(NB_SKEW, 256); }
      const uint32_t ph0 = ph;
      uint32_t d4;
#pragma unroll
      for (int kp = 0; kp < 5; kp++) {
        stage_begin();
#pragma unroll
        for (int kk = 0; kk < (kp < 4 ? 8 : 4); kk++) { const int i = (kp * 8 + kk) * 4; wgmma_n64_rs_tb1(a2, xa[i], xa[i + 1], xa[i + 2], xa[i + 3], desc((dlo + kk * 128) + DLO_MN, DHI_SW128), (kp | kk) != 0); }
        if (kp == 2 && wg == 0) bar_arrive(NB_SKEW, 256);
        d4 = dlo;
        stage_end(kp > 0);
        if (kp == 0 && !first && wg == 0) staged();
      }
      if (first) mbar_wait(bars + 8 * B_HSFULL, 0);
      stage_begin();
#pragma unroll
      for (int kk = 0; kk < 8; kk++) wgmma_n64_ss_tb0(a2, desc(dhs + kk * (2 * HS_LBO >> 4), DHI_NONE), desc((dlo + (kk >> 2) * 512 + (kk & 3) * 2) + DLO_K, DHI_SW128), 1);
      wgmma_n64_ss_tb0(a2, desc(d4 + 640 + drem, DHI_NONE), desc((d4 + 512) | ((1024 >> 4) << 16), DHI_NONE), 1);
      wg_commit();
      if (!first) {
        if (kind == 1) mbar_wait(bars + 8 * (B_EMPTY + wg), ph0 ^ 1);
        if (kind == 2) { mbar_wait(bars + 8 * (B_SFREE + wg), 1); mbar_wait(bars + 8 * (B_RFULL + wg), 1); }
      }
      wg_wait<0>();
      release(prev); release(s); advance();
      keep(a2);
      if (!first && kind >= 2) {
#pragma unroll
        for (int i = 0; i < 4; i++) {
          uint32_t v[4];
          lds128(rcv + (kind & 1) * 8192 + i * 512, v[0], v[1], v[2], v[3]);
#pragma unroll
          for (int e = 0; e < 4; e++) { a2[8 * i + 2 * e] += bflo(v[e]); a2[8 * i + 2 * e + 1] += bfhi(v[e]); }
        }
        __syncwarp();
      }
      const uint32_t stg = (!first && kind == 1 ? sb + wg * SLOT : sb + OFF_STG + wg * 32768 + (kind == 3 ? 16384 : 0)) + so;
#pragma unroll
      for (int i = 0; i < 8; i++) {
        const uint32_t a = stg + (i >> 2) * 8192 + (sx ^ ((i & 3) << 5));
        sts64f(a, a2[4 * i], a2[4 * i + 1]);
        sts64f(a + 1024, a2[4 * i + 2], a2[4 * i + 3]);
      }
    };
    if (rank) half_tile(true, 0);
    for (int t = 0; t < 4 - rank; t++) {
      if (wg == 1) { if (t + rank > 0) staged(); bar_sync(NB_SKEW, 256); }
#pragma unroll
      for (int kb = 0; kb < 9; kb++) {
        if ((kb == 5 && t == 0 && rank) || (kb == 1 && t == 1)) nst = NST + 1;
        if (t == 1 && ((kb == 1 && rank) || kb == 7)) nst = NST + 2;
        stage_begin();
#pragma unroll
        for (int kk = 0; kk < 4; kk++) { const int i = (kb * 4 + kk) * 4; wgmma_n128_rs_tb1(acc, xa[i], xa[i + 1], xa[i + 2], xa[i + 3], desc((dlo + kk * 128) + DLO_MN, DHI_SW128), (kb | kk) != 0); }
        if (kb == SKEW - 1 && wg == 0) bar_arrive(NB_SKEW, 256);
        stage_end(kb > 0);
        if (kb == 3 && t + rank > 0 && wg == 0) staged();
      }
      if (t == 0) mbar_wait(bars + 8 * B_HSFULL, 0);
      stage_begin();
#pragma unroll
      for (int kk = 0; kk < 4; kk++) wgmma_n128_ss_tb0(acc, desc(dhs + kk * (2 * HS_LBO >> 4), DHI_NONE), desc((dlo + kk * 2) + DLO_K, DHI_SW128), 1);
      stage_end(true);
      stage_begin();
#pragma unroll
      for (int kk = 0; kk < 4; kk++) wgmma_n128_ss_tb0(acc, desc(dhs + (4 + kk) * (2 * HS_LBO >> 4), DHI_NONE), desc((dlo + kk * 2) + DLO_K, DHI_SW128), 1);
      const int s_im = s;
      advance();
      stage_begin();
      wgmma_n128_ss_tb0(acc, desc(dlo + 256 + drem, DHI_NONE), desc(dlo | ((2048 >> 4) << 16), DHI_NONE), 1);
      stage_end(true);
      if (t + rank > 0) mbar_wait(bars + 8 * (B_SFREE + wg), (t + rank - 1) & 1);
      if (t & 1) mbar_wait(bars + 8 * (B_RFULL + wg), t >> 1);
      wg_wait<0>();
      release(s_im); release(prev);
      keep(acc);
      if (t & 1) {
        const uint32_t stg = sb + OFF_STG + wg * 32768 + so;
#pragma unroll
        for (int hh = 0; hh < 2; hh++) {
#pragma unroll
          for (int i = 4 * hh; i < 4 * hh + 4; i++) {
            uint32_t v[4];
            lds128(rcv + hh * 8192 + (i & 3) * 512, v[0], v[1], v[2], v[3]);
#pragma unroll
            for (int e = 0; e < 4; e++) { acc[8 * i + 2 * e] += bflo(v[e]); acc[8 * i + 2 * e + 1] += bfhi(v[e]); }
          }
          __syncwarp();
#pragma unroll
          for (int i = 8 * hh; i < 8 * hh + 8; i++) {
            const uint32_t a = stg + (i >> 2) * 8192 + (sx ^ ((i & 3) << 5));
            sts64f(a, acc[4 * i], acc[4 * i + 1]);
            sts64f(a + 1024, acc[4 * i + 2], acc[4 * i + 3]);
          }
        }
      } else {
#pragma unroll
        for (int i = 0; i < 8; i++)
          sts128(rcv - 16384 + (i >> 2) * 8192 + (i & 3) * 512, pack_bf16(acc[8 * i], acc[8 * i + 1]), pack_bf16(acc[8 * i + 2], acc[8 * i + 3]),
                 pack_bf16(acc[8 * i + 4], acc[8 * i + 5]), pack_bf16(acc[8 * i + 6], acc[8 * i + 7]));
      }
    }
#pragma unroll 1
    for (int kind = 1 + rank; kind < 2 + 2 * rank; kind++) half_tile(false, kind);
    staged();
  }
}

typedef CUresult (*EncodeFn)(CUtensorMap*, CUtensorMapDataType, cuuint32_t, void*, const cuuint64_t*, const cuuint64_t*, const cuuint32_t*,
                             const cuuint32_t*, CUtensorMapInterleave, CUtensorMapSwizzle, CUtensorMapL2promotion, CUtensorMapFloatOOBfill);

void map2d(EncodeFn enc, CUtensorMap* tm, const void* p, uint64_t cols, uint64_t rows, uint32_t bc, uint32_t br, CUtensorMapSwizzle sw) {
  cuuint64_t gd[2] = {cols, rows}, gs[1] = {cols * 2};
  cuuint32_t bd[2] = {bc, br}, es[2] = {1, 1};
  enc(tm, CU_TENSOR_MAP_DATA_TYPE_BFLOAT16, 2, (void*)p, gd, gs, bd, es, CU_TENSOR_MAP_INTERLEAVE_NONE, sw,
      sw == CU_TENSOR_MAP_SWIZZLE_128B ? CU_TENSOR_MAP_L2_PROMOTION_L2_128B : CU_TENSOR_MAP_L2_PROMOTION_NONE, CU_TENSOR_MAP_FLOAT_OOB_FILL_NONE);
}

}

extern "C" void kernel_launch(void* const* d_in, const int* in_sizes, int n_in, void* d_out, int out_size) {
  (void)in_sizes; (void)n_in; (void)out_size;
  static EncodeFn enc = nullptr;
  if (!enc) {
    cudaDriverEntryPointQueryResult qr;
    cudaGetDriverEntryPoint("cuTensorMapEncodeTiled", (void**)&enc, cudaEnableDefault, &qr);
    cudaFuncSetAttribute(fused_kernel, cudaFuncAttributeMaxDynamicSharedMemorySize, SMEM_BYTES);
  }
  Params prm;
  const CUtensorMapSwizzle S128 = CU_TENSOR_MAP_SWIZZLE_128B;
  map2d(enc, &prm.tx, d_in[0], kD, kS, 64, 64, S128);
  map2d(enc, &prm.tBre, d_in[3], kD, 576, 64, 72, S128);
  map2d(enc, &prm.tBim, d_in[4], kD, 576, 64, 72, S128);
  map2d(enc, &prm.tCre, d_in[5], 576, kD, 64, 64, S128);
  map2d(enc, &prm.tCim, d_in[6], 576, kD, 64, 64, S128);
  map2d(enc, &prm.tCre8, d_in[5], 576, kD, 8, 64, CU_TENSOR_MAP_SWIZZLE_NONE);
  map2d(enc, &prm.tCim8, d_in[6], 576, kD, 8, 64, CU_TENSOR_MAP_SWIZZLE_NONE);
  map2d(enc, &prm.tWg, d_in[10], kF, kD, 64, 64, S128);
  map2d(enc, &prm.tWu, d_in[11], kF, kD, 64, 64, S128);
  map2d(enc, &prm.tWd, d_in[12], kD, kF, 64, 64, S128);
  {
    cuuint64_t gd[4] = {kD, 2, 4, kS / 8}, gs[3] = {4 * kD * 4, kD * 4, 8 * kD * 4};
    cuuint32_t bd[4] = {32, 2, 4, 8}, es[4] = {1, 1, 1, 1};
    enc(&prm.tOut, CU_TENSOR_MAP_DATA_TYPE_FLOAT32, 4, d_out, gd, gs, bd, es, CU_TENSOR_MAP_INTERLEAVE_NONE, S128, CU_TENSOR_MAP_L2_PROMOTION_NONE,
        CU_TENSOR_MAP_FLOAT_OOB_FILL_NONE);
  }
  prm.lre = (const __nv_bfloat16*)d_in[1];
  prm.lim = (const __nv_bfloat16*)d_in[2];
  prm.bre = (const __nv_bfloat16*)d_in[3];
  prm.bim = (const __nv_bfloat16*)d_in[4];
  prm.cre = (const __nv_bfloat16*)d_in[5];
  prm.cim = (const __nv_bfloat16*)d_in[6];
  prm.wg = (const __nv_bfloat16*)d_in[10];
  prm.wu = (const __nv_bfloat16*)d_in[11];
  prm.wd = (const __nv_bfloat16*)d_in[12];
  prm.ldt = (const __nv_bfloat16*)d_in[7];
  prm.dskip = (const __nv_bfloat16*)d_in[8];
  prm.out = (float*)d_out;

  fused_kernel<<<128, 384, SMEM_BYTES, cudaStreamPerThread>>>(prm);
}
```

```cpp
#include <cuda_runtime.h>
#include <cuda.h>
#include <cuda_bf16.h>
#include <stdint.h>

namespace {

constexpr int kS = 2048, kD = 576, kF = 4608;
constexpr int SKEW = 4;
constexpr int PFD = 18;
constexpr int NST = 6;
constexpr uint32_t SLOT = 16384;
constexpr uint32_t OFF_H = NST * SLOT;
constexpr uint32_t HS_LBO = 1040;
constexpr uint32_t HS_BYTES = 18 * HS_LBO;
constexpr uint32_t OFF_DUMP = OFF_H + 65536 - HS_BYTES;
constexpr uint32_t OFF_STG = OFF_H + 2 * SLOT;
constexpr uint32_t OFF_HS = OFF_STG + 65536;
constexpr uint32_t HS_MAIN = 16 * HS_LBO, HS_REM = 2 * HS_LBO;
constexpr uint32_t OFF_CONST = OFF_H + 131072;
constexpr uint32_t OFF_BAR = OFF_CONST + 4 * 576;
constexpr uint32_t SMEM_BYTES = OFF_BAR + 384 + 384;
static_assert(SMEM_BYTES <= 232448 && OFF_HS + 2 * HS_MAIN <= OFF_BAR, "smem");

enum { B_FULL = 0, B_EMPTY = NST + 2, B_X = 2 * NST + 4, B_X8 = B_X + 8, B_BU  , B_RING = B_BU + 4  , B_SCAN = B_RING + 2  , B_PARK = B_SCAN + 2, B_HFREE, B_HSFULL, B_SFULL,
       B_SFREE = B_SFULL + 2, B_RFULL = B_SFREE + 2, B_RFREE = B_RFULL + 2, B_COUNT = B_RFREE + 2 };
static_assert(B_COUNT * 8 <= 384, "barriers");
enum { NB_SKEW = 1, NB_XDONE = 2  , NB_SCAN = 4, NB_DUMP = 5, NB_HFREE = 6, NB_STATS = 7 };
constexpr uint32_t HBLK0 = 0x07652CB4u, HBLK1 = 0x189A3DEFu;
constexpr uint32_t OFF_BU0 = SLOT, OFF_BU1 = OFF_H, OFF_BU2 = OFF_H + 65536 + 19456;
static_assert(OFF_BU1 + 5 * 9216 <= OFF_DUMP && OFF_BU2 >= OFF_DUMP + 2 * HS_BYTES && OFF_BU2 + 5 * 9216 <= OFF_CONST, "Bu tiles");

struct __align__(64) Params {
  CUtensorMap tx, tBre, tBim, tWg, tWu, tWd, tCre, tCim, tCre8, tCim8, tOut;
  const __nv_bfloat16 *lre, *lim, *bre, *bim, *cre, *cim, *ldt, *dskip, *wg, *wu, *wd;
  float* out;
};

__device__ unsigned g_epoch[128];
__device__ unsigned g_ready[16];
__device__ __align__(256) uint2 g_S[2][16][8][96];
__device__ __align__(128) uint8_t g_hs[128][2 * HS_BYTES];

__device__ __forceinline__ void wgmma_n72_rs_tb0(float (&d)[36], uint32_t a0, uint32_t a1, uint32_t a2, uint32_t a3, uint64_t db, int scale_d) {
  asm volatile("{\n.reg .pred p;\nsetp.ne.b32 p, %41, 0;\n"
    "wgmma.mma_async.sync.aligned.m64n72k16.f32.bf16.bf16 {"
    "%0, %1, %2, %3, %4, %5, %6, %7, %8, %9, %10, %11, %12, %13, %14, %15, "
    "%16, %17, %18, %19, %20, %21, %22, %23, %24, %25, %26, %27, %28, %29, %30, %31, "
    "%32, %33, %34, %35"
    "}, {%36, %37, %38, %39}, %40, p, 1, 1, 0;\n}\n"
    : "+f"(d[0]), "+f"(d[1]), "+f"(d[2]), "+f"(d[3]), "+f"(d[4]), "+f"(d[5]), "+f"(d[6]), "+f"(d[7]),
      "+f"(d[8]), "+f"(d[9]), "+f"(d[10]), "+f"(d[11]), "+f"(d[12]), "+f"(d[13]), "+f"(d[14]), "+f"(d[15]),
      "+f"(d[16]), "+f"(d[17]), "+f"(d[18]), "+f"(d[19]), "+f"(d[20]), "+f"(d[21]), "+f"(d[22]), "+f"(d[23]),
      "+f"(d[24]), "+f"(d[25]), "+f"(d[26]), "+f"(d[27]), "+f"(d[28]), "+f"(d[29]), "+f"(d[30]), "+f"(d[31]),
      "+f"(d[32]), "+f"(d[33]), "+f"(d[34]), "+f"(d[35])
    : "r"(a0), "r"(a1), "r"(a2), "r"(a3), "l"(db), "r"(scale_d));
}
__device__ __forceinline__ void wgmma_n128_rs_tb1(float (&d)[64], uint32_t a0, uint32_t a1, uint32_t a2, uint32_t a3, uint64_t db, int scale_d) {
  asm volatile("{\n.reg .pred p;\nsetp.ne.b32 p, %69, 0;\n"
    "wgmma.mma_async.sync.aligned.m64n128k16.f32.bf16.bf16 {"
    "%0, %1, %2, %3, %4, %5, %6, %7, %8, %9, %10, %11, %12, %13, %14, %15, "
    "%16, %17, %18, %19, %20, %21, %22, %23, %24, %25, %26, %27, %28, %29, %30, %31, "
    "%32, %33, %34, %35, %36, %37, %38, %39, %40, %41, %42, %43, %44, %45, %46, %47, "
    "%48, %49, %50, %51, %52, %53, %54, %55, %56, %57, %58, %59, %60, %61, %62, %63"
    "}, {%64, %65, %66, %67}, %68, p, 1, 1, 1;\n}\n"
    : "+f"(d[0]), "+f"(d[1]), "+f"(d[2]), "+f"(d[3]), "+f"(d[4]), "+f"(d[5]), "+f"(d[6]), "+f"(d[7]),
      "+f"(d[8]), "+f"(d[9]), "+f"(d[10]), "+f"(d[11]), "+f"(d[12]), "+f"(d[13]), "+f"(d[14]), "+f"(d[15]),
      "+f"(d[16]), "+f"(d[17]), "+f"(d[18]), "+f"(d[19]), "+f"(d[20]), "+f"(d[21]), "+f"(d[22]), "+f"(d[23]),
      "+f"(d[24]), "+f"(d[25]), "+f"(d[26]), "+f"(d[27]), "+f"(d[28]), "+f"(d[29]), "+f"(d[30]), "+f"(d[31]),
      "+f"(d[32]), "+f"(d[33]), "+f"(d[34]), "+f"(d[35]), "+f"(d[36]), "+f"(d[37]), "+f"(d[38]), "+f"(d[39]),
      "+f"(d[40]), "+f"(d[41]), "+f"(d[42]), "+f"(d[43]), "+f"(d[44]), "+f"(d[45]), "+f"(d[46]), "+f"(d[47]),
      "+f"(d[48]), "+f"(d[49]), "+f"(d[50]), "+f"(d[51]), "+f"(d[52]), "+f"(d[53]), "+f"(d[54]), "+f"(d[55]),
      "+f"(d[56]), "+f"(d[57]), "+f"(d[58]), "+f"(d[59]), "+f"(d[60]), "+f"(d[61]), "+f"(d[62]), "+f"(d[63])
    : "r"(a0), "r"(a1), "r"(a2), "r"(a3), "l"(db), "r"(scale_d));
}
__device__ __forceinline__ void wgmma_n128_ss_tb0(float (&d)[64], uint64_t da, uint64_t db, int scale_d) {
  asm volatile("{\n.reg .pred p;\nsetp.ne.b32 p, %66, 0;\n"
    "wgmma.mma_async.sync.aligned.m64n128k16.f32.bf16.bf16 {"
    "%0, %1, %2, %3, %4, %5, %6, %7, %8, %9, %10, %11, %12, %13, %14, %15, "
    "%16, %17, %18, %19, %20, %21, %22, %23, %24, %25, %26, %27, %28, %29, %30, %31, "
    "%32, %33, %34, %35, %36, %37, %38, %39, %40, %41, %42, %43, %44, %45, %46, %47, "
    "%48, %49, %50, %51, %52, %53, %54, %55, %56, %57, %58, %59, %60, %61, %62, %63"
    "}, %64, %65, p, 1, 1, 0, 0;\n}\n"
    : "+f"(d[0]), "+f"(d[1]), "+f"(d[2]), "+f"(d[3]), "+f"(d[4]), "+f"(d[5]), "+f"(d[6]), "+f"(d[7]),
      "+f"(d[8]), "+f"(d[9]), "+f"(d[10]), "+f"(d[11]), "+f"(d[12]), "+f"(d[13]), "+f"(d[14]), "+f"(d[15]),
      "+f"(d[16]), "+f"(d[17]), "+f"(d[18]), "+f"(d[19]), "+f"(d[20]), "+f"(d[21]), "+f"(d[22]), "+f"(d[23]),
      "+f"(d[24]), "+f"(d[25]), "+f"(d[26]), "+f"(d[27]), "+f"(d[28]), "+f"(d[29]), "+f"(d[30]), "+f"(d[31]),
      "+f"(d[32]), "+f"(d[33]), "+f"(d[34]), "+f"(d[35]), "+f"(d[36]), "+f"(d[37]), "+f"(d[38]), "+f"(d[39]),
      "+f"(d[40]), "+f"(d[41]), "+f"(d[42]), "+f"(d[43]), "+f"(d[44]), "+f"(d[45]), "+f"(d[46]), "+f"(d[47]),
      "+f"(d[48]), "+f"(d[49]), "+f"(d[50]), "+f"(d[51]), "+f"(d[52]), "+f"(d[53]), "+f"(d[54]), "+f"(d[55]),
      "+f"(d[56]), "+f"(d[57]), "+f"(d[58]), "+f"(d[59]), "+f"(d[60]), "+f"(d[61]), "+f"(d[62]), "+f"(d[63])
    : "l"(da), "l"(db), "r"(scale_d));
}
__device__ __forceinline__ void wgmma_n64_rs_tb1(float (&d)[32], uint32_t a0, uint32_t a1, uint32_t a2, uint32_t a3, uint64_t db, int scale_d) {
  asm volatile("{\n.reg .pred p;\nsetp.ne.b32 p, %37, 0;\n"
    "wgmma.mma_async.sync.aligned.m64n64k16.f32.bf16.bf16 {"
    "%0, %1, %2, %3, %4, %5, %6, %7, %8, %9, %10, %11, %12, %13, %14, %15, "
    "%16, %17, %18, %19, %20, %21, %22, %23, %24, %25, %26, %27, %28, %29, %30, %31"
    "}, {%32, %33, %34, %35}, %36, p, 1, 1, 1;\n}\n"
    : "+f"(d[0]), "+f"(d[1]), "+f"(d[2]), "+f"(d[3]), "+f"(d[4]), "+f"(d[5]), "+f"(d[6]), "+f"(d[7]),
      "+f"(d[8]), "+f"(d[9]), "+f"(d[10]), "+f"(d[11]), "+f"(d[12]), "+f"(d[13]), "+f"(d[14]), "+f"(d[15]),
      "+f"(d[16]), "+f"(d[17]), "+f"(d[18]), "+f"(d[19]), "+f"(d[20]), "+f"(d[21]), "+f"(d[22]), "+f"(d[23]),
      "+f"(d[24]), "+f"(d[25]), "+f"(d[26]), "+f"(d[27]), "+f"(d[28]), "+f"(d[29]), "+f"(d[30]), "+f"(d[31])
    : "r"(a0), "r"(a1), "r"(a2), "r"(a3), "l"(db), "r"(scale_d));
}
__device__ __forceinline__ void wgmma_n64_ss_tb0(float (&d)[32], uint64_t da, uint64_t db, int scale_d) {
  asm volatile("{\n.reg .pred p;\nsetp.ne.b32 p, %34, 0;\n"
    "wgmma.mma_async.sync.aligned.m64n64k16.f32.bf16.bf16 {"
    "%0, %1, %2, %3, %4, %5, %6, %7, %8, %9, %10, %11, %12, %13, %14, %15, "
    "%16, %17, %18, %19, %20, %21, %22, %23, %24, %25, %26, %27, %28, %29, %30, %31"
    "}, %32, %33, p, 1, 1, 0, 0;\n}\n"
    : "+f"(d[0]), "+f"(d[1]), "+f"(d[2]), "+f"(d[3]), "+f"(d[4]), "+f"(d[5]), "+f"(d[6]), "+f"(d[7]),
      "+f"(d[8]), "+f"(d[9]), "+f"(d[10]), "+f"(d[11]), "+f"(d[12]), "+f"(d[13]), "+f"(d[14]), "+f"(d[15]),
      "+f"(d[16]), "+f"(d[17]), "+f"(d[18]), "+f"(d[19]), "+f"(d[20]), "+f"(d[21]), "+f"(d[22]), "+f"(d[23]),
      "+f"(d[24]), "+f"(d[25]), "+f"(d[26]), "+f"(d[27]), "+f"(d[28]), "+f"(d[29]), "+f"(d[30]), "+f"(d[31])
    : "l"(da), "l"(db), "r"(scale_d));
}

__device__ __forceinline__ bool elect() {
  uint32_t p;
  asm volatile("{.reg .pred q; elect.sync _|q, 0xffffffff; selp.u32 %0,1,0,q;}" : "=r"(p));
  return p;
}
__device__ __forceinline__ void mbar_init(uint32_t bar, uint32_t cnt) { asm volatile("mbarrier.init.shared::cta.b64 [%0], %1;" ::"r"(bar), "r"(cnt) : "memory"); }
__device__ __forceinline__ void mbar_expect(uint32_t bar, uint32_t bytes) { asm volatile("mbarrier.arrive.expect_tx.shared::cta.b64 _, [%0], %1;" ::"r"(bar), "r"(bytes) : "memory"); }
__device__ __forceinline__ void mbar_arrive(uint32_t bar) { asm volatile("mbarrier.arrive.shared::cta.b64 _, [%0];" ::"r"(bar) : "memory"); }
__device__ __forceinline__ void mbar_arrive_cta(uint32_t bar, uint32_t cta) {
  asm volatile("{.reg .b32 ra; mapa.shared::cluster.u32 ra, %0, %1; mbarrier.arrive.shared::cluster.b64 _, [ra];}" ::"r"(bar), "r"(cta) : "memory");
}
__device__ __forceinline__ void mbar_wait(uint32_t bar, uint32_t parity) {
  asm volatile(
      "{\n.reg .pred p;\n.reg .u32 c;\nmov.u32 c, 0x100000;\n"
      "LAB_WAIT:\nmbarrier.try_wait.parity.shared::cta.b64 p, [%0], %1;\n@p bra DONE;\n"
      "nanosleep.u32 0;\nsub.u32 c, c, 1;\nsetp.ne.u32 p, c, 0;\n@p bra LAB_WAIT;\ntrap;\nDONE:\n}" ::"r"(bar), "r"(parity) : "memory");
}
__device__ __forceinline__ void bar_sync(int id, int n) { asm volatile("bar.sync %0, %1;" ::"r"(id), "r"(n) : "memory"); }
__device__ __forceinline__ void bar_arrive(int id, int n) { asm volatile("bar.arrive %0, %1;" ::"r"(id), "r"(n) : "memory"); }
__device__ __forceinline__ void wg_fence() { asm volatile("wgmma.fence.sync.aligned;" ::: "memory"); }
__device__ __forceinline__ void wg_commit() { asm volatile("wgmma.commit_group.sync.aligned;" ::: "memory"); }
template <int N> __device__ __forceinline__ void wg_wait() { asm volatile("wgmma.wait_group.sync.aligned %0;" ::"n"(N) : "memory"); }
__device__ __forceinline__ void tma2d(uint32_t dst, const CUtensorMap* tm, uint32_t bar, int c0, int c1) {
  asm volatile("cp.async.bulk.tensor.2d.shared::cluster.global.mbarrier::complete_tx::bytes [%0], [%1,{%3,%4}], [%2];" ::"r"(dst), "l"(tm), "r"(bar), "r"(c0), "r"(c1) : "memory");
}
__device__ __forceinline__ void tma2d_mc(uint32_t dst, const CUtensorMap* tm, uint32_t bar, int c0, int c1) {
  asm volatile("cp.async.bulk.tensor.2d.shared::cluster.global.mbarrier::complete_tx::bytes.multicast::cluster [%0], [%1,{%3,%4}], [%2], %5;" ::"r"(dst), "l"(tm), "r"(bar), "r"(c0), "r"(c1), "h"((uint16_t)3) : "memory");
}
__device__ __forceinline__ void l2_prefetch_line(const void* p) { asm volatile("prefetch.global.L2 [%0];" ::"l"(p)); }
__device__ __forceinline__ uint64_t desc(uint32_t lo, uint32_t hi) { return ((uint64_t)hi << 32) | lo; }
constexpr uint32_t DHI_SW128 = (1024 >> 4) | (1u << 30);
constexpr uint32_t DHI_NONE = (128 >> 4);
constexpr uint32_t DLO_HS = (HS_LBO >> 4) << 16;
constexpr uint32_t DLO_MN = (8192 >> 4) << 16;
constexpr uint32_t DLO_K = 1u << 16;
__device__ __forceinline__ float tanh_fast(float x) { float y; asm("tanh.approx.f32 %0, %1;" : "=f"(y) : "f"(x)); return y; }
__device__ __forceinline__ uint32_t pack_bf16(float lo, float hi) { uint32_t r; asm("cvt.rn.bf16x2.f32 %0, %1, %2;" : "=r"(r) : "f"(hi), "f"(lo)); return r; }
__device__ __forceinline__ float rbf(float x) { return __uint_as_float(pack_bf16(0.f, x)); }
__device__ __forceinline__ void mma16816(float (&c)[4], uint32_t a0, uint32_t a1, uint32_t a2, uint32_t a3, uint32_t b0, uint32_t b1) {
  asm volatile("mma.sync.aligned.m16n8k16.row.col.f32.bf16.bf16.f32 {%0,%1,%2,%3}, {%4,%5,%6,%7}, {%8,%9}, {%0,%1,%2,%3};"
               : "+f"(c[0]), "+f"(c[1]), "+f"(c[2]), "+f"(c[3]) : "r"(a0), "r"(a1), "r"(a2), "r"(a3), "r"(b0), "r"(b1));
}
__device__ __forceinline__ void sts128(uint32_t a, uint32_t x, uint32_t y, uint32_t z, uint32_t w) {
  asm volatile("st.shared.v4.b32 [%0], {%1,%2,%3,%4};" ::"r"(a), "r"(x), "r"(y), "r"(z), "r"(w) : "memory");
}
__device__ __forceinline__ void sts64f(uint32_t a, float x, float y) { asm volatile("st.shared.v2.f32 [%0], {%1,%2};" ::"r"(a), "f"(x), "f"(y) : "memory"); }
__device__ __forceinline__ float2 lds64f(uint32_t a) { float2 v; asm volatile("ld.shared.v2.f32 {%0,%1}, [%2];" : "=f"(v.x), "=f"(v.y) : "r"(a) : "memory"); return v; }
__device__ __forceinline__ uint32_t lds32(uint32_t a) { uint32_t v; asm volatile("ld.shared.b32 %0, [%1];" : "=r"(v) : "r"(a) : "memory"); return v; }
__device__ __forceinline__ void lds128(uint32_t a, uint32_t& x, uint32_t& y, uint32_t& z, uint32_t& w) {
  asm volatile("ld.shared.v4.b32 {%0,%1,%2,%3}, [%4];" : "=r"(x), "=r"(y), "=r"(z), "=r"(w) : "r"(a) : "memory");
}
__device__ __forceinline__ void lds128_inplace(uint32_t a, uint32_t& x, uint32_t& y, uint32_t& z, uint32_t& w) {
  asm volatile("{.reg .pred p; .reg .u32 n; mov.u32 n, %%ntid.y; setp.ne.u32 p, n, 0; @p ld.shared.v4.b32 {%0,%1,%2,%3}, [%4];}" : "+r"(x), "+r"(y), "+r"(z), "+r"(w) : "r"(a) : "memory");
}
__device__ __forceinline__ float bflo(uint32_t v) { return __uint_as_float(v << 16); }
__device__ __forceinline__ float bfhi(uint32_t v) { return __uint_as_float(v & 0xffff0000u); }
template <int N> __device__ __forceinline__ void keep(float (&a)[N]) {
#pragma unroll
  for (int i = 0; i < N; i++) asm volatile("" : "+f"(a[i])::"memory");
}

__global__ void __cluster_dims__(2, 1, 1) __launch_bounds__(384, 1) fused_kernel(const __grid_constant__ Params prm) {
  extern __shared__ __align__(1024) uint8_t smem[];
  const int warp = __shfl_sync(0xffffffffu, threadIdx.x >> 5, 0);
  const uint32_t sb0 = (uint32_t)__cvta_generic_to_shared(smem);
  const int j = blockIdx.x & 7, m = blockIdx.x >> 3, rank = j & 1;
  auto smem_base = [&]() { return __shfl_sync(0xffffffffu, sb0 + (threadIdx.x & 31), 0); };

  if (threadIdx.x == 320) asm volatile("prefetch.tensormap [%0];" ::"l"(&prm.tx) : "memory");
  if (warp == 0) {
    if (elect()) {
#pragma unroll
      for (int i = B_X8; i >= B_X; i--) mbar_init(sb0 + OFF_BAR + 8 * i, 1);
      asm volatile("fence.mbarrier_init.release.cluster;" ::: "memory");
    }
    __syncwarp();
  }
  asm volatile("barrier.cluster.arrive.relaxed.aligned;" ::: "memory");
  if (warp == 0) {
    const uint32_t xb = sb0 + OFF_BAR;
    if (elect()) {
      mbar_expect(xb + 8 * B_X8, 16384);
      tma2d(sb0, &prm.tx, xb + 8 * B_X8, 512, m * 128);
      tma2d(sb0 + 8192, &prm.tx, xb + 8 * B_X8, 512, m * 128 + 64);
#pragma unroll
      for (int i = 0; i < 4; i++) {
        mbar_expect(xb + 8 * (B_X + i), 16384);
        tma2d(sb0 + OFF_H + i * 16384, &prm.tx, xb + 8 * (B_X + i), i * 128, m * 128);
        tma2d(sb0 + OFF_H + i * 16384 + 8192, &prm.tx, xb + 8 * (B_X + i), i * 128 + 64, m * 128);
      }
    }
    __syncwarp();
  }
  asm volatile("barrier.cluster.wait.aligned;" ::: "memory");
  if (warp == 8 || warp == 9) {
    if (elect()) {
      if (warp == 8) {
#pragma unroll
        for (int i = 0; i < B_X; i++) mbar_init(sb0 + OFF_BAR + 8 * i, i >= B_EMPTY ? 2 : 1);
      } else {
#pragma unroll
        for (int i = B_X8 + 1; i < B_COUNT; i++) mbar_init(sb0 + OFF_BAR + 8 * i, (i >= B_SFULL && i < B_SFULL + 2) ? 4 : (i == B_RING || i == B_RING + 1) ? 2 : 1);
        if (sb0 & 1023) __trap();
      }
      asm volatile("fence.mbarrier_init.release.cluster;" ::: "memory");
    }
    __syncwarp();
  }
  if (warp == 0) {
    const uint32_t xb = sb0 + OFF_BAR;
    const bool e = elect();
#pragma unroll
    for (int i = 0; i < 4; i++) {
      const int kb = i * 2 + rank;
      if (e) { mbar_expect(xb + 8 * (B_X + 4 + i), 16384); tma2d_mc(sb0 + OFF_H + 65536 + kb * 8192, &prm.tx, xb + 8 * (B_X + 4 + i), kb * 64, m * 128 + 64); }
    }
    __syncwarp();
  }
  asm volatile("barrier.cluster.arrive.relaxed.aligned;\nbarrier.cluster.wait.aligned;" ::: "memory");

  if (warp >= 8) {
    asm volatile("setmaxnreg.dec.sync.aligned.u32 24;");
    if (warp == 8) {
      const uint32_t sb = smem_base(), bars = sb + OFF_BAR;
      bool e;
      int s = 0, nst = NST + 2; uint32_t ph = 1;
      uint32_t dst, fb;
      auto acquire = [&](uint32_t bytes) {
        mbar_wait(bars + 8 * (B_EMPTY + s), ph);
        fb = bars + 8 * (B_FULL + s); dst = sb + s * SLOT;
        e = elect();
        if (e) mbar_expect(fb, bytes);
        if (++s == nst) { s = 0; ph ^= 1; }
      };
      auto box = [&](const CUtensorMap* t, uint32_t o, int a, int b) { if (e) tma2d(dst + o, t, fb, a, b); };
      auto hs_rem = [&](uint32_t o) {
        if (e) asm volatile("cp.async.bulk.shared::cluster.global.mbarrier::complete_tx::bytes [%0], [%1], %2, [%3];" ::"r"(dst + o),
                            "l"(&g_hs[blockIdx.x][2 * HS_MAIN]), "r"(2 * HS_REM), "r"(fb) : "memory");
      };
      const int lane = threadIdx.x & 31;
      const char* pf = lane < 8 ? (const char*)(lane & 4 ? prm.wu : prm.wg) + ((size_t)(m * 4 + (lane & 3)) * kF + j * 576) * 2
                     : lane < 12 ? (const char*)prm.wd + (size_t)j * 576 * 1152 + (m * 324 + (lane & 3)) * 128
                                 : (const char*)(lane & 1 ? prm.cim : prm.cre) + (size_t)blockIdx.x * 5184;
      int pk = 0, pleft = 81;
      auto prefetch = [&]() {
        if (pleft > 0) {
          if (lane < 14) l2_prefetch_line(pf);
          pf += lane < 8 ? (pk == 8 ? 128 - 8 * 64 * kF * 2 : 64 * kF * 2) : lane < 12 ? 512 : 64;
          pk = pk == 8 ? 0 : pk + 1;
          pleft--;
        }
      };
      mbar_wait(bars + 8 * B_X8, 0);
      e = elect();
#pragma unroll 1
      for (int kb = 0; kb < 8; kb++) {
        fb = bars + 8 * (B_BU + (kb >> 2));
        if (e) { if ((kb & 3) == 0) mbar_expect(fb, 4 * 9216); tma2d(sb + OFF_BU0 + kb * 9216, &prm.tBre, fb, kb * 64, j * 72); }
      }
      bar_sync(NB_XDONE, 160);
      fb = bars + 8 * (B_BU + 2);
      if (e) { mbar_expect(fb, 5 * 9216); tma2d(sb + OFF_BU1, &prm.tBre, fb, 512, j * 72); }
#pragma unroll 1
      for (int kb = 0; kb < 4; kb++) if (e) tma2d(sb + OFF_BU1 + (kb + 1) * 9216, &prm.tBim, fb, kb * 64, j * 72);
#pragma unroll 1
      for (int i = 0; i < PFD / 2; i++) prefetch();
      bar_sync(NB_XDONE + 1, 160);
      fb = bars + 8 * (B_BU + 3);
      if (e) mbar_expect(fb, 5 * 9216);
#pragma unroll 1
      for (int kb = 4; kb < 9; kb++) if (e) tma2d(sb + OFF_BU2 + (kb - 4) * 9216, &prm.tBim, fb, kb * 64, j * 72);
#pragma unroll 1
      for (int i = PFD / 2; i < PFD; i++) prefetch();
      mbar_wait(bars + 8 * B_RING, 0);
#pragma unroll 1
      for (int c = 0; c < 9; c++) {
        const int col = j * 576 + c * 64;
#pragma unroll 1
        for (int kb = 0; kb < 9; kb++) {
          if (kb == 6 && c == 0) mbar_wait(bars + 8 * (B_RING + 1), 0);
          if (kb == 6 && c == 3) nst = 7;
          if (kb == 5 && c == 7) nst = 6;
          acquire(16384); box(&prm.tWg, 0, col, kb * 64); box(&prm.tWu, 8192, col, kb * 64); prefetch();
        }
      }
      auto half_tile = [&](int n0) {
#pragma unroll 1
        for (int kp = 0; kp < 4; kp++) { acquire(16384); box(&prm.tWd, 0, n0, j * 576 + kp * 128); box(&prm.tWd, 8192, n0, j * 576 + kp * 128 + 64); }
        acquire(8192 + 2048 + 2 * HS_REM); box(&prm.tWd, 0, n0, j * 576 + 512); box(&prm.tCre8, 8192, j * 72 + 64, n0); box(&prm.tCim8, 9216, j * 72 + 64, n0); hs_rem(10240);
        acquire(16384); box(&prm.tCre, 0, j * 72, n0); box(&prm.tCim, 8192, j * 72, n0);
      };
      mbar_wait(bars + 8 * B_PARK, 0);
      asm volatile("fence.proxy.async.global;" ::: "memory");
      if (rank) half_tile(512);
#pragma unroll 1
      for (int t = 0; t < 4 - rank; t++) {
        const int n0 = ((rank ^ t ^ 1) & 1) * 256 + (((t >> 1) ^ (j >> 1)) & 1) * 128;
#pragma unroll 1
        for (int kb = 0; kb < 9; kb++) {
          if (rank ? (t == 0 && kb == 5) : (t == 1 && kb == 1)) nst = NST + 1;
          if (t == 1 && kb == (rank ? 1 : 7)) nst = NST + 2;
          if (kb == 3 && t == 0 && rank) mbar_wait(bars + 8 * B_HFREE, 0);
          acquire(16384); box(&prm.tWd, 0, n0, j * 576 + kb * 64); box(&prm.tWd, 8192, n0 + 64, j * 576 + kb * 64);
        }
        if (t == 0) mbar_wait(bars + 8 * B_HFREE, 0);
        acquire(16384); box(&prm.tCre, 0, j * 72, n0); box(&prm.tCre, 8192, j * 72, n0 + 64);
        acquire(16384); box(&prm.tCim, 0, j * 72, n0); box(&prm.tCim, 8192, j * 72, n0 + 64);
        acquire(4096 + 2 * HS_REM); hs_rem(4096);
        box(&prm.tCre8, 0, j * 72 + 64, n0); box(&prm.tCre8, 1024, j * 72 + 64, n0 + 64);
        box(&prm.tCim8, 2048, j * 72 + 64, n0); box(&prm.tCim8, 3072, j * 72 + 64, n0 + 64);
      }
      if (!rank) half_tile(512);
      else {
#pragma unroll 1
        for (int hh = 0; hh < 2; hh++) half_tile(256 + (((j >> 1) ^ 1) & 1) * 128 + hh * 64);
      }
    } else {
      const uint32_t sb = smem_base(), bars = sb + OFF_BAR;
      const int p = min((int)threadIdx.x - 288, 71);
      if (threadIdx.x < 288 + 10) asm volatile("prefetch.tensormap [%0];" ::"l"(&prm.tBre + (threadIdx.x - 288)) : "memory");
      if (warp == 10) {
        const int l = threadIdx.x & 31;
        const char* q = (const char*)(l & 1 ? prm.bim : prm.bre) + (size_t)blockIdx.x * 5184;
        mbar_wait(bars + 8 * B_X8, 0);
#pragma unroll
        for (int i = 0; i < 3; i++) if (i * 16 + (l >> 1) < 42) l2_prefetch_line(q + min((i * 16 + (l >> 1)) * 128, 5183));
      }
      const unsigned epoch = *(volatile unsigned*)&g_epoch[blockIdx.x];
      {
        const int pg = j * 72 + p;
        const float lr = __bfloat162float(prm.lre[pg]), li = __bfloat162float(prm.lim[pg]);
        const float dt = rbf(expf(__bfloat162float(prm.ldt[pg])));
        const float ea = expf(dt * lr);
        float sn, cs;
        sincosf(dt * li, &sn, &cs);
        const float ar = ea * cs, ai = ea * sn;
        float br = ar, bi = ai;
#pragma unroll
        for (int k = 0; k < 6; k++) { const float t = br * br - bi * bi; bi = 2.f * br * bi; br = t; }
        const float nr = ar - 1.f, den = 4.f / (lr * lr + li * li);
        sts64f(sb + OFF_CONST + p * 8, ar, ai);
        sts64f(sb + OFF_CONST + 576 + p * 8, br, bi);
        sts64f(sb + OFF_CONST + 1152 + p * 8, (nr * lr + ai * li) * den, (ai * lr - nr * li) * den);
      }
      bar_sync(NB_DUMP, 352);
      {
        const int lane = threadIdx.x & 31;
        const int half = warp == 11 ? (lane >> 2) & 1 : warp - 9;
        const uint32_t cu = sb + OFF_CONST + (warp == 11 ? 32 + (lane & 3) : lane) * 16;
        uint32_t a0 = sb + OFF_DUMP + half * HS_BYTES + (warp == 11 ? 16 : lane >> 2) * HS_LBO + (lane & 3) * 4;
        asm volatile("" : "+r"(a0));
        const uint32_t di = warp == 11 ? HS_LBO : 8 * HS_LBO;
        float a[4], h[4] = {0.f, 0.f, 0.f, 0.f};
        auto ld4 = [&](uint32_t ad, float (&v)[4]) { asm volatile("ld.shared.v4.f32 {%0,%1,%2,%3}, [%4];" : "=f"(v[0]), "=f"(v[1]), "=f"(v[2]), "=f"(v[3]) : "r"(ad) : "memory"); };
        auto cfma = [&](const float (&c)[4], float r0, float i0, float r1, float i1) {
          const float n0 = fmaf(c[0], h[0], fmaf(-c[1], h[1], r0)), n1 = fmaf(c[2], h[2], fmaf(-c[3], h[3], r1));
          h[1] = fmaf(c[0], h[1], fmaf(c[1], h[0], i0)); h[3] = fmaf(c[2], h[3], fmaf(c[3], h[2], i1));
          h[0] = n0; h[2] = n1;
        };
        ld4(cu, a);
#pragma unroll 1
        for (uint32_t ad = a0; ad != a0 + 1024; ad += 64) {
          uint32_t wr[4], wi[4];
#pragma unroll
          for (int k = 0; k < 4; k++) { wr[k] = lds32(ad + k * 16); wi[k] = lds32(ad + di + k * 16); }
#pragma unroll
          for (int k = 0; k < 4; k++) cfma(a, bflo(wr[k]), bflo(wi[k]), bfhi(wr[k]), bfhi(wi[k]));
        }
        if (half == 0) sts128(cu + 1728, __float_as_uint(h[0]), __float_as_uint(h[1]), __float_as_uint(h[2]), __float_as_uint(h[3]));
        bar_sync(NB_SCAN, 96);
        if (half == 1 && m < 15) {
          float b[4], s1[4] = {h[0], h[1], h[2], h[3]};
          ld4(cu + 576, b); ld4(cu + 1728, h);
          cfma(b, s1[0], s1[1], s1[2], s1[3]);
          uint2* gp = &g_S[epoch & 1][m][j][(cu - sb - OFF_CONST) >> 3];
          asm volatile("st.relaxed.gpu.global.v2.b64 [%0], {%1,%2};" ::"l"(gp), "l"(~(((uint64_t)__float_as_uint(h[1]) << 32) | __float_as_uint(h[0]))),
                       "l"(~(((uint64_t)__float_as_uint(h[3]) << 32) | __float_as_uint(h[2]))) : "memory");
        }
        __syncwarp();
        g_S[(epoch & 1) ^ 1][m][j][p] = make_uint2(0u, 0u);
        {
          const float2 b = lds64f(sb + OFF_CONST + 576 + p * 8);
          const float br = b.x * b.x - b.y * b.y, bi = 2.f * b.x * b.y;
          float hr = 0.f, hi = 0.f;
          const uint2* sp = &g_S[epoch & 1][0][j][p];
#pragma unroll 1
          for (int left = m; left > 0; left -= 3, sp += 3 * 768) {
            uint32_t v[3][2];
            int spins = 0;
            uint32_t ok;
            do {
#pragma unroll
              for (int k = 0; k < 3; k++) {
                v[k][0] = v[k][1] = 0xffffffffu;
                if (k < left) asm volatile("ld.relaxed.gpu.global.v2.b32 {%0,%1}, [%2];" : "=r"(v[k][0]), "=r"(v[k][1]) : "l"(sp + k * 768) : "memory");
              }
              ok = min(min(min(v[0][0], v[0][1]), min(v[1][0], v[1][1])), min(v[2][0], v[2][1]));
              if (++spins > (1 << 22)) __trap();
            } while (ok == 0u);
#pragma unroll
            for (int k = 0; k < 3; k++)
              if (k < left) { const float nr = fmaf(br, hr, fmaf(-bi, hi, __uint_as_float(~v[k][0]))); hi = fmaf(br, hi, fmaf(bi, hr, __uint_as_float(~v[k][1]))); hr = nr; }
          }
          sts64f(sb + OFF_CONST + p * 8, hr, hi);
        }
        __syncwarp();
        bar_sync(NB_SCAN, 96);
        ld4(cu, h);
        uint32_t cr, ci, cn;
        {
          float b[4], s0[4];
          ld4(cu + 576, b); ld4(cu + 1728, s0);
          if (half == 1) cfma(b, s0[0], s0[1], s0[2], s0[3]);
          ld4(cu + 1152, b);
          cr = pack_bf16(b[0], b[2]); ci = pack_bf16(b[1], b[3]); cn = ci ^ 0x80008000u;
        }
        h[1] = -h[1]; h[3] = -h[3];
        __syncwarp();
#pragma unroll 1
        for (uint32_t ad = a0; ad != a0 + 1024; ad += 32) {
          uint32_t wr[2], wi[2];
#pragma unroll
          for (int k = 0; k < 2; k++) { wr[k] = lds32(ad + k * 16); wi[k] = lds32(ad + di + k * 16); }
#pragma unroll
          for (int k = 0; k < 2; k++) {
            const float n0 = fmaf(a[0], h[0], fmaf(a[1], h[1], bflo(wr[k]))), n1 = fmaf(a[2], h[2], fmaf(a[3], h[3], bfhi(wr[k])));
            h[1] = fmaf(a[0], h[1], fmaf(-a[1], h[0], -bflo(wi[k]))); h[3] = fmaf(a[2], h[3], fmaf(-a[3], h[2], -bfhi(wi[k])));
            h[0] = n0; h[2] = n1;
            const uint32_t hr = pack_bf16(h[0], h[2]), hn = pack_bf16(h[1], h[3]);
            uint32_t o0, o1;
            asm("{.reg .b32 t; mul.rn.bf16x2 t, %2, %4; fma.rn.bf16x2 %0, %1, %3, t;}" : "=r"(o0) : "r"(hr), "r"(hn), "r"(cr), "r"(ci));
            asm("{.reg .b32 t; mul.rn.bf16x2 t, %1, %4; fma.rn.bf16x2 %0, %2, %3, t;}" : "=r"(o1) : "r"(hr), "r"(hn), "r"(cr), "r"(cn));
            asm volatile("st.shared.b32 [%0], %1;" ::"r"(ad + k * 16), "r"(o0) : "memory");
            asm volatile("st.shared.b32 [%0], %1;" ::"r"(ad + di + k * 16), "r"(o1) : "memory");
          }
        }
        asm volatile("fence.proxy.async.shared::cta;" ::: "memory");
      }
      bar_sync(NB_SCAN, 96);
      const bool lead = elect();
      if (warp == 9) {
        if (lead) {
#pragma unroll 1
          for (int i = 0; i < 10; i++) {
            const int pc = (0x8654321970ull >> (4 * i)) & 15, w = pc & 1, c4 = pc >> 1;
            asm volatile("cp.async.bulk.global.shared::cta.bulk_group [%0], [%1], %2;" ::"l"(&g_hs[blockIdx.x][c4 < 4 ? w * HS_MAIN + c4 * 4 * HS_LBO : 2 * HS_MAIN + w * HS_REM]),
                         "r"(sb + OFF_DUMP + w * HS_BYTES + c4 * 4 * HS_LBO), "r"(c4 < 4 ? 4 * HS_LBO : HS_REM) : "memory");
            asm volatile("cp.async.bulk.commit_group;\ncp.async.bulk.wait_group.read 0;" ::: "memory");
            if (i == 2) mbar_arrive(bars + 8 * B_SCAN);
          }
          mbar_arrive(bars + 8 * (B_SCAN + 1));
        }
        __syncwarp();
      }
      if (warp == 9) {
        if (lead) {
          __threadfence();
          asm volatile("red.release.gpu.global.add.u32 [%0], 1;" ::"l"(&g_ready[m]) : "memory");
          g_epoch[blockIdx.x] = epoch + 1u;
          asm volatile("cp.async.bulk.wait_group 0;" ::: "memory");
          mbar_arrive(bars + 8 * B_PARK);
        }
        __syncwarp();
        bar_sync(NB_HFREE, 288);
        if (lead) {
          mbar_arrive(bars + 8 * B_HFREE);
          mbar_expect(bars + 8 * B_HSFULL, 2 * HS_MAIN);
          asm volatile("cp.async.bulk.shared::cluster.global.mbarrier::complete_tx::bytes [%0], [%1], %2, [%3];" ::"r"(sb + OFF_HS),
                       "l"(&g_hs[blockIdx.x][0]), "r"(2 * HS_MAIN), "r"(bars + 8 * B_HSFULL) : "memory");
          for (int w = 0; w < 2; w++) mbar_arrive_cta(bars + 8 * (B_RFREE + w), rank ^ 1);
        }
        __syncwarp();
      } else {
        const int w = warp - 10;
        {
          const unsigned target = 8u * (epoch + 1u);
          int spins = 0;
          unsigned v;
          do {
            if (spins) __nanosleep(500);
            asm volatile("ld.relaxed.gpu.global.u32 %0, [%1];" : "=r"(v) : "l"(&g_ready[m]) : "memory");
            if (++spins > (1 << 21)) __trap();
          } while ((int)(v - target) < 0);
          asm volatile("fence.acq_rel.gpu;" ::: "memory");
          asm volatile("fence.proxy.async.global;" ::: "memory");
        }
        const uint32_t stg = sb + OFF_STG + w * 32768;
        const int nu = 5 + rank;
#pragma unroll 1
        for (int u = 0; u < nu; u++) {
          const int t = u - rank;
          if (t == 0 || t == 2) {
            if (elect()) mbar_expect(bars + 8 * (B_RFULL + w), 16384);
            mbar_wait(bars + 8 * (B_SFULL + w), u & 1);
            mbar_wait(bars + 8 * (B_RFREE + w), t >> 1);
            if (elect())
              asm volatile("{.reg .b32 ra, rb; mapa.shared::cluster.u32 ra, %0, %3; mapa.shared::cluster.u32 rb, %2, %3;\n"
                           "cp.async.bulk.shared::cluster.shared::cta.mbarrier::complete_tx::bytes [ra], [%1], 16384, [rb];}" ::"r"(stg + 16384),
                           "r"(stg), "r"(bars + 8 * (B_RFULL + w)), "r"(rank ^ 1) : "memory");
            mbar_wait(bars + 8 * (B_RFULL + w), t >> 1);
            if (elect()) mbar_arrive_cta(bars + 8 * (B_SFREE + w), rank ^ 1);
          } else {
            mbar_wait(bars + 8 * (B_SFULL + w), u & 1);
            const bool d = u == (rank ? 0 : 4), hf = rank && u >= 4;
            const int n0 = d ? 512 : rank * 256 + (((min(t, 3) >> 1) ^ (j >> 1)) & 1) * 128 + (u == 5 ? 64 : 0);
            const uint32_t src = d && !rank ? sb + w * SLOT : stg + (u == 5 ? 16384 : 0);
            if (elect()) {
#pragma unroll 1
              for (int b = 0; b < (d || hf ? 2 : 4); b++) {
                asm volatile("cp.reduce.async.bulk.tensor.4d.global.shared::cta.add.tile.bulk_group [%0, {%1,%2,%2,%3}], [%4];" ::"l"(&prm.tOut), "r"(n0 + b * 32), "r"(0),
                             "r"(m * 16 + w * 8), "r"(src + b * 8192) : "memory");
                asm volatile("cp.async.bulk.commit_group;" ::: "memory");
                if (u < nu - 1) asm volatile("cp.async.bulk.wait_group.read 0;" ::: "memory");
              }
              if (u < 3) {
                asm volatile("cp.async.bulk.wait_group.read 0;" ::: "memory");
                mbar_arrive(bars + 8 * (B_SFREE + w));
                if (t == 1) mbar_arrive_cta(bars + 8 * (B_RFREE + w), rank ^ 1);
              }
              if (u == nu - 1) asm volatile("cp.async.bulk.wait_group.read 0;" ::: "memory");
            }
          }
          __syncwarp();
        }
      }
    }
  } else {
    asm volatile("setmaxnreg.inc.sync.aligned.u32 240;");
    const uint32_t sb = smem_base(), bars = sb + OFF_BAR;
    const int wg = warp >> 2, w4 = warp & 3;
    const int lane = threadIdx.x & 31, g = lane >> 2, q = lane & 3;
    const uint32_t hw = sb + OFF_H + wg * 65536;

    int s = 0, nst = NST + 2; uint32_t ph = 0;
    auto release = [&](int st) { if (w4 == 0) { if (elect()) mbar_arrive(bars + 8 * (B_EMPTY + st)); } };
    const uint32_t dring = (sb & 0x3FFFF) >> 4;
    uint32_t dlo; int prev = 0;
    auto stage_begin = [&]() { mbar_wait(bars + 8 * (B_FULL + s), ph); dlo = dring + s * (SLOT >> 4); wg_fence(); };
    auto advance = [&]() { if (++s == nst) { s = 0; ph ^= 1; } };
    auto stage_end = [&](bool rel) {
      wg_commit();
      if (rel) { wg_wait<1>(); release(prev); }
      prev = s;
      advance();
    };

    uint32_t xa[144];
    uint32_t xr[18], dk[9];
    uint32_t rh[2], cc[2];
#pragma unroll
    for (int i = 0; i < 9; i++) dk[i] = __ldg((const uint32_t*)(prm.dskip + j * 72 + i * 8 + q * 2));
    {
      const int r = w4 * 16 + (lane & 7) + ((lane >> 3) & 1) * 8;
      const uint32_t ro = r * 128, cx = ((lane >> 4) ^ (lane & 7)) << 4;
      float s1[2][4] = {};
      auto load = [&](int kb, uint32_t base) {
#pragma unroll
        for (int kk = 0; kk < 4; kk++) {
          const int i = (kb * 4 + kk) * 4;
          asm volatile("ldmatrix.sync.aligned.m8n8.x4.shared.b16 {%0,%1,%2,%3}, [%4];"
                       : "=r"(xa[i]), "=r"(xa[i + 1]), "=r"(xa[i + 2]), "=r"(xa[i + 3]) : "r"(base + ro + (cx ^ (kk << 5))) : "memory");
        }
      };
      float s2[4] = {}, s3[4] = {};
      auto sums = [&](int kb) {
#pragma unroll
        for (int kk = 0; kk < 4; kk += 2) {
          const int i = (kb * 4 + kk) * 4;
          uint32_t a[8];
#pragma unroll
          for (int e = 0; e < 8; e++) asm("mul.rn.bf16x2 %0, %1, %1;" : "=r"(a[e]) : "r"(xa[i + e]));
          mma16816(s3, a[4], a[5], a[6], a[7], 0x3f803f80u, 0x3f803f80u);
          mma16816(s1[0], xa[i], xa[i + 1], xa[i + 2], xa[i + 3], 0x3f803f80u, 0x3f803f80u);
          mma16816(s2, a[0], a[1], a[2], a[3], 0x3f803f80u, 0x3f803f80u);
          mma16816(s1[1], xa[i + 4], xa[i + 5], xa[i + 6], xa[i + 7], 0x3f803f80u, 0x3f803f80u);
        }
      };
#pragma unroll
      for (int i = 0; i < 9; i++) {
        const int c8 = j * 9 + i, kb = c8 >> 3;
        xr[2 * i] = (kb < 8 ? hw + kb * 8192 : sb + wg * 8192) + (w4 * 16 + g) * 128 + (((c8 & 7) ^ g) << 4) + q * 4;
        asm volatile("" : "+r"(xr[2 * i]));
      }
      mbar_wait(bars + 8 * B_X8, 0);
      load(8, sb + wg * 8192);
      auto pin = [&]() { asm volatile("{.reg .pred p; .reg .u32 c, z; mov.u32 c, %clock; mov.u32 z, %ntid.y; setp.eq.u32 p, z, 0; @p st.shared.u32 [c], c;}" ::: "memory"); };
#pragma unroll
      for (int kp = 0; kp < 4; kp++) {
        mbar_wait(bars + 8 * (B_X + wg * 4 + kp), 0);
        load(2 * kp, hw + 2 * kp * 8192);
        load(2 * kp + 1, hw + (2 * kp + 1) * 8192);
        if (kp == 3) {
#pragma unroll
          for (int i = 0; i < 9; i++) { xr[2 * i + 1] = lds32(xr[2 * i] + 1024); xr[2 * i] = lds32(xr[2 * i]); }
        }
        if (kp == 0) sums(8); else { sums(2 * kp - 2); sums(2 * kp - 1); }
      }
      asm volatile("fence.proxy.async.shared::cta;" ::: "memory");
      bar_arrive(NB_XDONE + wg, 160);
      if (wg == 1) bar_arrive(NB_STATS, 256);
      pin();
      sums(6);
      sums(7);
      pin();
#pragma unroll
      for (int e = 0; e < 2; e++) {
        const float mu = (s1[0][2 * e + 1] + s1[1][2 * e + 1]) * (1.f / kD);
        const float var = fmaxf(fmaf(-mu, mu, (s2[2 * e] + s3[2 * e]) * (1.f / kD)), 0.f);
        float sd, r;
        asm("sqrt.approx.ftz.f32 %0, %1;" : "=f"(sd) : "f"(rbf(rbf(var) + 1e-5f)));
        asm("rcp.approx.ftz.f32 %0, %1;" : "=f"(r) : "f"(rbf(sd)));
        rh[e] = pack_bf16(0.5f * r, 0.5f * r);
        cc[e] = pack_bf16(mu, mu);
      }
    }

    auto normalise = [&](int kb) {
#pragma unroll
      for (int i = 0; i < 16; i++) asm("{.reg .b32 d; sub.rn.bf16x2 d, %0, %2; mul.rn.bf16x2 %0, d, %1;}" : "+r"(xa[16 * kb + (i >> 3) + 2 * (i & 7)]) : "r"(rh[i >> 3]), "r"(cc[i >> 3]));
    };
    {
      float ab[36];
      float* op = prm.out + (size_t)(m * 128 + wg * 64 + w4 * 16 + g) * kD + j * 72 + q * 2;
      auto residual = [&](int i) {
        asm volatile("add.rn.bf16x2 %0, %0, %0;" : "+r"(dk[i]));
#pragma unroll
        for (int e = 0; e < 2; e++) {
          uint32_t t;
          asm("{.reg .b32 d; sub.rn.bf16x2 d, %1, %3; mul.rn.bf16x2 %0, d, %2;}" : "=r"(t) : "r"(xr[2 * i + e]), "r"(rh[e]), "r"(cc[e]));
          asm("fma.rn.bf16x2 %0, %0, %1, %2;" : "+r"(t) : "r"(dk[i]), "r"(xr[2 * i + e]));
          *(float2*)(op + e * 8 * kD + i * 8) = make_float2(bflo(t), bfhi(t));
        }
      };
      const uint32_t da = sb + OFF_DUMP + wg * HS_BYTES + (w4 * 16 + g) * 16 + q * 4;
      auto dump = [&](int im) {
#pragma unroll
        for (int i = 0; i < 18; i++)
          asm volatile("st.shared.b32 [%0], %1;" ::"r"(da + (i < 16 ? 8 * im + (i >> 1) : 16 + im) * HS_LBO + (i & 1) * 128), "r"(pack_bf16(ab[2 * i], ab[2 * i + 1])) : "memory");
      };
      auto bu = [&](int kb, uint32_t off) {
        wg_fence();
#pragma unroll
        for (int kk = 0; kk < 4; kk++) { const int i = (kb * 4 + kk) * 4; wgmma_n72_rs_tb0(ab, xa[i], xa[i + 1], xa[i + 2], xa[i + 3], desc((dring + (off >> 4) + kk * 2) + DLO_K, DHI_SW128), (kb | kk) != 0); }
        wg_commit();
      };
      normalise(0);
      if (wg == 0) {
#pragma unroll
        for (int kb = 1; kb < 9; kb++) normalise(kb);
        bar_sync(NB_STATS, 256);
      }
#pragma unroll
      for (int kb = 0; kb < 9; kb++) {
        if ((kb & 3) == 0) mbar_wait(bars + 8 * (B_BU + (kb >> 2)), 0);
        bu(kb, kb < 8 ? OFF_BU0 + kb * 9216 : OFF_BU1);
        if (wg == 0) residual(kb);
        else if (kb < 8) normalise(kb + 1);
      }
      wg_wait<0>();
      if (w4 == 0) { if (elect()) mbar_arrive(bars + 8 * B_RING); }
      keep(ab);
      dump(0);
#pragma unroll
      for (int kb = 0; kb < 9; kb++) {
        if (kb == 4) mbar_wait(bars + 8 * (B_BU + 3), 0);
        bu(kb, kb < 4 ? OFF_BU1 + (kb + 1) * 9216 : OFF_BU2 + (kb - 4) * 9216);
        if (wg == 1) residual(kb);
        if (kb == 5) { wg_wait<2>(); if (w4 == 0) { if (elect()) mbar_arrive(bars + 8 * (B_RING + 1)); } }
      }
      wg_wait<0>();
      keep(ab);
      dump(1);
      bar_arrive(NB_DUMP, 352);
    }

    float acc[64];
    {
      const uint32_t ha = sb + OFF_H + (threadIdx.x & 127) * 16, hblk = wg ? HBLK1 : HBLK0;
      auto glu = [&](int i) {
        return pack_bf16(fmaf(acc[32 + 2 * i], tanh_fast(acc[2 * i]), acc[32 + 2 * i]), fmaf(acc[33 + 2 * i], tanh_fast(acc[2 * i + 1]), acc[33 + 2 * i]));
      };
      for (int c = 0; c < 8; c++) {
        if (wg == 1) bar_sync(NB_SKEW, 256);
#pragma unroll
        for (int kb = 0; kb < 9; kb++) {
          if (kb == 6 && c == 3) nst = 7;
          if (kb == 5 && c == 7) nst = 6;
          stage_begin();
#pragma unroll
          for (int kk = 0; kk < 4; kk++) { const int i = (kb * 4 + kk) * 4; wgmma_n128_rs_tb1(acc, xa[i], xa[i + 1], xa[i + 2], xa[i + 3], desc((dlo + kk * 128) + DLO_MN, DHI_SW128), (kb | kk) != 0); }
          if (kb == SKEW - 1 && wg == 0) bar_arrive(NB_SKEW, 256);
          if (kb == 8 && c >= 3 && c != 6) mbar_wait(bars + 8 * (c == 3 ? B_EMPTY + 7 : c == 7 ? B_EMPTY + 6 : B_SCAN - 4 + c), c == 3);
          stage_end(kb > 0);
        }
        wg_wait<0>();
        release(prev);
        keep(acc);
        const uint32_t hc = ha + ((hblk >> (4 * c)) & 15) * 8192;
#pragma unroll
        for (int i = 0; i < 4; i++) sts128(hc + i * 2048, glu(4 * i), glu(4 * i + 1), glu(4 * i + 2), glu(4 * i + 3));
      }
      if (wg == 1) bar_sync(NB_SKEW, 256);
#pragma unroll
      for (int kb = 0; kb < 9; kb++) {
        stage_begin();
#pragma unroll
        for (int kk = 0; kk < 4; kk++) { const int i = (kb * 4 + kk) * 4; wgmma_n128_rs_tb1(acc, xa[i], xa[i + 1], xa[i + 2], xa[i + 3], desc((dlo + kk * 128) + DLO_MN, DHI_SW128), (kb | kk) != 0); }
        if (kb == SKEW - 1 && wg == 0) bar_arrive(NB_SKEW, 256);
        stage_end(kb > 0);
        if (kb > 0) {
          const uint32_t hc = ha + ((hblk >> (4 * (kb - 1))) & 15) * 8192;
#pragma unroll
          for (int i = 4 * (kb - 1); i < 4 * kb; i++) lds128_inplace(hc + (i & 3) * 2048, xa[4 * i], xa[4 * i + 1], xa[4 * i + 2], xa[4 * i + 3]);
        }
      }
      asm volatile("fence.proxy.async.shared::cta;" ::: "memory");
      bar_arrive(NB_HFREE, 288);
      wg_wait<0>();
      release(prev);
      keep(acc);
#pragma unroll
      for (int i = 0; i < 16; i++) xa[128 + i] = glu(i);
    }

    const uint32_t dhs = (((sb + OFF_HS + wg * HS_MAIN) & 0x3FFFF) >> 4) | DLO_HS, drem = DLO_HS + wg * (HS_REM >> 4);
    const int rp = (g >> 2) + 2 * (g & 3);
    const uint32_t so = w4 * 2048 + rp * 128 + (q & 1) * 8, sx = ((q >> 1) ^ rp) << 4;
    const uint32_t rcv = sb + OFF_STG + wg * 32768 + 16384 + w4 * 2048 + lane * 16;
    auto staged = [&]() {
      asm volatile("fence.proxy.async.shared::cta;" ::: "memory");
      __syncwarp();
      if (elect()) mbar_arrive(bars + 8 * (B_SFULL + wg));
    };
    auto half_tile = [&](const bool first, const int kind) {
      float a2[32];
      if (wg == 1) { if (!first) staged(); bar_sync(NB_SKEW, 256); }
      const uint32_t ph0 = ph;
      uint32_t d4;
#pragma unroll
      for (int kp = 0; kp < 5; kp++) {
        stage_begin();
#pragma unroll
        for (int kk = 0; kk < (kp < 4 ? 8 : 4); kk++) { const int i = (kp * 8 + kk) * 4; wgmma_n64_rs_tb1(a2, xa[i], xa[i + 1], xa[i + 2], xa[i + 3], desc((dlo + kk * 128) + DLO_MN, DHI_SW128), (kp | kk) != 0); }
        if (kp == 2 && wg == 0) bar_arrive(NB_SKEW, 256);
        d4 = dlo;
        stage_end(kp > 0);
        if (kp == 0 && !first && wg == 0) staged();
      }
      if (first) mbar_wait(bars + 8 * B_HSFULL, 0);
      stage_begin();
#pragma unroll
      for (int kk = 0; kk < 8; kk++) wgmma_n64_ss_tb0(a2, desc(dhs + kk * (2 * HS_LBO >> 4), DHI_NONE), desc((dlo + (kk >> 2) * 512 + (kk & 3) * 2) + DLO_K, DHI_SW128), 1);
      wgmma_n64_ss_tb0(a2, desc(d4 + 640 + drem, DHI_NONE), desc((d4 + 512) | ((1024 >> 4) << 16), DHI_NONE), 1);
      wg_commit();
      if (!first) {
        if (kind == 1) mbar_wait(bars + 8 * (B_EMPTY + wg), ph0 ^ 1);
        if (kind == 2) { mbar_wait(bars + 8 * (B_SFREE + wg), 1); mbar_wait(bars + 8 * (B_RFULL + wg), 1); }
      }
      wg_wait<0>();
      release(prev); release(s); advance();
      keep(a2);
      if (!first && kind >= 2) {
#pragma unroll
        for (int i = 0; i < 4; i++) {
          uint32_t v[4];
          lds128(rcv + (kind & 1) * 8192 + i * 512, v[0], v[1], v[2], v[3]);
#pragma unroll
          for (int e = 0; e < 4; e++) { a2[8 * i + 2 * e] += bflo(v[e]); a2[8 * i + 2 * e + 1] += bfhi(v[e]); }
        }
        __syncwarp();
      }
      const uint32_t stg = (!first && kind == 1 ? sb + wg * SLOT : sb + OFF_STG + wg * 32768 + (kind == 3 ? 16384 : 0)) + so;
#pragma unroll
      for (int i = 0; i < 8; i++) {
        const uint32_t a = stg + (i >> 2) * 8192 + (sx ^ ((i & 3) << 5));
        sts64f(a, a2[4 * i], a2[4 * i + 1]);
        sts64f(a + 1024, a2[4 * i + 2], a2[4 * i + 3]);
      }
    };
    if (rank) half_tile(true, 0);
    for (int t = 0; t < 4 - rank; t++) {
      if (wg == 1) { if (t + rank > 0) staged(); bar_sync(NB_SKEW, 256); }
#pragma unroll
      for (int kb = 0; kb < 9; kb++) {
        if ((kb == 5 && t == 0 && rank) || (kb == 1 && t == 1)) nst = NST + 1;
        if (t == 1 && ((kb == 1 && rank) || kb == 7)) nst = NST + 2;
        stage_begin();
#pragma unroll
        for (int kk = 0; kk < 4; kk++) { const int i = (kb * 4 + kk) * 4; wgmma_n128_rs_tb1(acc, xa[i], xa[i + 1], xa[i + 2], xa[i + 3], desc((dlo + kk * 128) + DLO_MN, DHI_SW128), (kb | kk) != 0); }
        if (kb == SKEW - 1 && wg == 0) bar_arrive(NB_SKEW, 256);
        stage_end(kb > 0);
        if (kb == 3 && t + rank > 0 && wg == 0) staged();
      }
      if (t == 0) mbar_wait(bars + 8 * B_HSFULL, 0);
      stage_begin();
#pragma unroll
      for (int kk = 0; kk < 4; kk++) wgmma_n128_ss_tb0(acc, desc(dhs + kk * (2 * HS_LBO >> 4), DHI_NONE), desc((dlo + kk * 2) + DLO_K, DHI_SW128), 1);
      stage_end(true);
      stage_begin();
#pragma unroll
      for (int kk = 0; kk < 4; kk++) wgmma_n128_ss_tb0(acc, desc(dhs + (4 + kk) * (2 * HS_LBO >> 4), DHI_NONE), desc((dlo + kk * 2) + DLO_K, DHI_SW128), 1);
      const int s_im = s;
      advance();
      stage_begin();
      wgmma_n128_ss_tb0(acc, desc(dlo + 256 + drem, DHI_NONE), desc(dlo | ((2048 >> 4) << 16), DHI_NONE), 1);
      stage_end(true);
      if (t + rank > 0) mbar_wait(bars + 8 * (B_SFREE + wg), (t + rank - 1) & 1);
      if (t & 1) mbar_wait(bars + 8 * (B_RFULL + wg), t >> 1);
      wg_wait<0>();
      release(s_im); release(prev);
      keep(acc);
      if (t & 1) {
        const uint32_t stg = sb + OFF_STG + wg * 32768 + so;
#pragma unroll
        for (int hh = 0; hh < 2; hh++) {
#pragma unroll
          for (int i = 4 * hh; i < 4 * hh + 4; i++) {
            uint32_t v[4];
            lds128(rcv + hh * 8192 + (i & 3) * 512, v[0], v[1], v[2], v[3]);
#pragma unroll
            for (int e = 0; e < 4; e++) { acc[8 * i + 2 * e] += bflo(v[e]); acc[8 * i + 2 * e + 1] += bfhi(v[e]); }
          }
          __syncwarp();
#pragma unroll
          for (int i = 8 * hh; i < 8 * hh + 8; i++) {
            const uint32_t a = stg + (i >> 2) * 8192 + (sx ^ ((i & 3) << 5));
            sts64f(a, acc[4 * i], acc[4 * i + 1]);
            sts64f(a + 1024, acc[4 * i + 2], acc[4 * i + 3]);
          }
        }
      } else {
#pragma unroll
        for (int i = 0; i < 8; i++)
          sts128(rcv - 16384 + (i >> 2) * 8192 + (i & 3) * 512, pack_bf16(acc[8 * i], acc[8 * i + 1]), pack_bf16(acc[8 * i + 2], acc[8 * i + 3]),
                 pack_bf16(acc[8 * i + 4], acc[8 * i + 5]), pack_bf16(acc[8 * i + 6], acc[8 * i + 7]));
      }
    }
#pragma unroll 1
    for (int kind = 1 + rank; kind < 2 + 2 * rank; kind++) half_tile(false, kind);
    staged();
  }
}

typedef CUresult (*EncodeFn)(CUtensorMap*, CUtensorMapDataType, cuuint32_t, void*, const cuuint64_t*, const cuuint64_t*, const cuuint32_t*,
                             const cuuint32_t*, CUtensorMapInterleave, CUtensorMapSwizzle, CUtensorMapL2promotion, CUtensorMapFloatOOBfill);

void map2d(EncodeFn enc, CUtensorMap* tm, const void* p, uint64_t cols, uint64_t rows, uint32_t bc, uint32_t br, CUtensorMapSwizzle sw) {
  cuuint64_t gd[2] = {cols, rows}, gs[1] = {cols * 2};
  cuuint32_t bd[2] = {bc, br}, es[2] = {1, 1};
  enc(tm, CU_TENSOR_MAP_DATA_TYPE_BFLOAT16, 2, (void*)p, gd, gs, bd, es, CU_TENSOR_MAP_INTERLEAVE_NONE, sw,
      sw == CU_TENSOR_MAP_SWIZZLE_128B ? CU_TENSOR_MAP_L2_PROMOTION_L2_128B : CU_TENSOR_MAP_L2_PROMOTION_NONE, CU_TENSOR_MAP_FLOAT_OOB_FILL_NONE);
}

}

extern "C" void kernel_launch(void* const* d_in, const int* in_sizes, int n_in, void* d_out, int out_size) {
  (void)in_sizes; (void)n_in; (void)out_size;
  static EncodeFn enc = nullptr;
  if (!enc) {
    cudaDriverEntryPointQueryResult qr;
    cudaGetDriverEntryPoint("cuTensorMapEncodeTiled", (void**)&enc, cudaEnableDefault, &qr);
    cudaFuncSetAttribute(fused_kernel, cudaFuncAttributeMaxDynamicSharedMemorySize, SMEM_BYTES);
  }
  Params prm;
  const CUtensorMapSwizzle S128 = CU_TENSOR_MAP_SWIZZLE_128B;
  map2d(enc, &prm.tx, d_in[0], kD, kS, 64, 64, S128);
  map2d(enc, &prm.tBre, d_in[3], kD, 576, 64, 72, S128);
  map2d(enc, &prm.tBim, d_in[4], kD, 576, 64, 72, S128);
  map2d(enc, &prm.tCre, d_in[5], 576, kD, 64, 64, S128);
  map2d(enc, &prm.tCim, d_in[6], 576, kD, 64, 64, S128);
  map2d(enc, &prm.tCre8, d_in[5], 576, kD, 8, 64, CU_TENSOR_MAP_SWIZZLE_NONE);
  map2d(enc, &prm.tCim8, d_in[6], 576, kD, 8, 64, CU_TENSOR_MAP_SWIZZLE_NONE);
  map2d(enc, &prm.tWg, d_in[10], kF, kD, 64, 64, S128);
  map2d(enc, &prm.tWu, d_in[11], kF, kD, 64, 64, S128);
  map2d(enc, &prm.tWd, d_in[12], kD, kF, 64, 64, S128);
  {
    cuuint64_t gd[4] = {kD, 2, 4, kS / 8}, gs[3] = {4 * kD * 4, kD * 4, 8 * kD * 4};
    cuuint32_t bd[4] = {32, 2, 4, 8}, es[4] = {1, 1, 1, 1};
    enc(&prm.tOut, CU_TENSOR_MAP_DATA_TYPE_FLOAT32, 4, d_out, gd, gs, bd, es, CU_TENSOR_MAP_INTERLEAVE_NONE, S128, CU_TENSOR_MAP_L2_PROMOTION_NONE,
        CU_TENSOR_MAP_FLOAT_OOB_FILL_NONE);
  }
  prm.lre = (const __nv_bfloat16*)d_in[1];
  prm.lim = (const __nv_bfloat16*)d_in[2];
  prm.bre = (const __nv_bfloat16*)d_in[3];
  prm.bim = (const __nv_bfloat16*)d_in[4];
  prm.cre = (const __nv_bfloat16*)d_in[5];
  prm.cim = (const __nv_bfloat16*)d_in[6];
  prm.wg = (const __nv_bfloat16*)d_in[10];
  prm.wu = (const __nv_bfloat16*)d_in[11];
  prm.wd = (const __nv_bfloat16*)d_in[12];
  prm.ldt = (const __nv_bfloat16*)d_in[7];
  prm.dskip = (const __nv_bfloat16*)d_in[8];
  prm.out = (float*)d_out;

  fused_kernel<<<128, 384, SMEM_BYTES, cudaStreamPerThread>>>(prm);
}
```

```cpp
#include <cuda_runtime.h>
#include <cuda.h>
#include <cuda_bf16.h>
#include <stdint.h>

namespace {

constexpr int kS = 2048, kD = 576, kF = 4608;
constexpr int SKEW = 4;
constexpr int PFD = 18;
constexpr int NST = 6;
constexpr uint32_t SLOT = 16384;
constexpr uint32_t OFF_H = NST * SLOT;
constexpr uint32_t HS_LBO = 1040;
constexpr uint32_t HS_BYTES = 18 * HS_LBO;
constexpr uint32_t OFF_DUMP = OFF_H + 65536 - HS_BYTES;
constexpr uint32_t OFF_STG = OFF_H + 2 * SLOT;
constexpr uint32_t OFF_HS = OFF_STG + 65536;
constexpr uint32_t HS_MAIN = 16 * HS_LBO, HS_REM = 2 * HS_LBO;
constexpr uint32_t OFF_CONST = OFF_H + 131072;
constexpr uint32_t OFF_BAR = OFF_CONST + 4 * 576;
constexpr uint32_t SMEM_BYTES = OFF_BAR + 384 + 384;
static_assert(SMEM_BYTES <= 232448 && OFF_HS + 2 * HS_MAIN <= OFF_BAR, "smem");

enum { B_FULL = 0, B_EMPTY = NST + 2, B_X = 2 * NST + 4, B_X8 = B_X + 8, B_BU  , B_RING = B_BU + 4  , B_SCAN = B_RING + 2  , B_PARK = B_SCAN + 2, B_HFREE, B_HSFULL, B_SFULL,
       B_SFREE = B_SFULL + 2, B_RFULL = B_SFREE + 2, B_RFREE = B_RFULL + 2, B_COUNT = B_RFREE + 2 };
static_assert(B_COUNT * 8 <= 384, "barriers");
enum { NB_SKEW = 1, NB_XDONE = 2  , NB_SCAN = 4, NB_DUMP = 5, NB_HFREE = 6, NB_STATS = 7 };
constexpr uint32_t HBLK0 = 0x07652CB4u, HBLK1 = 0x189A3DEFu;
constexpr uint32_t OFF_BU0 = SLOT, OFF_BU1 = OFF_H, OFF_BU2 = OFF_H + 65536 + 19456;
static_assert(OFF_BU1 + 5 * 9216 <= OFF_DUMP && OFF_BU2 >= OFF_DUMP + 2 * HS_BYTES && OFF_BU2 + 5 * 9216 <= OFF_CONST, "Bu tiles");

struct __align__(64) Params {
  CUtensorMap tx, tBre, tBim, tWg, tWu, tWd, tCre, tCim, tCre8, tCim8, tOut;
  const __nv_bfloat16 *lre, *lim, *bre, *bim, *cre, *cim, *ldt, *dskip, *wg, *wu, *wd;
  float* out;
};

__device__ unsigned g_epoch[128];
__device__ unsigned g_ready[16];
__device__ __align__(256) uint2 g_S[2][16][8][96];
__device__ __align__(128) uint8_t g_hs[128][2 * HS_BYTES];

__device__ __forceinline__ void wgmma_n72_rs_tb0(float (&d)[36], uint32_t a0, uint32_t a1, uint32_t a2, uint32_t a3, uint64_t db, int scale_d) {
  asm volatile("{\n.reg .pred p;\nsetp.ne.b32 p, %41, 0;\n"
    "wgmma.mma_async.sync.aligned.m64n72k16.f32.bf16.bf16 {"
    "%0, %1, %2, %3, %4, %5, %6, %7, %8, %9, %10, %11, %12, %13, %14, %15, "
    "%16, %17, %18, %19, %20, %21, %22, %23, %24, %25, %26, %27, %28, %29, %30, %31, "
    "%32, %33, %34, %35"
    "}, {%36, %37, %38, %39}, %40, p, 1, 1, 0;\n}\n"
    : "+f"(d[0]), "+f"(d[1]), "+f"(d[2]), "+f"(d[3]), "+f"(d[4]), "+f"(d[5]), "+f"(d[6]), "+f"(d[7]),
      "+f"(d[8]), "+f"(d[9]), "+f"(d[10]), "+f"(d[11]), "+f"(d[12]), "+f"(d[13]), "+f"(d[14]), "+f"(d[15]),
      "+f"(d[16]), "+f"(d[17]), "+f"(d[18]), "+f"(d[19]), "+f"(d[20]), "+f"(d[21]), "+f"(d[22]), "+f"(d[23]),
      "+f"(d[24]), "+f"(d[25]), "+f"(d[26]), "+f"(d[27]), "+f"(d[28]), "+f"(d[29]), "+f"(d[30]), "+f"(d[31]),
      "+f"(d[32]), "+f"(d[33]), "+f"(d[34]), "+f"(d[35])
    : "r"(a0), "r"(a1), "r"(a2), "r"(a3), "l"(db), "r"(scale_d));
}
__device__ __forceinline__ void wgmma_n128_rs_tb1(float (&d)[64], uint32_t a0, uint32_t a1, uint32_t a2, uint32_t a3, uint64_t db, int scale_d) {
  asm volatile("{\n.reg .pred p;\nsetp.ne.b32 p, %69, 0;\n"
    "wgmma.mma_async.sync.aligned.m64n128k16.f32.bf16.bf16 {"
    "%0, %1, %2, %3, %4, %5, %6, %7, %8, %9, %10, %11, %12, %13, %14, %15, "
    "%16, %17, %18, %19, %20, %21, %22, %23, %24, %25, %26, %27, %28, %29, %30, %31, "
    "%32, %33, %34, %35, %36, %37, %38, %39, %40, %41, %42, %43, %44, %45, %46, %47, "
    "%48, %49, %50, %51, %52, %53, %54, %55, %56, %57, %58, %59, %60, %61, %62, %63"
    "}, {%64, %65, %66, %67}, %68, p, 1, 1, 1;\n}\n"
    : "+f"(d[0]), "+f"(d[1]), "+f"(d[2]), "+f"(d[3]), "+f"(d[4]), "+f"(d[5]), "+f"(d[6]), "+f"(d[7]),
      "+f"(d[8]), "+f"(d[9]), "+f"(d[10]), "+f"(d[11]), "+f"(d[12]), "+f"(d[13]), "+f"(d[14]), "+f"(d[15]),
      "+f"(d[16]), "+f"(d[17]), "+f"(d[18]), "+f"(d[19]), "+f"(d[20]), "+f"(d[21]), "+f"(d[22]), "+f"(d[23]),
      "+f"(d[24]), "+f"(d[25]), "+f"(d[26]), "+f"(d[27]), "+f"(d[28]), "+f"(d[29]), "+f"(d[30]), "+f"(d[31]),
      "+f"(d[32]), "+f"(d[33]), "+f"(d[34]), "+f"(d[35]), "+f"(d[36]), "+f"(d[37]), "+f"(d[38]), "+f"(d[39]),
      "+f"(d[40]), "+f"(d[41]), "+f"(d[42]), "+f"(d[43]), "+f"(d[44]), "+f"(d[45]), "+f"(d[46]), "+f"(d[47]),
      "+f"(d[48]), "+f"(d[49]), "+f"(d[50]), "+f"(d[51]), "+f"(d[52]), "+f"(d[53]), "+f"(d[54]), "+f"(d[55]),
      "+f"(d[56]), "+f"(d[57]), "+f"(d[58]), "+f"(d[59]), "+f"(d[60]), "+f"(d[61]), "+f"(d[62]), "+f"(d[63])
    : "r"(a0), "r"(a1), "r"(a2), "r"(a3), "l"(db), "r"(scale_d));
}
__device__ __forceinline__ void wgmma_n128_ss_tb0(float (&d)[64], uint64_t da, uint64_t db, int scale_d) {
  asm volatile("{\n.reg .pred p;\nsetp.ne.b32 p, %66, 0;\n"
    "wgmma.mma_async.sync.aligned.m64n128k16.f32.bf16.bf16 {"
    "%0, %1, %2, %3, %4, %5, %6, %7, %8, %9, %10, %11, %12, %13, %14, %15, "
    "%16, %17, %18, %19, %20, %21, %22, %23, %24, %25, %26, %27, %28, %29, %30, %31, "
    "%32, %33, %34, %35, %36, %37, %38, %39, %40, %41, %42, %43, %44, %45, %46, %47, "
    "%48, %49, %50, %51, %52, %53, %54, %55, %56, %57, %58, %59, %60, %61, %62, %63"
    "}, %64, %65, p, 1, 1, 0, 0;\n}\n"
    : "+f"(d[0]), "+f"(d[1]), "+f"(d[2]), "+f"(d[3]), "+f"(d[4]), "+f"(d[5]), "+f"(d[6]), "+f"(d[7]),
      "+f"(d[8]), "+f"(d[9]), "+f"(d[10]), "+f"(d[11]), "+f"(d[12]), "+f"(d[13]), "+f"(d[14]), "+f"(d[15]),
      "+f"(d[16]), "+f"(d[17]), "+f"(d[18]), "+f"(d[19]), "+f"(d[20]), "+f"(d[21]), "+f"(d[22]), "+f"(d[23]),
      "+f"(d[24]), "+f"(d[25]), "+f"(d[26]), "+f"(d[27]), "+f"(d[28]), "+f"(d[29]), "+f"(d[30]), "+f"(d[31]),
      "+f"(d[32]), "+f"(d[33]), "+f"(d[34]), "+f"(d[35]), "+f"(d[36]), "+f"(d[37]), "+f"(d[38]), "+f"(d[39]),
      "+f"(d[40]), "+f"(d[41]), "+f"(d[42]), "+f"(d[43]), "+f"(d[44]), "+f"(d[45]), "+f"(d[46]), "+f"(d[47]),
      "+f"(d[48]), "+f"(d[49]), "+f"(d[50]), "+f"(d[51]), "+f"(d[52]), "+f"(d[53]), "+f"(d[54]), "+f"(d[55]),
      "+f"(d[56]), "+f"(d[57]), "+f"(d[58]), "+f"(d[59]), "+f"(d[60]), "+f"(d[61]), "+f"(d[62]), "+f"(d[63])
    : "l"(da), "l"(db), "r"(scale_d));
}
__device__ __forceinline__ void wgmma_n64_rs_tb1(float (&d)[32], uint32_t a0, uint32_t a1, uint32_t a2, uint32_t a3, uint64_t db, int scale_d) {
  asm volatile("{\n.reg .pred p;\nsetp.ne.b32 p, %37, 0;\n"
    "wgmma.mma_async.sync.aligned.m64n64k16.f32.bf16.bf16 {"
    "%0, %1, %2, %3, %4, %5, %6, %7, %8, %9, %10, %11, %12, %13, %14, %15, "
    "%16, %17, %18, %19, %20, %21, %22, %23, %24, %25, %26, %27, %28, %29, %30, %31"
    "}, {%32, %33, %34, %35}, %36, p, 1, 1, 1;\n}\n"
    : "+f"(d[0]), "+f"(d[1]), "+f"(d[2]), "+f"(d[3]), "+f"(d[4]), "+f"(d[5]), "+f"(d[6]), "+f"(d[7]),
      "+f"(d[8]), "+f"(d[9]), "+f"(d[10]), "+f"(d[11]), "+f"(d[12]), "+f"(d[13]), "+f"(d[14]), "+f"(d[15]),
      "+f"(d[16]), "+f"(d[17]), "+f"(d[18]), "+f"(d[19]), "+f"(d[20]), "+f"(d[21]), "+f"(d[22]), "+f"(d[23]),
      "+f"(d[24]), "+f"(d[25]), "+f"(d[26]), "+f"(d[27]), "+f"(d[28]), "+f"(d[29]), "+f"(d[30]), "+f"(d[31])
    : "r"(a0), "r"(a1), "r"(a2), "r"(a3), "l"(db), "r"(scale_d));
}
__device__ __forceinline__ void wgmma_n64_ss_tb0(float (&d)[32], uint64_t da, uint64_t db, int scale_d) {
  asm volatile("{\n.reg .pred p;\nsetp.ne.b32 p, %34, 0;\n"
    "wgmma.mma_async.sync.aligned.m64n64k16.f32.bf16.bf16 {"
    "%0, %1, %2, %3, %4, %5, %6, %7, %8, %9, %10, %11, %12, %13, %14, %15, "
    "%16, %17, %18, %19, %20, %21, %22, %23, %24, %25, %26, %27, %28, %29, %30, %31"
    "}, %32, %33, p, 1, 1, 0, 0;\n}\n"
    : "+f"(d[0]), "+f"(d[1]), "+f"(d[2]), "+f"(d[3]), "+f"(d[4]), "+f"(d[5]), "+f"(d[6]), "+f"(d[7]),
      "+f"(d[8]), "+f"(d[9]), "+f"(d[10]), "+f"(d[11]), "+f"(d[12]), "+f"(d[13]), "+f"(d[14]), "+f"(d[15]),
      "+f"(d[16]), "+f"(d[17]), "+f"(d[18]), "+f"(d[19]), "+f"(d[20]), "+f"(d[21]), "+f"(d[22]), "+f"(d[23]),
      "+f"(d[24]), "+f"(d[25]), "+f"(d[26]), "+f"(d[27]), "+f"(d[28]), "+f"(d[29]), "+f"(d[30]), "+f"(d[31])
    : "l"(da), "l"(db), "r"(scale_d));
}

__device__ __forceinline__ bool elect() {
  uint32_t p;
  asm volatile("{.reg .pred q; elect.sync _|q, 0xffffffff; selp.u32 %0,1,0,q;}" : "=r"(p));
  return p;
}
__device__ __forceinline__ void mbar_init(uint32_t bar, uint32_t cnt) { asm volatile("mbarrier.init.shared::cta.b64 [%0], %1;" ::"r"(bar), "r"(cnt) : "memory"); }
__device__ __forceinline__ void mbar_expect(uint32_t bar, uint32_t bytes) { asm volatile("mbarrier.arrive.expect_tx.shared::cta.b64 _, [%0], %1;" ::"r"(bar), "r"(bytes) : "memory"); }
__device__ __forceinline__ void mbar_arrive(uint32_t bar) { asm volatile("mbarrier.arrive.shared::cta.b64 _, [%0];" ::"r"(bar) : "memory"); }
__device__ __forceinline__ void mbar_arrive_cta(uint32_t bar, uint32_t cta) {
  asm volatile("{.reg .b32 ra; mapa.shared::cluster.u32 ra, %0, %1; mbarrier.arrive.shared::cluster.b64 _, [ra];}" ::"r"(bar), "r"(cta) : "memory");
}
__device__ __forceinline__ void mbar_wait(uint32_t bar, uint32_t parity) {
  asm volatile(
      "{\n.reg .pred p;\n.reg .u32 c;\nmov.u32 c, 0x100000;\n"
      "LAB_WAIT:\nmbarrier.try_wait.parity.shared::cta.b64 p, [%0], %1;\n@p bra DONE;\n"
      "nanosleep.u32 0;\nsub.u32 c, c, 1;\nsetp.ne.u32 p, c, 0;\n@p bra LAB_WAIT;\ntrap;\nDONE:\n}" ::"r"(bar), "r"(parity) : "memory");
}
__device__ __forceinline__ void bar_sync(int id, int n) { asm volatile("bar.sync %0, %1;" ::"r"(id), "r"(n) : "memory"); }
__device__ __forceinline__ void bar_arrive(int id, int n) { asm volatile("bar.arrive %0, %1;" ::"r"(id), "r"(n) : "memory"); }
__device__ __forceinline__ void wg_fence() { asm volatile("wgmma.fence.sync.aligned;" ::: "memory"); }
__device__ __forceinline__ void wg_commit() { asm volatile("wgmma.commit_group.sync.aligned;" ::: "memory"); }
template <int N> __device__ __forceinline__ void wg_wait() { asm volatile("wgmma.wait_group.sync.aligned %0;" ::"n"(N) : "memory"); }
__device__ __forceinline__ void tma2d(uint32_t dst, const CUtensorMap* tm, uint32_t bar, int c0, int c1) {
  asm volatile("cp.async.bulk.tensor.2d.shared::cluster.global.mbarrier::complete_tx::bytes [%0], [%1,{%3,%4}], [%2];" ::"r"(dst), "l"(tm), "r"(bar), "r"(c0), "r"(c1) : "memory");
}
__device__ __forceinline__ void tma2d_mc(uint32_t dst, const CUtensorMap* tm, uint32_t bar, int c0, int c1) {
  asm volatile("cp.async.bulk.tensor.2d.shared::cluster.global.mbarrier::complete_tx::bytes.multicast::cluster [%0], [%1,{%3,%4}], [%2], %5;" ::"r"(dst), "l"(tm), "r"(bar), "r"(c0), "r"(c1), "h"((uint16_t)3) : "memory");
}
__device__ __forceinline__ void l2_prefetch_line(const void* p) { asm volatile("prefetch.global.L2 [%0];" ::"l"(p)); }
__device__ __forceinline__ uint64_t desc(uint32_t lo, uint32_t hi) { return ((uint64_t)hi << 32) | lo; }
constexpr uint32_t DHI_SW128 = (1024 >> 4) | (1u << 30);
constexpr uint32_t DHI_NONE = (128 >> 4);
constexpr uint32_t DLO_HS = (HS_LBO >> 4) << 16;
constexpr uint32_t DLO_MN = (8192 >> 4) << 16;
constexpr uint32_t DLO_K = 1u << 16;
__device__ __forceinline__ float tanh_fast(float x) { float y; asm("tanh.approx.f32 %0, %1;" : "=f"(y) : "f"(x)); return y; }
__device__ __forceinline__ uint32_t pack_bf16(float lo, float hi) { uint32_t r; asm("cvt.rn.bf16x2.f32 %0, %1, %2;" : "=r"(r) : "f"(hi), "f"(lo)); return r; }
__device__ __forceinline__ float rbf(float x) { return __uint_as_float(pack_bf16(0.f, x)); }
__device__ __forceinline__ void mma16816(float (&c)[4], uint32_t a0, uint32_t a1, uint32_t a2, uint32_t a3, uint32_t b0, uint32_t b1) {
  asm volatile("mma.sync.aligned.m16n8k16.row.col.f32.bf16.bf16.f32 {%0,%1,%2,%3}, {%4,%5,%6,%7}, {%8,%9}, {%0,%1,%2,%3};"
               : "+f"(c[0]), "+f"(c[1]), "+f"(c[2]), "+f"(c[3]) : "r"(a0), "r"(a1), "r"(a2), "r"(a3), "r"(b0), "r"(b1));
}
__device__ __forceinline__ void sts128(uint32_t a, uint32_t x, uint32_t y, uint32_t z, uint32_t w) {
  asm volatile("st.shared.v4.b32 [%0], {%1,%2,%3,%4};" ::"r"(a), "r"(x), "r"(y), "r"(z), "r"(w) : "memory");
}
__device__ __forceinline__ void sts64f(uint32_t a, float x, float y) { asm volatile("st.shared.v2.f32 [%0], {%1,%2};" ::"r"(a), "f"(x), "f"(y) : "memory"); }
__device__ __forceinline__ float2 lds64f(uint32_t a) { float2 v; asm volatile("ld.shared.v2.f32 {%0,%1}, [%2];" : "=f"(v.x), "=f"(v.y) : "r"(a) : "memory"); return v; }
__device__ __forceinline__ uint32_t lds32(uint32_t a) { uint32_t v; asm volatile("ld.shared.b32 %0, [%1];" : "=r"(v) : "r"(a) : "memory"); return v; }
__device__ __forceinline__ void lds128(uint32_t a, uint32_t& x, uint32_t& y, uint32_t& z, uint32_t& w) {
  asm volatile("ld.shared.v4.b32 {%0,%1,%2,%3}, [%4];" : "=r"(x), "=r"(y), "=r"(z), "=r"(w) : "r"(a) : "memory");
}
__device__ __forceinline__ void lds128_inplace(uint32_t a, uint32_t& x, uint32_t& y, uint32_t& z, uint32_t& w) {
  asm volatile("{.reg .pred p; .reg .u32 n; mov.u32 n, %%ntid.y; setp.ne.u32 p, n, 0; @p ld.shared.v4.b32 {%0,%1,%2,%3}, [%4];}" : "+r"(x), "+r"(y), "+r"(z), "+r"(w) : "r"(a) : "memory");
}
__device__ __forceinline__ float bflo(uint32_t v) { return __uint_as_float(v << 16); }
__device__ __forceinline__ float bfhi(uint32_t v) { return __uint_as_float(v & 0xffff0000u); }
template <int N> __device__ __forceinline__ void keep(float (&a)[N]) {
#pragma unroll
  for (int i = 0; i < N; i++) asm volatile("" : "+f"(a[i])::"memory");
}

__global__ void __cluster_dims__(2, 1, 1) __launch_bounds__(384, 1) fused_kernel(const __grid_constant__ Params prm) {
  extern __shared__ __align__(1024) uint8_t smem[];
  const int warp = __shfl_sync(0xffffffffu, threadIdx.x >> 5, 0);
  const uint32_t sb0 = (uint32_t)__cvta_generic_to_shared(smem);
  const int j = blockIdx.x & 7, m = blockIdx.x >> 3, rank = j & 1;
  auto smem_base = [&]() { return __shfl_sync(0xffffffffu, sb0 + (threadIdx.x & 31), 0); };

  if (threadIdx.x == 320) asm volatile("prefetch.tensormap [%0];" ::"l"(&prm.tx) : "memory");
  if (warp == 0) {
    if (elect()) {
#pragma unroll
      for (int i = B_X8; i >= B_X; i--) mbar_init(sb0 + OFF_BAR + 8 * i, 1);
      asm volatile("fence.mbarrier_init.release.cluster;" ::: "memory");
    }
    __syncwarp();
  }
  asm volatile("barrier.cluster.arrive.relaxed.aligned;" ::: "memory");
  if (warp == 0) {
    const uint32_t xb = sb0 + OFF_BAR;
    if (elect()) {
      mbar_expect(xb + 8 * B_X8, 16384);
      tma2d(sb0, &prm.tx, xb + 8 * B_X8, 512, m * 128);
      tma2d(sb0 + 8192, &prm.tx, xb + 8 * B_X8, 512, m * 128 + 64);
#pragma unroll
      for (int i = 0; i < 4; i++) {
        mbar_expect(xb + 8 * (B_X + i), 16384);
        tma2d(sb0 + OFF_H + i * 16384, &prm.tx, xb + 8 * (B_X + i), i * 128, m * 128);
        tma2d(sb0 + OFF_H + i * 16384 + 8192, &prm.tx, xb + 8 * (B_X + i), i * 128 + 64, m * 128);
      }
    }
    __syncwarp();
  }
  asm volatile("barrier.cluster.wait.aligned;" ::: "memory");
  if (warp == 8 || warp == 9) {
    if (elect()) {
      if (warp == 8) {
#pragma unroll
        for (int i = 0; i < B_X; i++) mbar_init(sb0 + OFF_BAR + 8 * i, i >= B_EMPTY ? 2 : 1);
      } else {
#pragma unroll
        for (int i = B_X8 + 1; i < B_COUNT; i++) mbar_init(sb0 + OFF_BAR + 8 * i, (i >= B_SFULL && i < B_SFULL + 2) ? 4 : (i == B_RING || i == B_RING + 1) ? 2 : 1);
        if (sb0 & 1023) __trap();
      }
      asm volatile("fence.mbarrier_init.release.cluster;" ::: "memory");
    }
    __syncwarp();
  }
  if (warp == 0) {
    const uint32_t xb = sb0 + OFF_BAR;
    const bool e = elect();
#pragma unroll
    for (int i = 0; i < 4; i++) {
      const int kb = i * 2 + rank;
      if (e) { mbar_expect(xb + 8 * (B_X + 4 + i), 16384); tma2d_mc(sb0 + OFF_H + 65536 + kb * 8192, &prm.tx, xb + 8 * (B_X + 4 + i), kb * 64, m * 128 + 64); }
    }
    __syncwarp();
  }
  asm volatile("barrier.cluster.arrive.relaxed.aligned;\nbarrier.cluster.wait.aligned;" ::: "memory");

  if (warp >= 8) {
    asm volatile("setmaxnreg.dec.sync.aligned.u32 24;");
    if (warp == 8) {
      const uint32_t sb = smem_base(), bars = sb + OFF_BAR;
      bool e;
      int s = 0, nst = NST + 2; uint32_t ph = 1;
      uint32_t dst, fb;
      auto acquire = [&](uint32_t bytes) {
        mbar_wait(bars + 8 * (B_EMPTY + s), ph);
        fb = bars + 8 * (B_FULL + s); dst = sb + s * SLOT;
        e = elect();
        if (e) mbar_expect(fb, bytes);
        if (++s == nst) { s = 0; ph ^= 1; }
      };
      auto box = [&](const CUtensorMap* t, uint32_t o, int a, int b) { if (e) tma2d(dst + o, t, fb, a, b); };
      auto hs_rem = [&](uint32_t o) {
        if (e) asm volatile("cp.async.bulk.shared::cluster.global.mbarrier::complete_tx::bytes [%0], [%1], %2, [%3];" ::"r"(dst + o),
                            "l"(&g_hs[blockIdx.x][2 * HS_MAIN]), "r"(2 * HS_REM), "r"(fb) : "memory");
      };
      const int lane = threadIdx.x & 31;
      const char* pf = lane < 8 ? (const char*)(lane & 4 ? prm.wu : prm.wg) + ((size_t)(m * 4 + (lane & 3)) * kF + j * 576) * 2
                     : lane < 12 ? (const char*)prm.wd + (size_t)j * 576 * 1152 + (m * 324 + (lane & 3)) * 128
                                 : (const char*)(lane & 1 ? prm.cim : prm.cre) + (size_t)blockIdx.x * 5184;
      int pk = 0, pleft = 81;
      auto prefetch = [&]() {
        if (pleft > 0) {
          if (lane < 14) l2_prefetch_line(pf);
          pf += lane < 8 ? (pk == 8 ? 128 - 8 * 64 * kF * 2 : 64 * kF * 2) : lane < 12 ? 512 : 64;
          pk = pk == 8 ? 0 : pk + 1;
          pleft--;
        }
      };
      mbar_wait(bars + 8 * B_X8, 0);
      e = elect();
#pragma unroll 1
      for (int kb = 0; kb < 8; kb++) {
        fb = bars + 8 * (B_BU + (kb >> 2));
        if (e) { if ((kb & 3) == 0) mbar_expect(fb, 4 * 9216); tma2d(sb + OFF_BU0 + kb * 9216, &prm.tBre, fb, kb * 64, j * 72); }
      }
      bar_sync(NB_XDONE, 160);
      fb = bars + 8 * (B_BU + 2);
      if (e) { mbar_expect(fb, 5 * 9216); tma2d(sb + OFF_BU1, &prm.tBre, fb, 512, j * 72); }
#pragma unroll 1
      for (int kb = 0; kb < 4; kb++) if (e) tma2d(sb + OFF_BU1 + (kb + 1) * 9216, &prm.tBim, fb, kb * 64, j * 72);
#pragma unroll 1
      for (int i = 0; i < PFD / 2; i++) prefetch();
      bar_sync(NB_XDONE + 1, 160);
      fb = bars + 8 * (B_BU + 3);
      if (e) mbar_expect(fb, 5 * 9216);
#pragma unroll 1
      for (int kb = 4; kb < 9; kb++) if (e) tma2d(sb + OFF_BU2 + (kb - 4) * 9216, &prm.tBim, fb, kb * 64, j * 72);
#pragma unroll 1
      for (int i = PFD / 2; i < PFD; i++) prefetch();
      mbar_wait(bars + 8 * B_RING, 0);
#pragma unroll 1
      for (int c = 0; c < 9; c++) {
        const int col = j * 576 + c * 64;
#pragma unroll 1
        for (int kb = 0; kb < 9; kb++) {
          if (kb == 6 && c == 0) mbar_wait(bars + 8 * (B_RING + 1), 0);
          if (kb == 6 && c == 3) nst = 7;
          if (kb == 5 && c == 7) nst = 6;
          acquire(16384); box(&prm.tWg, 0, col, kb * 64); box(&prm.tWu, 8192, col, kb * 64); prefetch();
        }
      }
      auto half_tile = [&](int n0) {
#pragma unroll 1
        for (int kp = 0; kp < 4; kp++) { acquire(16384); box(&prm.tWd, 0, n0, j * 576 + kp * 128); box(&prm.tWd, 8192, n0, j * 576 + kp * 128 + 64); }
        acquire(8192 + 2048 + 2 * HS_REM); box(&prm.tWd, 0, n0, j * 576 + 512); box(&prm.tCre8, 8192, j * 72 + 64, n0); box(&prm.tCim8, 9216, j * 72 + 64, n0); hs_rem(10240);
        acquire(16384); box(&prm.tCre, 0, j * 72, n0); box(&prm.tCim, 8192, j * 72, n0);
      };
      mbar_wait(bars + 8 * B_PARK, 0);
      asm volatile("fence.proxy.async.global;" ::: "memory");
      if (rank) half_tile(512);
#pragma unroll 1
      for (int t = 0; t < 4 - rank; t++) {
        const int n0 = ((rank ^ t ^ 1) & 1) * 256 + (((t >> 1) ^ (j >> 1)) & 1) * 128;
#pragma unroll 1
        for (int kb = 0; kb < 9; kb++) {
          if (rank ? (t == 0 && kb == 5) : (t == 1 && kb == 1)) nst = NST + 1;
          if (t == 1 && kb == (rank ? 1 : 7)) nst = NST + 2;
          if (kb == 3 && t == 0 && rank) mbar_wait(bars + 8 * B_HFREE, 0);
          acquire(16384); box(&prm.tWd, 0, n0, j * 576 + kb * 64); box(&prm.tWd, 8192, n0 + 64, j * 576 + kb * 64);
        }
        if (t == 0) mbar_wait(bars + 8 * B_HFREE, 0);
        acquire(16384); box(&prm.tCre, 0, j * 72, n0); box(&prm.tCre, 8192, j * 72, n0 + 64);
        acquire(16384); box(&prm.tCim, 0, j * 72, n0); box(&prm.tCim, 8192, j * 72, n0 + 64);
        acquire(4096 + 2 * HS_REM); hs_rem(4096);
        box(&prm.tCre8, 0, j * 72 + 64, n0); box(&prm.tCre8, 1024, j * 72 + 64, n0 + 64);
        box(&prm.tCim8, 2048, j * 72 + 64, n0); box(&prm.tCim8, 3072, j * 72 + 64, n0 + 64);
      }
      if (!rank) half_tile(512);
      else {
#pragma unroll 1
        for (int hh = 0; hh < 2; hh++) half_tile(256 + (((j >> 1) ^ 1) & 1) * 128 + hh * 64);
      }
    } else {
      const uint32_t sb = smem_base(), bars = sb + OFF_BAR;
      const int p = min((int)threadIdx.x - 288, 71);
      if (threadIdx.x < 288 + 10) asm volatile("prefetch.tensormap [%0];" ::"l"(&prm.tBre + (threadIdx.x - 288)) : "memory");
      if (warp == 10) {
        const int l = threadIdx.x & 31;
        const char* q = (const char*)(l & 1 ? prm.bim : prm.bre) + (size_t)blockIdx.x * 5184;
        mbar_wait(bars + 8 * B_X8, 0);
#pragma unroll
        for (int i = 0; i < 3; i++) if (i * 16 + (l >> 1) < 42) l2_prefetch_line(q + min((i * 16 + (l >> 1)) * 128, 5183));
      }
      const unsigned epoch = *(volatile unsigned*)&g_epoch[blockIdx.x];
      {
        const int pg = j * 72 + p;
        const float lr = __bfloat162float(prm.lre[pg]), li = __bfloat162float(prm.lim[pg]);
        const float dt = rbf(expf(__bfloat162float(prm.ldt[pg])));
        const float ea = expf(dt * lr);
        float sn, cs;
        sincosf(dt * li, &sn, &cs);
        const float ar = ea * cs, ai = ea * sn;
        float br = ar, bi = ai;
#pragma unroll
        for (int k = 0; k < 6; k++) { const float t = br * br - bi * bi; bi = 2.f * br * bi; br = t; }
        const float nr = ar - 1.f, den = 4.f / (lr * lr + li * li);
        sts64f(sb + OFF_CONST + p * 8, ar, ai);
        sts64f(sb + OFF_CONST + 576 + p * 8, br, bi);
        sts64f(sb + OFF_CONST + 1152 + p * 8, (nr * lr + ai * li) * den, (ai * lr - nr * li) * den);
      }
      bar_sync(NB_DUMP, 352);
      {
        const int lane = threadIdx.x & 31;
        const int half = warp == 11 ? (lane >> 2) & 1 : warp - 9;
        const uint32_t cu = sb + OFF_CONST + (warp == 11 ? 32 + (lane & 3) : lane) * 16;
        uint32_t a0 = sb + OFF_DUMP + half * HS_BYTES + (warp == 11 ? 16 : lane >> 2) * HS_LBO + (lane & 3) * 4;
        asm volatile("" : "+r"(a0));
        const uint32_t di = warp == 11 ? HS_LBO : 8 * HS_LBO;
        float a[4], h[4] = {0.f, 0.f, 0.f, 0.f};
        auto ld4 = [&](uint32_t ad, float (&v)[4]) { asm volatile("ld.shared.v4.f32 {%0,%1,%2,%3}, [%4];" : "=f"(v[0]), "=f"(v[1]), "=f"(v[2]), "=f"(v[3]) : "r"(ad) : "memory"); };
        auto cfma = [&](const float (&c)[4], float r0, float i0, float r1, float i1) {
          const float n0 = fmaf(c[0], h[0], fmaf(-c[1], h[1], r0)), n1 = fmaf(c[2], h[2], fmaf(-c[3], h[3], r1));
          h[1] = fmaf(c[0], h[1], fmaf(c[1], h[0], i0)); h[3] = fmaf(c[2], h[3], fmaf(c[3], h[2], i1));
          h[0] = n0; h[2] = n1;
        };
        ld4(cu, a);
#pragma unroll 1
        for (uint32_t ad = a0; ad != a0 + 1024; ad += 64) {
          uint32_t wr[4], wi[4];
#pragma unroll
          for (int k = 0; k < 4; k++) { wr[k] = lds32(ad + k * 16); wi[k] = lds32(ad + di + k * 16); }
#pragma unroll
          for (int k = 0; k < 4; k++) cfma(a, bflo(wr[k]), bflo(wi[k]), bfhi(wr[k]), bfhi(wi[k]));
        }
        if (half == 0) sts128(cu + 1728, __float_as_uint(h[0]), __float_as_uint(h[1]), __float_as_uint(h[2]), __float_as_uint(h[3]));
        bar_sync(NB_SCAN, 96);
        if (half == 1 && m < 15) {
          float b[4], s1[4] = {h[0], h[1], h[2], h[3]};
          ld4(cu + 576, b); ld4(cu + 1728, h);
          cfma(b, s1[0], s1[1], s1[2], s1[3]);
          uint2* gp = &g_S[epoch & 1][m][j][(cu - sb - OFF_CONST) >> 3];
          asm volatile("st.relaxed.gpu.global.v2.b64 [%0], {%1,%2};" ::"l"(gp), "l"(~(((uint64_t)__float_as_uint(h[1]) << 32) | __float_as_uint(h[0]))),
                       "l"(~(((uint64_t)__float_as_uint(h[3]) << 32) | __float_as_uint(h[2]))) : "memory");
        }
        __syncwarp();
        g_S[(epoch & 1) ^ 1][m][j][p] = make_uint2(0u, 0u);
        {
          const float2 b = lds64f(sb + OFF_CONST + 576 + p * 8);
          const float br = b.x * b.x - b.y * b.y, bi = 2.f * b.x * b.y;
          float hr = 0.f, hi = 0.f;
          const uint2* sp = &g_S[epoch & 1][0][j][p];
#pragma unroll 1
          for (int left = m; left > 0; left -= 3, sp += 3 * 768) {
            uint32_t v[3][2];
            int spins = 0;
            uint32_t ok;
            do {
#pragma unroll
              for (int k = 0; k < 3; k++) {
                v[k][0] = v[k][1] = 0xffffffffu;
                if (k < left) asm volatile("ld.relaxed.gpu.global.v2.b32 {%0,%1}, [%2];" : "=r"(v[k][0]), "=r"(v[k][1]) : "l"(sp + k * 768) : "memory");
              }
              ok = min(min(min(v[0][0], v[0][1]), min(v[1][0], v[1][1])), min(v[2][0], v[2][1]));
              if (++spins > (1 << 22)) __trap();
            } while (ok == 0u);
#pragma unroll
            for (int k = 0; k < 3; k++)
              if (k < left) { const float nr = fmaf(br, hr, fmaf(-bi, hi, __uint_as_float(~v[k][0]))); hi = fmaf(br, hi, fmaf(bi, hr, __uint_as_float(~v[k][1]))); hr = nr; }
          }
          sts64f(sb + OFF_CONST + p * 8, hr, hi);
        }
        __syncwarp();
        bar_sync(NB_SCAN, 96);
        ld4(cu, h);
        uint32_t cr, ci, cn;
        {
          float b[4], s0[4];
          ld4(cu + 576, b); ld4(cu + 1728, s0);
          if (half == 1) cfma(b, s0[0], s0[1], s0[2], s0[3]);
          ld4(cu + 1152, b);
          cr = pack_bf16(b[0], b[2]); ci = pack_bf16(b[1], b[3]); cn = ci ^ 0x80008000u;
        }
        h[1] = -h[1]; h[3] = -h[3];
        __syncwarp();
#pragma unroll 1
        for (uint32_t ad = a0; ad != a0 + 1024; ad += 32) {
          uint32_t wr[2], wi[2];
#pragma unroll
          for (int k = 0; k < 2; k++) { wr[k] = lds32(ad + k * 16); wi[k] = lds32(ad + di + k * 16); }
#pragma unroll
          for (int k = 0; k < 2; k++) {
            const float n0 = fmaf(a[0], h[0], fmaf(a[1], h[1], bflo(wr[k]))), n1 = fmaf(a[2], h[2], fmaf(a[3], h[3], bfhi(wr[k])));
            h[1] = fmaf(a[0], h[1], fmaf(-a[1], h[0], -bflo(wi[k]))); h[3] = fmaf(a[2], h[3], fmaf(-a[3], h[2], -bfhi(wi[k])));
            h[0] = n0; h[2] = n1;
            const uint32_t hr = pack_bf16(h[0], h[2]), hn = pack_bf16(h[1], h[3]);
            uint32_t o0, o1;
            asm("{.reg .b32 t; mul.rn.bf16x2 t, %2, %4; fma.rn.bf16x2 %0, %1, %3, t;}" : "=r"(o0) : "r"(hr), "r"(hn), "r"(cr), "r"(ci));
            asm("{.reg .b32 t; mul.rn.bf16x2 t, %1, %4; fma.rn.bf16x2 %0, %2, %3, t;}" : "=r"(o1) : "r"(hr), "r"(hn), "r"(cr), "r"(cn));
            asm volatile("st.shared.b32 [%0], %1;" ::"r"(ad + k * 16), "r"(o0) : "memory");
            asm volatile("st.shared.b32 [%0], %1;" ::"r"(ad + di + k * 16), "r"(o1) : "memory");
          }
        }
        asm volatile("fence.proxy.async.shared::cta;" ::: "memory");
      }
      bar_sync(NB_SCAN, 96);
      const bool lead = elect();
      if (warp == 9) {
        if (lead) {
#pragma unroll 1
          for (int i = 0; i < 10; i++) {
            const int pc = (0x8654321970ull >> (4 * i)) & 15, w = pc & 1, c4 = pc >> 1;
            asm volatile("cp.async.bulk.global.shared::cta.bulk_group [%0], [%1], %2;" ::"l"(&g_hs[blockIdx.x][c4 < 4 ? w * HS_MAIN + c4 * 4 * HS_LBO : 2 * HS_MAIN + w * HS_REM]),
                         "r"(sb + OFF_DUMP + w * HS_BYTES + c4 * 4 * HS_LBO), "r"(c4 < 4 ? 4 * HS_LBO : HS_REM) : "memory");
            asm volatile("cp.async.bulk.commit_group;\ncp.async.bulk.wait_group.read 0;" ::: "memory");
            if (i == 2) mbar_arrive(bars + 8 * B_SCAN);
          }
          mbar_arrive(bars + 8 * (B_SCAN + 1));
        }
        __syncwarp();
      }
      if (warp == 9) {
        if (lead) {
          __threadfence();
          asm volatile("red.release.gpu.global.add.u32 [%0], 1;" ::"l"(&g_ready[m]) : "memory");
          g_epoch[blockIdx.x] = epoch + 1u;
          asm volatile("cp.async.bulk.wait_group 0;" ::: "memory");
          mbar_arrive(bars + 8 * B_PARK);
        }
        __syncwarp();
        bar_sync(NB_HFREE, 288);
        if (lead) {
          mbar_arrive(bars + 8 * B_HFREE);
          mbar_expect(bars + 8 * B_HSFULL, 2 * HS_MAIN);
          asm volatile("cp.async.bulk.shared::cluster.global.mbarrier::complete_tx::bytes [%0], [%1], %2, [%3];" ::"r"(sb + OFF_HS),
                       "l"(&g_hs[blockIdx.x][0]), "r"(2 * HS_MAIN), "r"(bars + 8 * B_HSFULL) : "memory");
          for (int w = 0; w < 2; w++) mbar_arrive_cta(bars + 8 * (B_RFREE + w), rank ^ 1);
        }
        __syncwarp();
      } else {
        const int w = warp - 10;
        {
          const unsigned target = 8u * (epoch + 1u);
          int spins = 0;
          unsigned v;
          do {
            if (spins) __nanosleep(500);
            asm volatile("ld.relaxed.gpu.global.u32 %0, [%1];" : "=r"(v) : "l"(&g_ready[m]) : "memory");
            if (++spins > (1 << 21)) __trap();
          } while ((int)(v - target) < 0);
          asm volatile("fence.acq_rel.gpu;" ::: "memory");
          asm volatile("fence.proxy.async.global;" ::: "memory");
        }
        const uint32_t stg = sb + OFF_STG + w * 32768;
        const int nu = 5 + rank;
#pragma unroll 1
        for (int u = 0; u < nu; u++) {
          const int t = u - rank;
          if (t == 0 || t == 2) {
            if (elect()) mbar_expect(bars + 8 * (B_RFULL + w), 16384);
            mbar_wait(bars + 8 * (B_SFULL + w), u & 1);
            mbar_wait(bars + 8 * (B_RFREE + w), t >> 1);
            if (elect())
              asm volatile("{.reg .b32 ra, rb; mapa.shared::cluster.u32 ra, %0, %3; mapa.shared::cluster.u32 rb, %2, %3;\n"
                           "cp.async.bulk.shared::cluster.shared::cta.mbarrier::complete_tx::bytes [ra], [%1], 16384, [rb];}" ::"r"(stg + 16384),
                           "r"(stg), "r"(bars + 8 * (B_RFULL + w)), "r"(rank ^ 1) : "memory");
            mbar_wait(bars + 8 * (B_RFULL + w), t >> 1);
            if (elect()) mbar_arrive_cta(bars + 8 * (B_SFREE + w), rank ^ 1);
          } else {
            mbar_wait(bars + 8 * (B_SFULL + w), u & 1);
            const bool d = u == (rank ? 0 : 4), hf = rank && u >= 4;
            const int n0 = d ? 512 : rank * 256 + (((min(t, 3) >> 1) ^ (j >> 1)) & 1) * 128 + (u == 5 ? 64 : 0);
            const uint32_t src = d && !rank ? sb + w * SLOT : stg + (u == 5 ? 16384 : 0);
            if (elect()) {
#pragma unroll 1
              for (int b = 0; b < (d || hf ? 2 : 4); b++) {
                asm volatile("cp.reduce.async.bulk.tensor.4d.global.shared::cta.add.tile.bulk_group [%0, {%1,%2,%2,%3}], [%4];" ::"l"(&prm.tOut), "r"(n0 + b * 32), "r"(0),
                             "r"(m * 16 + w * 8), "r"(src + b * 8192) : "memory");
                asm volatile("cp.async.bulk.commit_group;" ::: "memory");
                if (u < nu - 1) asm volatile("cp.async.bulk.wait_group.read 0;" ::: "memory");
              }
              if (u < 3) {
                asm volatile("cp.async.bulk.wait_group.read 0;" ::: "memory");
                mbar_arrive(bars + 8 * (B_SFREE + w));
                if (t == 1) mbar_arrive_cta(bars + 8 * (B_RFREE + w), rank ^ 1);
              }
              if (u == nu - 1) asm volatile("cp.async.bulk.wait_group.read 0;" ::: "memory");
            }
          }
          __syncwarp();
        }
      }
    }
  } else {
    asm volatile("setmaxnreg.inc.sync.aligned.u32 240;");
    const uint32_t sb = smem_base(), bars = sb + OFF_BAR;
    const int wg = warp >> 2, w4 = warp & 3;
    const int lane = threadIdx.x & 31, g = lane >> 2, q = lane & 3;
    const uint32_t hw = sb + OFF_H + wg * 65536;

    int s = 0, nst = NST + 2; uint32_t ph = 0;
    auto release = [&](int st) { if (w4 == 0) { if (elect()) mbar_arrive(bars + 8 * (B_EMPTY + st)); } };
    const uint32_t dring = (sb & 0x3FFFF) >> 4;
    uint32_t dlo; int prev = 0;
    auto stage_begin = [&]() { mbar_wait(bars + 8 * (B_FULL + s), ph); dlo = dring + s * (SLOT >> 4); wg_fence(); };
    auto advance = [&]() { if (++s == nst) { s = 0; ph ^= 1; } };
    auto stage_end = [&](bool rel) {
      wg_commit();
      if (rel) { wg_wait<1>(); release(prev); }
      prev = s;
      advance();
    };

    uint32_t xa[144];
    uint32_t xr[18], dk[9];
    uint32_t rh[2], cc[2];
#pragma unroll
    for (int i = 0; i < 9; i++) dk[i] = __ldg((const uint32_t*)(prm.dskip + j * 72 + i * 8 + q * 2));
    {
      const int r = w4 * 16 + (lane & 7) + ((lane >> 3) & 1) * 8;
      const uint32_t ro = r * 128, cx = ((lane >> 4) ^ (lane & 7)) << 4;
      float s1[2][4] = {};
      auto load = [&](int kb, uint32_t base) {
#pragma unroll
        for (int kk = 0; kk < 4; kk++) {
          const int i = (kb * 4 + kk) * 4;
          asm volatile("ldmatrix.sync.aligned.m8n8.x4.shared.b16 {%0,%1,%2,%3}, [%4];"
                       : "=r"(xa[i]), "=r"(xa[i + 1]), "=r"(xa[i + 2]), "=r"(xa[i + 3]) : "r"(base + ro + (cx ^ (kk << 5))) : "memory");
        }
      };
      float s2[4] = {}, s3[4] = {};
      auto sums = [&](int kb) {
#pragma unroll
        for (int kk = 0; kk < 4; kk += 2) {
          const int i = (kb * 4 + kk) * 4;
          uint32_t a[8];
#pragma unroll
          for (int e = 0; e < 8; e++) asm("mul.rn.bf16x2 %0, %1, %1;" : "=r"(a[e]) : "r"(xa[i + e]));
          mma16816(s3, a[4], a[5], a[6], a[7], 0x3f803f80u, 0x3f803f80u);
          mma16816(s1[0], xa[i], xa[i + 1], xa[i + 2], xa[i + 3], 0x3f803f80u, 0x3f803f80u);
          mma16816(s2, a[0], a[1], a[2], a[3], 0x3f803f80u, 0x3f803f80u);
          mma16816(s1[1], xa[i + 4], xa[i + 5], xa[i + 6], xa[i + 7], 0x3f803f80u, 0x3f803f80u);
        }
      };
#pragma unroll
      for (int i = 0; i < 9; i++) {
        const int c8 = j * 9 + i, kb = c8 >> 3;
        xr[2 * i] = (kb < 8 ? hw + kb * 8192 : sb + wg * 8192) + (w4 * 16 + g) * 128 + (((c8 & 7) ^ g) << 4) + q * 4;
        asm volatile("" : "+r"(xr[2 * i]));
      }
      mbar_wait(bars + 8 * B_X8, 0);
      load(8, sb + wg * 8192);
      auto pin = [&]() { asm volatile("{.reg .pred p; .reg .u32 c, z; mov.u32 c, %clock; mov.u32 z, %ntid.y; setp.eq.u32 p, z, 0; @p st.shared.u32 [c], c;}" ::: "memory"); };
#pragma unroll
      for (int kp = 0; kp < 4; kp++) {
        mbar_wait(bars + 8 * (B_X + wg * 4 + kp), 0);
        load(2 * kp, hw + 2 * kp * 8192);
        load(2 * kp + 1, hw + (2 * kp + 1) * 8192);
        if (kp == 3) {
#pragma unroll
          for (int i = 0; i < 9; i++) { xr[2 * i + 1] = lds32(xr[2 * i] + 1024); xr[2 * i] = lds32(xr[2 * i]); }
        }
        if (kp == 0) sums(8); else { sums(2 * kp - 2); sums(2 * kp - 1); }
      }
      asm volatile("fence.proxy.async.shared::cta;" ::: "memory");
      bar_arrive(NB_XDONE + wg, 160);
      if (wg == 1) bar_arrive(NB_STATS, 256);
      pin();
      sums(6);
      sums(7);
      pin();
#pragma unroll
      for (int e = 0; e < 2; e++) {
        const float mu = (s1[0][2 * e + 1] + s1[1][2 * e + 1]) * (1.f / kD);
        const float var = fmaxf(fmaf(-mu, mu, (s2[2 * e] + s3[2 * e]) * (1.f / kD)), 0.f);
        float sd, r;
        asm("sqrt.approx.ftz.f32 %0, %1;" : "=f"(sd) : "f"(rbf(rbf(var) + 1e-5f)));
        asm("rcp.approx.ftz.f32 %0, %1;" : "=f"(r) : "f"(rbf(sd)));
        rh[e] = pack_bf16(0.5f * r, 0.5f * r);
        cc[e] = pack_bf16(mu, mu);
      }
    }

    auto normalise = [&](int kb) {
#pragma unroll
      for (int i = 0; i < 16; i++) asm("{.reg .b32 d; sub.rn.bf16x2 d, %0, %2; mul.rn.bf16x2 %0, d, %1;}" : "+r"(xa[16 * kb + (i >> 3) + 2 * (i & 7)]) : "r"(rh[i >> 3]), "r"(cc[i >> 3]));
    };
    {
      float ab[36];
      float* op = prm.out + (size_t)(m * 128 + wg * 64 + w4 * 16 + g) * kD + j * 72 + q * 2;
      auto residual = [&](int i) {
        asm volatile("add.rn.bf16x2 %0, %0, %0;" : "+r"(dk[i]));
#pragma unroll
        for (int e = 0; e < 2; e++) {
          uint32_t t;
          asm("{.reg .b32 d; sub.rn.bf16x2 d, %1, %3; mul.rn.bf16x2 %0, d, %2;}" : "=r"(t) : "r"(xr[2 * i + e]), "r"(rh[e]), "r"(cc[e]));
          asm("fma.rn.bf16x2 %0, %0, %1, %2;" : "+r"(t) : "r"(dk[i]), "r"(xr[2 * i + e]));
          *(float2*)(op + e * 8 * kD + i * 8) = make_float2(bflo(t), bfhi(t));
        }
      };
      const uint32_t da = sb + OFF_DUMP + wg * HS_BYTES + (w4 * 16 + g) * 16 + q * 4;
      auto dump = [&](int im) {
#pragma unroll
        for (int i = 0; i < 18; i++)
          asm volatile("st.shared.b32 [%0], %1;" ::"r"(da + (i < 16 ? 8 * im + (i >> 1) : 16 + im) * HS_LBO + (i & 1) * 128), "r"(pack_bf16(ab[2 * i], ab[2 * i + 1])) : "memory");
      };
      auto bu = [&](int kb, uint32_t off) {
        wg_fence();
#pragma unroll
        for (int kk = 0; kk < 4; kk++) { const int i = (kb * 4 + kk) * 4; wgmma_n72_rs_tb0(ab, xa[i], xa[i + 1], xa[i + 2], xa[i + 3], desc((dring + (off >> 4) + kk * 2) + DLO_K, DHI_SW128), (kb | kk) != 0); }
        wg_commit();
      };
      normalise(0);
      if (wg == 0) {
#pragma unroll
        for (int kb = 1; kb < 9; kb++) normalise(kb);
        bar_sync(NB_STATS, 256);
      }
#pragma unroll
      for (int kb = 0; kb < 9; kb++) {
        if ((kb & 3) == 0) mbar_wait(bars + 8 * (B_BU + (kb >> 2)), 0);
        bu(kb, kb < 8 ? OFF_BU0 + kb * 9216 : OFF_BU1);
        if (wg == 0) residual(kb);
        else if (kb < 8) normalise(kb + 1);
      }
      wg_wait<0>();
      if (w4 == 0) { if (elect()) mbar_arrive(bars + 8 * B_RING); }
      keep(ab);
      dump(0);
#pragma unroll
      for (int kb = 0; kb < 9; kb++) {
        if (kb == 4) mbar_wait(bars + 8 * (B_BU + 3), 0);
        bu(kb, kb < 4 ? OFF_BU1 + (kb + 1) * 9216 : OFF_BU2 + (kb - 4) * 9216);
        if (wg == 1) residual(kb);
        if (kb == 5) { wg_wait<2>(); if (w4 == 0) { if (elect()) mbar_arrive(bars + 8 * (B_RING + 1)); } }
      }
      wg_wait<0>();
      keep(ab);
      dump(1);
      bar_arrive(NB_DUMP, 352);
    }

    float acc[64];
    {
      const uint32_t ha = sb + OFF_H + (threadIdx.x & 127) * 16, hblk = wg ? HBLK1 : HBLK0;
      auto glu = [&](int i) {
        return pack_bf16(fmaf(acc[32 + 2 * i], tanh_fast(acc[2 * i]), acc[32 + 2 * i]), fmaf(acc[33 + 2 * i], tanh_fast(acc[2 * i + 1]), acc[33 + 2 * i]));
      };
      for (int c = 0; c < 8; c++) {
        if (wg == 1) bar_sync(NB_SKEW, 256);
#pragma unroll
        for (int kb = 0; kb < 9; kb++) {
          if (kb == 6 && c == 3) nst = 7;
          if (kb == 5 && c == 7) nst = 6;
          stage_begin();
#pragma unroll
          for (int kk = 0; kk < 4; kk++) { const int i = (kb * 4 + kk) * 4; wgmma_n128_rs_tb1(acc, xa[i], xa[i + 1], xa[i + 2], xa[i + 3], desc((dlo + kk * 128) + DLO_MN, DHI_SW128), (kb | kk) != 0); }
          if (kb == SKEW - 1 && wg == 0) bar_arrive(NB_SKEW, 256);
          if (kb == 8 && c >= 3 && c != 6) mbar_wait(bars + 8 * (c == 3 ? B_EMPTY + 7 : c == 7 ? B_EMPTY + 6 : B_SCAN - 4 + c), c == 3);
          stage_end(kb > 0);
        }
        wg_wait<0>();
        release(prev);
        keep(acc);
        const uint32_t hc = ha + ((hblk >> (4 * c)) & 15) * 8192;
#pragma unroll
        for (int i = 0; i < 4; i++) sts128(hc + i * 2048, glu(4 * i), glu(4 * i + 1), glu(4 * i + 2), glu(4 * i + 3));
      }
      if (wg == 1) bar_sync(NB_SKEW, 256);
#pragma unroll
      for (int kb = 0; kb < 9; kb++) {
        stage_begin();
#pragma unroll
        for (int kk = 0; kk < 4; kk++) { const int i = (kb * 4 + kk) * 4; wgmma_n128_rs_tb1(acc, xa[i], xa[i + 1], xa[i + 2], xa[i + 3], desc((dlo + kk * 128) + DLO_MN, DHI_SW128), (kb | kk) != 0); }
        if (kb == SKEW - 1 && wg == 0) bar_arrive(NB_SKEW, 256);
        stage_end(kb > 0);
        if (kb > 0) {
          const uint32_t hc = ha + ((hblk >> (4 * (kb - 1))) & 15) * 8192;
#pragma unroll
          for (int i = 4 * (kb - 1); i < 4 * kb; i++) lds128_inplace(hc + (i & 3) * 2048, xa[4 * i], xa[4 * i + 1], xa[4 * i + 2], xa[4 * i + 3]);
        }
      }
      asm volatile("fence.proxy.async.shared::cta;" ::: "memory");
      bar_arrive(NB_HFREE, 288);
      wg_wait<0>();
      release(prev);
      keep(acc);
#pragma unroll
      for (int i = 0; i < 16; i++) xa[128 + i] = glu(i);
    }

    const uint32_t dhs = (((sb + OFF_HS + wg * HS_MAIN) & 0x3FFFF) >> 4) | DLO_HS, drem = DLO_HS + wg * (HS_REM >> 4);
    const int rp = (g >> 2) + 2 * (g & 3);
    const uint32_t so = w4 * 2048 + rp * 128 + (q & 1) * 8, sx = ((q >> 1) ^ rp) << 4;
    const uint32_t rcv = sb + OFF_STG + wg * 32768 + 16384 + w4 * 2048 + lane * 16;
    auto staged = [&]() {
      asm volatile("fence.proxy.async.shared::cta;" ::: "memory");
      __syncwarp();
      if (elect()) mbar_arrive(bars + 8 * (B_SFULL + wg));
    };
    auto half_tile = [&](const bool first, const int kind) {
      float a2[32];
      if (wg == 1) { if (!first) staged(); bar_sync(NB_SKEW, 256); }
      const uint32_t ph0 = ph;
      uint32_t d4;
#pragma unroll
      for (int kp = 0; kp < 5; kp++) {
        stage_begin();
#pragma unroll
        for (int kk = 0; kk < (kp < 4 ? 8 : 4); kk++) { const int i = (kp * 8 + kk) * 4; wgmma_n64_rs_tb1(a2, xa[i], xa[i + 1], xa[i + 2], xa[i + 3], desc((dlo + kk * 128) + DLO_MN, DHI_SW128), (kp | kk) != 0); }
        if (kp == 2 && wg == 0) bar_arrive(NB_SKEW, 256);
        d4 = dlo;
        stage_end(kp > 0);
        if (kp == 0 && !first && wg == 0) staged();
      }
      if (first) mbar_wait(bars + 8 * B_HSFULL, 0);
      stage_begin();
#pragma unroll
      for (int kk = 0; kk < 8; kk++) wgmma_n64_ss_tb0(a2, desc(dhs + kk * (2 * HS_LBO >> 4), DHI_NONE), desc((dlo + (kk >> 2) * 512 + (kk & 3) * 2) + DLO_K, DHI_SW128), 1);
      wgmma_n64_ss_tb0(a2, desc(d4 + 640 + drem, DHI_NONE), desc((d4 + 512) | ((1024 >> 4) << 16), DHI_NONE), 1);
      wg_commit();
      if (!first) {
        if (kind == 1) mbar_wait(bars + 8 * (B_EMPTY + wg), ph0 ^ 1);
        if (kind == 2) { mbar_wait(bars + 8 * (B_SFREE + wg), 1); mbar_wait(bars + 8 * (B_RFULL + wg), 1); }
      }
      wg_wait<0>();
      release(prev); release(s); advance();
      keep(a2);
      if (!first && kind >= 2) {
#pragma unroll
        for (int i = 0; i < 4; i++) {
          uint32_t v[4];
          lds128(rcv + (kind & 1) * 8192 + i * 512, v[0], v[1], v[2], v[3]);
#pragma unroll
          for (int e = 0; e < 4; e++) { a2[8 * i + 2 * e] += bflo(v[e]); a2[8 * i + 2 * e + 1] += bfhi(v[e]); }
        }
        __syncwarp();
      }
      const uint32_t stg = (!first && kind == 1 ? sb + wg * SLOT : sb + OFF_STG + wg * 32768 + (kind == 3 ? 16384 : 0)) + so;
#pragma unroll
      for (int i = 0; i < 8; i++) {
        const uint32_t a = stg + (i >> 2) * 8192 + (sx ^ ((i & 3) << 5));
        sts64f(a, a2[4 * i], a2[4 * i + 1]);
        sts64f(a + 1024, a2[4 * i + 2], a2[4 * i + 3]);
      }
    };
    if (rank) half_tile(true, 0);
    for (int t = 0; t < 4 - rank; t++) {
      if (wg == 1) { if (t + rank > 0) staged(); bar_sync(NB_SKEW, 256); }
#pragma unroll
      for (int kb = 0; kb < 9; kb++) {
        if ((kb == 5 && t == 0 && rank) || (kb == 1 && t == 1)) nst = NST + 1;
        if (t == 1 && ((kb == 1 && rank) || kb == 7)) nst = NST + 2;
        stage_begin();
#pragma unroll
        for (int kk = 0; kk < 4; kk++) { const int i = (kb * 4 + kk) * 4; wgmma_n128_rs_tb1(acc, xa[i], xa[i + 1], xa[i + 2], xa[i + 3], desc((dlo + kk * 128) + DLO_MN, DHI_SW128), (kb | kk) != 0); }
        if (kb == SKEW - 1 && wg == 0) bar_arrive(NB_SKEW, 256);
        stage_end(kb > 0);
        if (kb == 3 && t + rank > 0 && wg == 0) staged();
      }
      if (t == 0) mbar_wait(bars + 8 * B_HSFULL, 0);
      stage_begin();
#pragma unroll
      for (int kk = 0; kk < 4; kk++) wgmma_n128_ss_tb0(acc, desc(dhs + kk * (2 * HS_LBO >> 4), DHI_NONE), desc((dlo + kk * 2) + DLO_K, DHI_SW128), 1);
      stage_end(true);
      stage_begin();
#pragma unroll
      for (int kk = 0; kk < 4; kk++) wgmma_n128_ss_tb0(acc, desc(dhs + (4 + kk) * (2 * HS_LBO >> 4), DHI_NONE), desc((dlo + kk * 2) + DLO_K, DHI_SW128), 1);
      const int s_im = s;
      advance();
      stage_begin();
      wgmma_n128_ss_tb0(acc, desc(dlo + 256 + drem, DHI_NONE), desc(dlo | ((2048 >> 4) << 16), DHI_NONE), 1);
      stage_end(true);
      if (t + rank > 0) mbar_wait(bars + 8 * (B_SFREE + wg), (t + rank - 1) & 1);
      uint32_t pv[8];
      if (t & 1) {
        mbar_wait(bars + 8 * (B_RFULL + wg), t >> 1);
#pragma unroll
        for (int i = 0; i < 2; i++) lds128(rcv + i * 512, pv[4 * i], pv[4 * i + 1], pv[4 * i + 2], pv[4 * i + 3]);
      }
      wg_wait<0>();
      release(s_im); release(prev);
      keep(acc);
      if (t & 1) {
        const uint32_t stg = sb + OFF_STG + wg * 32768 + so;
#pragma unroll
        for (int hh = 0; hh < 2; hh++) {
#pragma unroll
          for (int i = 4 * hh; i < 4 * hh + 4; i++) {
            uint32_t v[4];
            if (i < 2) { v[0] = pv[4 * i]; v[1] = pv[4 * i + 1]; v[2] = pv[4 * i + 2]; v[3] = pv[4 * i + 3]; }
            else lds128(rcv + hh * 8192 + (i & 3) * 512, v[0], v[1], v[2], v[3]);
#pragma unroll
            for (int e = 0; e < 4; e++) { acc[8 * i + 2 * e] += bflo(v[e]); acc[8 * i + 2 * e + 1] += bfhi(v[e]); }
          }
          __syncwarp();
#pragma unroll
          for (int i = 8 * hh; i < 8 * hh + 8; i++) {
            const uint32_t a = stg + (i >> 2) * 8192 + (sx ^ ((i & 3) << 5));
            sts64f(a, acc[4 * i], acc[4 * i + 1]);
            sts64f(a + 1024, acc[4 * i + 2], acc[4 * i + 3]);
          }
        }
      } else {
#pragma unroll
        for (int i = 0; i < 8; i++)
          sts128(rcv - 16384 + (i >> 2) * 8192 + (i & 3) * 512, pack_bf16(acc[8 * i], acc[8 * i + 1]), pack_bf16(acc[8 * i + 2], acc[8 * i + 3]),
                 pack_bf16(acc[8 * i + 4], acc[8 * i + 5]), pack_bf16(acc[8 * i + 6], acc[8 * i + 7]));
      }
    }
#pragma unroll 1
    for (int kind = 1 + rank; kind < 2 + 2 * rank; kind++) half_tile(false, kind);
    staged();
  }
}

typedef CUresult (*EncodeFn)(CUtensorMap*, CUtensorMapDataType, cuuint32_t, void*, const cuuint64_t*, const cuuint64_t*, const cuuint32_t*,
                             const cuuint32_t*, CUtensorMapInterleave, CUtensorMapSwizzle, CUtensorMapL2promotion, CUtensorMapFloatOOBfill);

void map2d(EncodeFn enc, CUtensorMap* tm, const void* p, uint64_t cols, uint64_t rows, uint32_t bc, uint32_t br, CUtensorMapSwizzle sw) {
  cuuint64_t gd[2] = {cols, rows}, gs[1] = {cols * 2};
  cuuint32_t bd[2] = {bc, br}, es[2] = {1, 1};
  enc(tm, CU_TENSOR_MAP_DATA_TYPE_BFLOAT16, 2, (void*)p, gd, gs, bd, es, CU_TENSOR_MAP_INTERLEAVE_NONE, sw,
      sw == CU_TENSOR_MAP_SWIZZLE_128B ? CU_TENSOR_MAP_L2_PROMOTION_L2_128B : CU_TENSOR_MAP_L2_PROMOTION_NONE, CU_TENSOR_MAP_FLOAT_OOB_FILL_NONE);
}

}

extern "C" void kernel_launch(void* const* d_in, const int* in_sizes, int n_in, void* d_out, int out_size) {
  (void)in_sizes; (void)n_in; (void)out_size;
  static EncodeFn enc = nullptr;
  if (!enc) {
    cudaDriverEntryPointQueryResult qr;
    cudaGetDriverEntryPoint("cuTensorMapEncodeTiled", (void**)&enc, cudaEnableDefault, &qr);
    cudaFuncSetAttribute(fused_kernel, cudaFuncAttributeMaxDynamicSharedMemorySize, SMEM_BYTES);
  }
  Params prm;
  const CUtensorMapSwizzle S128 = CU_TENSOR_MAP_SWIZZLE_128B;
  map2d(enc, &prm.tx, d_in[0], kD, kS, 64, 64, S128);
  map2d(enc, &prm.tBre, d_in[3], kD, 576, 64, 72, S128);
  map2d(enc, &prm.tBim, d_in[4], kD, 576, 64, 72, S128);
  map2d(enc, &prm.tCre, d_in[5], 576, kD, 64, 64, S128);
  map2d(enc, &prm.tCim, d_in[6], 576, kD, 64, 64, S128);
  map2d(enc, &prm.tCre8, d_in[5], 576, kD, 8, 64, CU_TENSOR_MAP_SWIZZLE_NONE);
  map2d(enc, &prm.tCim8, d_in[6], 576, kD, 8, 64, CU_TENSOR_MAP_SWIZZLE_NONE);
  map2d(enc, &prm.tWg, d_in[10], kF, kD, 64, 64, S128);
  map2d(enc, &prm.tWu, d_in[11], kF, kD, 64, 64, S128);
  map2d(enc, &prm.tWd, d_in[12], kD, kF, 64, 64, S128);
  {
    cuuint64_t gd[4] = {kD, 2, 4, kS / 8}, gs[3] = {4 * kD * 4, kD * 4, 8 * kD * 4};
    cuuint32_t bd[4] = {32, 2, 4, 8}, es[4] = {1, 1, 1, 1};
    enc(&prm.tOut, CU_TENSOR_MAP_DATA_TYPE_FLOAT32, 4, d_out, gd, gs, bd, es, CU_TENSOR_MAP_INTERLEAVE_NONE, S128, CU_TENSOR_MAP_L2_PROMOTION_NONE,
        CU_TENSOR_MAP_FLOAT_OOB_FILL_NONE);
  }
  prm.lre = (const __nv_bfloat16*)d_in[1];
  prm.lim = (const __nv_bfloat16*)d_in[2];
  prm.bre = (const __nv_bfloat16*)d_in[3];
  prm.bim = (const __nv_bfloat16*)d_in[4];
  prm.cre = (const __nv_bfloat16*)d_in[5];
  prm.cim = (const __nv_bfloat16*)d_in[6];
  prm.wg = (const __nv_bfloat16*)d_in[10];
  prm.wu = (const __nv_bfloat16*)d_in[11];
  prm.wd = (const __nv_bfloat16*)d_in[12];
  prm.ldt = (const __nv_bfloat16*)d_in[7];
  prm.dskip = (const __nv_bfloat16*)d_in[8];
  prm.out = (float*)d_out;

  fused_kernel<<<128, 384, SMEM_BYTES, cudaStreamPerThread>>>(prm);
}
```

```cpp
#include <cuda_runtime.h>
#include <cuda.h>
#include <cuda_bf16.h>
#include <stdint.h>

namespace {

constexpr int kS = 2048, kD = 576, kF = 4608;
constexpr int SKEW = 4;
constexpr int PFD = 18;
constexpr int NST = 6;
constexpr uint32_t SLOT = 16384;
constexpr uint32_t OFF_H = NST * SLOT;
constexpr uint32_t HS_LBO = 1040;
constexpr uint32_t HS_BYTES = 18 * HS_LBO;
constexpr uint32_t OFF_DUMP = OFF_H + 65536 - HS_BYTES;
constexpr uint32_t OFF_STG = OFF_H + 2 * SLOT;
constexpr uint32_t OFF_HS = OFF_STG + 65536;
constexpr uint32_t HS_MAIN = 16 * HS_LBO, HS_REM = 2 * HS_LBO;
constexpr uint32_t OFF_CONST = OFF_H + 131072;
constexpr uint32_t OFF_BAR = OFF_CONST + 4 * 576;
constexpr uint32_t SMEM_BYTES = OFF_BAR + 384 + 384;
static_assert(SMEM_BYTES <= 232448 && OFF_HS + 2 * HS_MAIN <= OFF_BAR, "smem");

enum { B_FULL = 0, B_EMPTY = NST + 2, B_X = 2 * NST + 4, B_X8 = B_X + 8, B_BU  , B_RING = B_BU + 4  , B_SCAN = B_RING + 2  , B_PARK = B_SCAN + 2, B_HFREE, B_HSFULL, B_SFULL,
       B_SFREE = B_SFULL + 2, B_RFULL = B_SFREE + 2, B_RFREE = B_RFULL + 2, B_COUNT = B_RFREE + 2 };
static_assert(B_COUNT * 8 <= 384, "barriers");
enum { NB_SKEW = 1, NB_XDONE = 2  , NB_SCAN = 4, NB_DUMP = 5, NB_HFREE = 6, NB_STATS = 7 };
constexpr uint32_t HBLK0 = 0x07652CB4u, HBLK1 = 0x189A3DEFu;
constexpr uint32_t OFF_BU0 = SLOT, OFF_BU1 = OFF_H, OFF_BU2 = OFF_H + 65536 + 19456;
static_assert(OFF_BU1 + 5 * 9216 <= OFF_DUMP && OFF_BU2 >= OFF_DUMP + 2 * HS_BYTES && OFF_BU2 + 5 * 9216 <= OFF_CONST, "Bu tiles");

struct __align__(64) Params {
  CUtensorMap tx, tBre, tBim, tWg, tWu, tWd, tCre, tCim, tCre8, tCim8, tOut;
  const __nv_bfloat16 *lre, *lim, *bre, *bim, *cre, *cim, *ldt, *dskip, *wg, *wu, *wd;
  float* out;
};

__device__ unsigned g_epoch[128];
__device__ unsigned g_ready[16];
__device__ __align__(256) uint2 g_S[2][16][8][96];
__device__ __align__(128) uint8_t g_hs[128][2 * HS_BYTES];

__device__ __forceinline__ void wgmma_n72_rs_tb0(float (&d)[36], uint32_t a0, uint32_t a1, uint32_t a2, uint32_t a3, uint64_t db, int scale_d) {
  asm volatile("{\n.reg .pred p;\nsetp.ne.b32 p, %41, 0;\n"
    "wgmma.mma_async.sync.aligned.m64n72k16.f32.bf16.bf16 {"
    "%0, %1, %2, %3, %4, %5, %6, %7, %8, %9, %10, %11, %12, %13, %14, %15, "
    "%16, %17, %18, %19, %20, %21, %22, %23, %24, %25, %26, %27, %28, %29, %30, %31, "
    "%32, %33, %34, %35"
    "}, {%36, %37, %38, %39}, %40, p, 1, 1, 0;\n}\n"
    : "+f"(d[0]), "+f"(d[1]), "+f"(d[2]), "+f"(d[3]), "+f"(d[4]), "+f"(d[5]), "+f"(d[6]), "+f"(d[7]),
      "+f"(d[8]), "+f"(d[9]), "+f"(d[10]), "+f"(d[11]), "+f"(d[12]), "+f"(d[13]), "+f"(d[14]), "+f"(d[15]),
      "+f"(d[16]), "+f"(d[17]), "+f"(d[18]), "+f"(d[19]), "+f"(d[20]), "+f"(d[21]), "+f"(d[22]), "+f"(d[23]),
      "+f"(d[24]), "+f"(d[25]), "+f"(d[26]), "+f"(d[27]), "+f"(d[28]), "+f"(d[29]), "+f"(d[30]), "+f"(d[31]),
      "+f"(d[32]), "+f"(d[33]), "+f"(d[34]), "+f"(d[35])
    : "r"(a0), "r"(a1), "r"(a2), "r"(a3), "l"(db), "r"(scale_d));
}
__device__ __forceinline__ void wgmma_n128_rs_tb1(float (&d)[64], uint32_t a0, uint32_t a1, uint32_t a2, uint32_t a3, uint64_t db, int scale_d) {
  asm volatile("{\n.reg .pred p;\nsetp.ne.b32 p, %69, 0;\n"
    "wgmma.mma_async.sync.aligned.m64n128k16.f32.bf16.bf16 {"
    "%0, %1, %2, %3, %4, %5, %6, %7, %8, %9, %10, %11, %12, %13, %14, %15, "
    "%16, %17, %18, %19, %20, %21, %22, %23, %24, %25, %26, %27, %28, %29, %30, %31, "
    "%32, %33, %34, %35, %36, %37, %38, %39, %40, %41, %42, %43, %44, %45, %46, %47, "
    "%48, %49, %50, %51, %52, %53, %54, %55, %56, %57, %58, %59, %60, %61, %62, %63"
    "}, {%64, %65, %66, %67}, %68, p, 1, 1, 1;\n}\n"
    : "+f"(d[0]), "+f"(d[1]), "+f"(d[2]), "+f"(d[3]), "+f"(d[4]), "+f"(d[5]), "+f"(d[6]), "+f"(d[7]),
      "+f"(d[8]), "+f"(d[9]), "+f"(d[10]), "+f"(d[11]), "+f"(d[12]), "+f"(d[13]), "+f"(d[14]), "+f"(d[15]),
      "+f"(d[16]), "+f"(d[17]), "+f"(d[18]), "+f"(d[19]), "+f"(d[20]), "+f"(d[21]), "+f"(d[22]), "+f"(d[23]),
      "+f"(d[24]), "+f"(d[25]), "+f"(d[26]), "+f"(d[27]), "+f"(d[28]), "+f"(d[29]), "+f"(d[30]), "+f"(d[31]),
      "+f"(d[32]), "+f"(d[33]), "+f"(d[34]), "+f"(d[35]), "+f"(d[36]), "+f"(d[37]), "+f"(d[38]), "+f"(d[39]),
      "+f"(d[40]), "+f"(d[41]), "+f"(d[42]), "+f"(d[43]), "+f"(d[44]), "+f"(d[45]), "+f"(d[46]), "+f"(d[47]),
      "+f"(d[48]), "+f"(d[49]), "+f"(d[50]), "+f"(d[51]), "+f"(d[52]), "+f"(d[53]), "+f"(d[54]), "+f"(d[55]),
      "+f"(d[56]), "+f"(d[57]), "+f"(d[58]), "+f"(d[59]), "+f"(d[60]), "+f"(d[61]), "+f"(d[62]), "+f"(d[63])
    : "r"(a0), "r"(a1), "r"(a2), "r"(a3), "l"(db), "r"(scale_d));
}
__device__ __forceinline__ void wgmma_n128_ss_tb0(float (&d)[64], uint64_t da, uint64_t db, int scale_d) {
  asm volatile("{\n.reg .pred p;\nsetp.ne.b32 p, %66, 0;\n"
    "wgmma.mma_async.sync.aligned.m64n128k16.f32.bf16.bf16 {"
    "%0, %1, %2, %3, %4, %5, %6, %7, %8, %9, %10, %11, %12, %13, %14, %15, "
    "%16, %17, %18, %19, %20, %21, %22, %23, %24, %25, %26, %27, %28, %29, %30, %31, "
    "%32, %33, %34, %35, %36, %37, %38, %39, %40, %41, %42, %43, %44, %45, %46, %47, "
    "%48, %49, %50, %51, %52, %53, %54, %55, %56, %57, %58, %59, %60, %61, %62, %63"
    "}, %64, %65, p, 1, 1, 0, 0;\n}\n"
    : "+f"(d[0]), "+f"(d[1]), "+f"(d[2]), "+f"(d[3]), "+f"(d[4]), "+f"(d[5]), "+f"(d[6]), "+f"(d[7]),
      "+f"(d[8]), "+f"(d[9]), "+f"(d[10]), "+f"(d[11]), "+f"(d[12]), "+f"(d[13]), "+f"(d[14]), "+f"(d[15]),
      "+f"(d[16]), "+f"(d[17]), "+f"(d[18]), "+f"(d[19]), "+f"(d[20]), "+f"(d[21]), "+f"(d[22]), "+f"(d[23]),
      "+f"(d[24]), "+f"(d[25]), "+f"(d[26]), "+f"(d[27]), "+f"(d[28]), "+f"(d[29]), "+f"(d[30]), "+f"(d[31]),
      "+f"(d[32]), "+f"(d[33]), "+f"(d[34]), "+f"(d[35]), "+f"(d[36]), "+f"(d[37]), "+f"(d[38]), "+f"(d[39]),
      "+f"(d[40]), "+f"(d[41]), "+f"(d[42]), "+f"(d[43]), "+f"(d[44]), "+f"(d[45]), "+f"(d[46]), "+f"(d[47]),
      "+f"(d[48]), "+f"(d[49]), "+f"(d[50]), "+f"(d[51]), "+f"(d[52]), "+f"(d[53]), "+f"(d[54]), "+f"(d[55]),
      "+f"(d[56]), "+f"(d[57]), "+f"(d[58]), "+f"(d[59]), "+f"(d[60]), "+f"(d[61]), "+f"(d[62]), "+f"(d[63])
    : "l"(da), "l"(db), "r"(scale_d));
}
__device__ __forceinline__ void wgmma_n64_rs_tb1(float (&d)[32], uint32_t a0, uint32_t a1, uint32_t a2, uint32_t a3, uint64_t db, int scale_d) {
  asm volatile("{\n.reg .pred p;\nsetp.ne.b32 p, %37, 0;\n"
    "wgmma.mma_async.sync.aligned.m64n64k16.f32.bf16.bf16 {"
    "%0, %1, %2, %3, %4, %5, %6, %7, %8, %9, %10, %11, %12, %13, %14, %15, "
    "%16, %17, %18, %19, %20, %21, %22, %23, %24, %25, %26, %27, %28, %29, %30, %31"
    "}, {%32, %33, %34, %35}, %36, p, 1, 1, 1;\n}\n"
    : "+f"(d[0]), "+f"(d[1]), "+f"(d[2]), "+f"(d[3]), "+f"(d[4]), "+f"(d[5]), "+f"(d[6]), "+f"(d[7]),
      "+f"(d[8]), "+f"(d[9]), "+f"(d[10]), "+f"(d[11]), "+f"(d[12]), "+f"(d[13]), "+f"(d[14]), "+f"(d[15]),
      "+f"(d[16]), "+f"(d[17]), "+f"(d[18]), "+f"(d[19]), "+f"(d[20]), "+f"(d[21]), "+f"(d[22]), "+f"(d[23]),
      "+f"(d[24]), "+f"(d[25]), "+f"(d[26]), "+f"(d[27]), "+f"(d[28]), "+f"(d[29]), "+f"(d[30]), "+f"(d[31])
    : "r"(a0), "r"(a1), "r"(a2), "r"(a3), "l"(db), "r"(scale_d));
}
__device__ __forceinline__ void wgmma_n64_ss_tb0(float (&d)[32], uint64_t da, uint64_t db, int scale_d) {
  asm volatile("{\n.reg .pred p;\nsetp.ne.b32 p, %34, 0;\n"
    "wgmma.mma_async.sync.aligned.m64n64k16.f32.bf16.bf16 {"
    "%0, %1, %2, %3, %4, %5, %6, %7, %8, %9, %10, %11, %12, %13, %14, %15, "
    "%16, %17, %18, %19, %20, %21, %22, %23, %24, %25, %26, %27, %28, %29, %30, %31"
    "}, %32, %33, p, 1, 1, 0, 0;\n}\n"
    : "+f"(d[0]), "+f"(d[1]), "+f"(d[2]), "+f"(d[3]), "+f"(d[4]), "+f"(d[5]), "+f"(d[6]), "+f"(d[7]),
      "+f"(d[8]), "+f"(d[9]), "+f"(d[10]), "+f"(d[11]), "+f"(d[12]), "+f"(d[13]), "+f"(d[14]), "+f"(d[15]),
      "+f"(d[16]), "+f"(d[17]), "+f"(d[18]), "+f"(d[19]), "+f"(d[20]), "+f"(d[21]), "+f"(d[22]), "+f"(d[23]),
      "+f"(d[24]), "+f"(d[25]), "+f"(d[26]), "+f"(d[27]), "+f"(d[28]), "+f"(d[29]), "+f"(d[30]), "+f"(d[31])
    : "l"(da), "l"(db), "r"(scale_d));
}

__device__ __forceinline__ bool elect() {
  uint32_t p;
  asm volatile("{.reg .pred q; elect.sync _|q, 0xffffffff; selp.u32 %0,1,0,q;}" : "=r"(p));
  return p;
}
__device__ __forceinline__ void mbar_init(uint32_t bar, uint32_t cnt) { asm volatile("mbarrier.init.shared::cta.b64 [%0], %1;" ::"r"(bar), "r"(cnt) : "memory"); }
__device__ __forceinline__ void mbar_expect(uint32_t bar, uint32_t bytes) { asm volatile("mbarrier.arrive.expect_tx.shared::cta.b64 _, [%0], %1;" ::"r"(bar), "r"(bytes) : "memory"); }
__device__ __forceinline__ void mbar_arrive(uint32_t bar) { asm volatile("mbarrier.arrive.shared::cta.b64 _, [%0];" ::"r"(bar) : "memory"); }
__device__ __forceinline__ void mbar_arrive_cta(uint32_t bar, uint32_t cta) {
  asm volatile("{.reg .b32 ra; mapa.shared::cluster.u32 ra, %0, %1; mbarrier.arrive.shared::cluster.b64 _, [ra];}" ::"r"(bar), "r"(cta) : "memory");
}
__device__ __forceinline__ void mbar_wait(uint32_t bar, uint32_t parity) {
  asm volatile(
      "{\n.reg .pred p;\n.reg .u32 c;\nmov.u32 c, 0x100000;\n"
      "LAB_WAIT:\nmbarrier.try_wait.parity.shared::cta.b64 p, [%0], %1;\n@p bra DONE;\n"
      "nanosleep.u32 0;\nsub.u32 c, c, 1;\nsetp.ne.u32 p, c, 0;\n@p bra LAB_WAIT;\ntrap;\nDONE:\n}" ::"r"(bar), "r"(parity) : "memory");
}
__device__ __forceinline__ void bar_sync(int id, int n) { asm volatile("bar.sync %0, %1;" ::"r"(id), "r"(n) : "memory"); }
__device__ __forceinline__ void bar_arrive(int id, int n) { asm volatile("bar.arrive %0, %1;" ::"r"(id), "r"(n) : "memory"); }
__device__ __forceinline__ void wg_fence() { asm volatile("wgmma.fence.sync.aligned;" ::: "memory"); }
__device__ __forceinline__ void wg_commit() { asm volatile("wgmma.commit_group.sync.aligned;" ::: "memory"); }
template <int N> __device__ __forceinline__ void wg_wait() { asm volatile("wgmma.wait_group.sync.aligned %0;" ::"n"(N) : "memory"); }
__device__ __forceinline__ void tma2d(uint32_t dst, const CUtensorMap* tm, uint32_t bar, int c0, int c1) {
  asm volatile("cp.async.bulk.tensor.2d.shared::cluster.global.mbarrier::complete_tx::bytes [%0], [%1,{%3,%4}], [%2];" ::"r"(dst), "l"(tm), "r"(bar), "r"(c0), "r"(c1) : "memory");
}
__device__ __forceinline__ void tma2d_mc(uint32_t dst, const CUtensorMap* tm, uint32_t bar, int c0, int c1) {
  asm volatile("cp.async.bulk.tensor.2d.shared::cluster.global.mbarrier::complete_tx::bytes.multicast::cluster [%0], [%1,{%3,%4}], [%2], %5;" ::"r"(dst), "l"(tm), "r"(bar), "r"(c0), "r"(c1), "h"((uint16_t)3) : "memory");
}
__device__ __forceinline__ void l2_prefetch_line(const void* p) { asm volatile("prefetch.global.L2 [%0];" ::"l"(p)); }
__device__ __forceinline__ uint64_t desc(uint32_t lo, uint32_t hi) { return ((uint64_t)hi << 32) | lo; }
constexpr uint32_t DHI_SW128 = (1024 >> 4) | (1u << 30);
constexpr uint32_t DHI_NONE = (128 >> 4);
constexpr uint32_t DLO_HS = (HS_LBO >> 4) << 16;
constexpr uint32_t DLO_MN = (8192 >> 4) << 16;
constexpr uint32_t DLO_K = 1u << 16;
__device__ __forceinline__ float tanh_fast(float x) { float y; asm("tanh.approx.f32 %0, %1;" : "=f"(y) : "f"(x)); return y; }
__device__ __forceinline__ uint32_t pack_bf16(float lo, float hi) { uint32_t r; asm("cvt.rn.bf16x2.f32 %0, %1, %2;" : "=r"(r) : "f"(hi), "f"(lo)); return r; }
__device__ __forceinline__ float rbf(float x) { return __uint_as_float(pack_bf16(0.f, x)); }
__device__ __forceinline__ void mma16816(float (&c)[4], uint32_t a0, uint32_t a1, uint32_t a2, uint32_t a3, uint32_t b0, uint32_t b1) {
  asm volatile("mma.sync.aligned.m16n8k16.row.col.f32.bf16.bf16.f32 {%0,%1,%2,%3}, {%4,%5,%6,%7}, {%8,%9}, {%0,%1,%2,%3};"
               : "+f"(c[0]), "+f"(c[1]), "+f"(c[2]), "+f"(c[3]) : "r"(a0), "r"(a1), "r"(a2), "r"(a3), "r"(b0), "r"(b1));
}
__device__ __forceinline__ void sts128(uint32_t a, uint32_t x, uint32_t y, uint32_t z, uint32_t w) {
  asm volatile("st.shared.v4.b32 [%0], {%1,%2,%3,%4};" ::"r"(a), "r"(x), "r"(y), "r"(z), "r"(w) : "memory");
}
__device__ __forceinline__ void sts64f(uint32_t a, float x, float y) { asm volatile("st.shared.v2.f32 [%0], {%1,%2};" ::"r"(a), "f"(x), "f"(y) : "memory"); }
__device__ __forceinline__ float2 lds64f(uint32_t a) { float2 v; asm volatile("ld.shared.v2.f32 {%0,%1}, [%2];" : "=f"(v.x), "=f"(v.y) : "r"(a) : "memory"); return v; }
__device__ __forceinline__ uint32_t lds32(uint32_t a) { uint32_t v; asm volatile("ld.shared.b32 %0, [%1];" : "=r"(v) : "r"(a) : "memory"); return v; }
__device__ __forceinline__ void lds128(uint32_t a, uint32_t& x, uint32_t& y, uint32_t& z, uint32_t& w) {
  asm volatile("ld.shared.v4.b32 {%0,%1,%2,%3}, [%4];" : "=r"(x), "=r"(y), "=r"(z), "=r"(w) : "r"(a) : "memory");
}
__device__ __forceinline__ void lds128_inplace(uint32_t a, uint32_t& x, uint32_t& y, uint32_t& z, uint32_t& w) {
  asm volatile("{.reg .pred p; .reg .u32 n; mov.u32 n, %%ntid.y; setp.ne.u32 p, n, 0; @p ld.shared.v4.b32 {%0,%1,%2,%3}, [%4];}" : "+r"(x), "+r"(y), "+r"(z), "+r"(w) : "r"(a) : "memory");
}
__device__ __forceinline__ float bflo(uint32_t v) { return __uint_as_float(v << 16); }
__device__ __forceinline__ float bfhi(uint32_t v) { return __uint_as_float(v & 0xffff0000u); }
template <int N> __device__ __forceinline__ void keep(float (&a)[N]) {
#pragma unroll
  for (int i = 0; i < N; i++) asm volatile("" : "+f"(a[i])::"memory");
}

__global__ void __cluster_dims__(2, 1, 1) __launch_bounds__(384, 1) fused_kernel(const __grid_constant__ Params prm) {
  extern __shared__ __align__(1024) uint8_t smem[];
  const int warp = __shfl_sync(0xffffffffu, threadIdx.x >> 5, 0);
  const uint32_t sb0 = (uint32_t)__cvta_generic_to_shared(smem);
  const int j = blockIdx.x & 7, m = blockIdx.x >> 3, rank = j & 1;
  auto smem_base = [&]() { return __shfl_sync(0xffffffffu, sb0 + (threadIdx.x & 31), 0); };

  if (threadIdx.x == 320) asm volatile("prefetch.tensormap [%0];" ::"l"(&prm.tx) : "memory");
  if (warp == 0) {
    if (elect()) {
#pragma unroll
      for (int i = B_X8; i >= B_X; i--) mbar_init(sb0 + OFF_BAR + 8 * i, 1);
      asm volatile("fence.mbarrier_init.release.cluster;" ::: "memory");
    }
    __syncwarp();
  }
  asm volatile("barrier.cluster.arrive.relaxed.aligned;" ::: "memory");
  if (warp == 0) {
    const uint32_t xb = sb0 + OFF_BAR;
    if (elect()) {
      mbar_expect(xb + 8 * B_X8, 16384);
      tma2d(sb0, &prm.tx, xb + 8 * B_X8, 512, m * 128);
      tma2d(sb0 + 8192, &prm.tx, xb + 8 * B_X8, 512, m * 128 + 64);
#pragma unroll
      for (int i = 0; i < 4; i++) {
        mbar_expect(xb + 8 * (B_X + i), 16384);
        tma2d(sb0 + OFF_H + i * 16384, &prm.tx, xb + 8 * (B_X + i), i * 128, m * 128);
        tma2d(sb0 + OFF_H + i * 16384 + 8192, &prm.tx, xb + 8 * (B_X + i), i * 128 + 64, m * 128);
      }
    }
    __syncwarp();
  }
  asm volatile("barrier.cluster.wait.aligned;" ::: "memory");
  if (warp == 8 || warp == 9) {
    if (elect()) {
      if (warp == 8) {
#pragma unroll
        for (int i = 0; i < B_X; i++) mbar_init(sb0 + OFF_BAR + 8 * i, i >= B_EMPTY ? 2 : 1);
      } else {
#pragma unroll
        for (int i = B_X8 + 1; i < B_COUNT; i++) mbar_init(sb0 + OFF_BAR + 8 * i, (i >= B_SFULL && i < B_SFULL + 2) ? 4 : (i == B_RING || i == B_RING + 1) ? 2 : 1);
        if (sb0 & 1023) __trap();
      }
      asm volatile("fence.mbarrier_init.release.cluster;" ::: "memory");
    }
    __syncwarp();
  }
  if (warp == 0) {
    const uint32_t xb = sb0 + OFF_BAR;
    const bool e = elect();
#pragma unroll
    for (int i = 0; i < 4; i++) {
      const int kb = i * 2 + rank;
      if (e) { mbar_expect(xb + 8 * (B_X + 4 + i), 16384); tma2d_mc(sb0 + OFF_H + 65536 + kb * 8192, &prm.tx, xb + 8 * (B_X + 4 + i), kb * 64, m * 128 + 64); }
    }
    __syncwarp();
  }
  asm volatile("barrier.cluster.arrive.relaxed.aligned;\nbarrier.cluster.wait.aligned;" ::: "memory");

  if (warp >= 8) {
    asm volatile("setmaxnreg.dec.sync.aligned.u32 24;");
    if (warp == 8) {
      const uint32_t sb = smem_base(), bars = sb + OFF_BAR;
      bool e;
      int s = 0, nst = NST + 2; uint32_t ph = 1;
      uint32_t dst, fb;
      auto acquire = [&](uint32_t bytes) {
        mbar_wait(bars + 8 * (B_EMPTY + s), ph);
        fb = bars + 8 * (B_FULL + s); dst = sb + s * SLOT;
        e = elect();
        if (e) mbar_expect(fb, bytes);
        if (++s == nst) { s = 0; ph ^= 1; }
      };
      auto box = [&](const CUtensorMap* t, uint32_t o, int a, int b) { if (e) tma2d(dst + o, t, fb, a, b); };
      auto hs_rem = [&](uint32_t o) {
        if (e) asm volatile("cp.async.bulk.shared::cluster.global.mbarrier::complete_tx::bytes [%0], [%1], %2, [%3];" ::"r"(dst + o),
                            "l"(&g_hs[blockIdx.x][2 * HS_MAIN]), "r"(2 * HS_REM), "r"(fb) : "memory");
      };
      const int lane = threadIdx.x & 31;
      const char* pf = lane < 8 ? (const char*)(lane & 4 ? prm.wu : prm.wg) + ((size_t)(m * 4 + (lane & 3)) * kF + j * 576) * 2
                     : lane < 12 ? (const char*)prm.wd + (size_t)j * 576 * 1152 + (m * 324 + (lane & 3)) * 128
                                 : (const char*)(lane & 1 ? prm.cim : prm.cre) + (size_t)blockIdx.x * 5184;
      int pk = 0, pleft = 81;
      auto prefetch = [&]() {
        if (pleft > 0) {
          if (lane < 14) l2_prefetch_line(pf);
          pf += lane < 8 ? (pk == 8 ? 128 - 8 * 64 * kF * 2 : 64 * kF * 2) : lane < 12 ? 512 : 64;
          pk = pk == 8 ? 0 : pk + 1;
          pleft--;
        }
      };
      mbar_wait(bars + 8 * B_X8, 0);
      e = elect();
#pragma unroll 1
      for (int kb = 0; kb < 8; kb++) {
        fb = bars + 8 * (B_BU + (kb >> 2));
        if (e) { if ((kb & 3) == 0) mbar_expect(fb, 4 * 9216); tma2d(sb + OFF_BU0 + kb * 9216, &prm.tBre, fb, kb * 64, j * 72); }
      }
      bar_sync(NB_XDONE, 160);
      fb = bars + 8 * (B_BU + 2);
      if (e) { mbar_expect(fb, 5 * 9216); tma2d(sb + OFF_BU1, &prm.tBre, fb, 512, j * 72); }
#pragma unroll 1
      for (int kb = 0; kb < 4; kb++) if (e) tma2d(sb + OFF_BU1 + (kb + 1) * 9216, &prm.tBim, fb, kb * 64, j * 72);
      bar_sync(NB_XDONE + 1, 160);
      fb = bars + 8 * (B_BU + 3);
      if (e) mbar_expect(fb, 5 * 9216);
#pragma unroll 1
      for (int kb = 4; kb < 9; kb++) if (e) tma2d(sb + OFF_BU2 + (kb - 4) * 9216, &prm.tBim, fb, kb * 64, j * 72);
#pragma unroll 1
      for (int i = 0; i < PFD; i++) prefetch();
      mbar_wait(bars + 8 * B_RING, 0);
#pragma unroll 1
      for (int c = 0; c < 9; c++) {
        const int col = j * 576 + c * 64;
#pragma unroll 1
        for (int kb = 0; kb < 9; kb++) {
          if (kb == 6 && c == 0) mbar_wait(bars + 8 * (B_RING + 1), 0);
          if (kb == 6 && c == 3) nst = 7;
          if (kb == 5 && c == 7) nst = 6;
          acquire(16384); box(&prm.tWg, 0, col, kb * 64); box(&prm.tWu, 8192, col, kb * 64); prefetch();
        }
      }
      auto half_tile = [&](int n0) {
#pragma unroll 1
        for (int kp = 0; kp < 4; kp++) { acquire(16384); box(&prm.tWd, 0, n0, j * 576 + kp * 128); box(&prm.tWd, 8192, n0, j * 576 + kp * 128 + 64); }
        acquire(8192 + 2048 + 2 * HS_REM); box(&prm.tWd, 0, n0, j * 576 + 512); box(&prm.tCre8, 8192, j * 72 + 64, n0); box(&prm.tCim8, 9216, j * 72 + 64, n0); hs_rem(10240);
        acquire(16384); box(&prm.tCre, 0, j * 72, n0); box(&prm.tCim, 8192, j * 72, n0);
      };
      mbar_wait(bars + 8 * B_PARK, 0);
      asm volatile("fence.proxy.async.global;" ::: "memory");
      if (rank) half_tile(512);
#pragma unroll 1
      for (int t = 0; t < 4 - rank; t++) {
        const int n0 = ((rank ^ t ^ 1) & 1) * 256 + (((t >> 1) ^ (j >> 1)) & 1) * 128;
#pragma unroll 1
        for (int kb = 0; kb < 9; kb++) {
          if (rank ? (t == 0 && kb == 5) : (t == 1 && kb == 1)) nst = NST + 1;
          if (t == 1 && kb == (rank ? 1 : 7)) nst = NST + 2;
          if (kb == 3 && t == 0 && rank) mbar_wait(bars + 8 * B_HFREE, 0);
          acquire(16384); box(&prm.tWd, 0, n0, j * 576 + kb * 64); box(&prm.tWd, 8192, n0 + 64, j * 576 + kb * 64);
        }
        if (t == 0) mbar_wait(bars + 8 * B_HFREE, 0);
        acquire(16384); box(&prm.tCre, 0, j * 72, n0); box(&prm.tCre, 8192, j * 72, n0 + 64);
        acquire(16384); box(&prm.tCim, 0, j * 72, n0); box(&prm.tCim, 8192, j * 72, n0 + 64);
        acquire(4096 + 2 * HS_REM); hs_rem(4096);
        box(&prm.tCre8, 0, j * 72 + 64, n0); box(&prm.tCre8, 1024, j * 72 + 64, n0 + 64);
        box(&prm.tCim8, 2048, j * 72 + 64, n0); box(&prm.tCim8, 3072, j * 72 + 64, n0 + 64);
      }
      if (!rank) half_tile(512);
      else {
#pragma unroll 1
        for (int hh = 0; hh < 2; hh++) half_tile(256 + (((j >> 1) ^ 1) & 1) * 128 + hh * 64);
      }
    } else {
      const uint32_t sb = smem_base(), bars = sb + OFF_BAR;
      const int p = min((int)threadIdx.x - 288, 71);
      if (threadIdx.x < 288 + 10) asm volatile("prefetch.tensormap [%0];" ::"l"(&prm.tBre + (threadIdx.x - 288)) : "memory");
      if (warp == 10) {
        const int l = threadIdx.x & 31;
        const char* q = (const char*)(l & 1 ? prm.bim : prm.bre) + (size_t)blockIdx.x * 5184;
        mbar_wait(bars + 8 * B_X8, 0);
#pragma unroll
        for (int i = 0; i < 3; i++) if (i * 16 + (l >> 1) < 42) l2_prefetch_line(q + min((i * 16 + (l >> 1)) * 128, 5183));
      }
      const unsigned epoch = *(volatile unsigned*)&g_epoch[blockIdx.x];
      {
        const int pg = j * 72 + p;
        const float lr = __bfloat162float(prm.lre[pg]), li = __bfloat162float(prm.lim[pg]);
        const float dt = rbf(expf(__bfloat162float(prm.ldt[pg])));
        const float ea = expf(dt * lr);
        float sn, cs;
        sincosf(dt * li, &sn, &cs);
        const float ar = ea * cs, ai = ea * sn;
        float br = ar, bi = ai;
#pragma unroll
        for (int k = 0; k < 6; k++) { const float t = br * br - bi * bi; bi = 2.f * br * bi; br = t; }
        const float nr = ar - 1.f, den = 4.f / (lr * lr + li * li);
        sts64f(sb + OFF_CONST + p * 8, ar, ai);
        sts64f(sb + OFF_CONST + 576 + p * 8, br, bi);
        sts64f(sb + OFF_CONST + 1152 + p * 8, (nr * lr + ai * li) * den, (ai * lr - nr * li) * den);
      }
      bar_sync(NB_DUMP, 352);
      {
        const int lane = threadIdx.x & 31;
        const int half = warp == 11 ? (lane >> 2) & 1 : warp - 9;
        const uint32_t cu = sb + OFF_CONST + (warp == 11 ? 32 + (lane & 3) : lane) * 16;
        uint32_t a0 = sb + OFF_DUMP + half * HS_BYTES + (warp == 11 ? 16 : lane >> 2) * HS_LBO + (lane & 3) * 4;
        asm volatile("" : "+r"(a0));
        const uint32_t di = warp == 11 ? HS_LBO : 8 * HS_LBO;
        float a[4], h[4] = {0.f, 0.f, 0.f, 0.f};
        auto ld4 = [&](uint32_t ad, float (&v)[4]) { asm volatile("ld.shared.v4.f32 {%0,%1,%2,%3}, [%4];" : "=f"(v[0]), "=f"(v[1]), "=f"(v[2]), "=f"(v[3]) : "r"(ad) : "memory"); };
        auto cfma = [&](const float (&c)[4], float r0, float i0, float r1, float i1) {
          const float n0 = fmaf(c[0], h[0], fmaf(-c[1], h[1], r0)), n1 = fmaf(c[2], h[2], fmaf(-c[3], h[3], r1));
          h[1] = fmaf(c[0], h[1], fmaf(c[1], h[0], i0)); h[3] = fmaf(c[2], h[3], fmaf(c[3], h[2], i1));
          h[0] = n0; h[2] = n1;
        };
        ld4(cu, a);
#pragma unroll 1
        for (uint32_t ad = a0; ad != a0 + 1024; ad += 64) {
          uint32_t wr[4], wi[4];
#pragma unroll
          for (int k = 0; k < 4; k++) { wr[k] = lds32(ad + k * 16); wi[k] = lds32(ad + di + k * 16); }
#pragma unroll
          for (int k = 0; k < 4; k++) cfma(a, bflo(wr[k]), bflo(wi[k]), bfhi(wr[k]), bfhi(wi[k]));
        }
        if (half == 0) sts128(cu + 1728, __float_as_uint(h[0]), __float_as_uint(h[1]), __float_as_uint(h[2]), __float_as_uint(h[3]));
        bar_sync(NB_SCAN, 96);
        if (half == 1 && m < 15) {
          float b[4], s1[4] = {h[0], h[1], h[2], h[3]};
          ld4(cu + 576, b); ld4(cu + 1728, h);
          cfma(b, s1[0], s1[1], s1[2], s1[3]);
          uint2* gp = &g_S[epoch & 1][m][j][(cu - sb - OFF_CONST) >> 3];
          asm volatile("st.relaxed.gpu.global.v2.b64 [%0], {%1,%2};" ::"l"(gp), "l"(~(((uint64_t)__float_as_uint(h[1]) << 32) | __float_as_uint(h[0]))),
                       "l"(~(((uint64_t)__float_as_uint(h[3]) << 32) | __float_as_uint(h[2]))) : "memory");
        }
        __syncwarp();
        g_S[(epoch & 1) ^ 1][m][j][p] = make_uint2(0u, 0u);
        {
          const float2 b = lds64f(sb + OFF_CONST + 576 + p * 8);
          const float br = b.x * b.x - b.y * b.y, bi = 2.f * b.x * b.y;
          float hr = 0.f, hi = 0.f;
          const uint2* sp = &g_S[epoch & 1][0][j][p];
#pragma unroll 1
          for (int left = m; left > 0; left -= 3, sp += 3 * 768) {
            uint32_t v[3][2];
            int spins = 0;
            uint32_t ok;
            do {
#pragma unroll
              for (int k = 0; k < 3; k++) {
                v[k][0] = v[k][1] = 0xffffffffu;
                if (k < left) asm volatile("ld.relaxed.gpu.global.v2.b32 {%0,%1}, [%2];" : "=r"(v[k][0]), "=r"(v[k][1]) : "l"(sp + k * 768) : "memory");
              }
              ok = min(min(min(v[0][0], v[0][1]), min(v[1][0], v[1][1])), min(v[2][0], v[2][1]));
              if (++spins > (1 << 22)) __trap();
            } while (ok == 0u);
#pragma unroll
            for (int k = 0; k < 3; k++)
              if (k < left) { const float nr = fmaf(br, hr, fmaf(-bi, hi, __uint_as_float(~v[k][0]))); hi = fmaf(br, hi, fmaf(bi, hr, __uint_as_float(~v[k][1]))); hr = nr; }
          }
          sts64f(sb + OFF_CONST + p * 8, hr, hi);
        }
        __syncwarp();
        bar_sync(NB_SCAN, 96);
        ld4(cu, h);
        uint32_t cr, ci, cn;
        {
          float b[4], s0[4];
          ld4(cu + 576, b); ld4(cu + 1728, s0);
          if (half == 1) cfma(b, s0[0], s0[1], s0[2], s0[3]);
          ld4(cu + 1152, b);
          cr = pack_bf16(b[0], b[2]); ci = pack_bf16(b[1], b[3]); cn = ci ^ 0x80008000u;
        }
        h[1] = -h[1]; h[3] = -h[3];
        __syncwarp();
#pragma unroll 1
        for (uint32_t ad = a0; ad != a0 + 1024; ad += 32) {
          uint32_t wr[2], wi[2];
#pragma unroll
          for (int k = 0; k < 2; k++) { wr[k] = lds32(ad + k * 16); wi[k] = lds32(ad + di + k * 16); }
#pragma unroll
          for (int k = 0; k < 2; k++) {
            const float n0 = fmaf(a[0], h[0], fmaf(a[1], h[1], bflo(wr[k]))), n1 = fmaf(a[2], h[2], fmaf(a[3], h[3], bfhi(wr[k])));
            h[1] = fmaf(a[0], h[1], fmaf(-a[1], h[0], -bflo(wi[k]))); h[3] = fmaf(a[2], h[3], fmaf(-a[3], h[2], -bfhi(wi[k])));
            h[0] = n0; h[2] = n1;
            const uint32_t hr = pack_bf16(h[0], h[2]), hn = pack_bf16(h[1], h[3]);
            uint32_t o0, o1;
            asm("{.reg .b32 t; mul.rn.bf16x2 t, %2, %4; fma.rn.bf16x2 %0, %1, %3, t;}" : "=r"(o0) : "r"(hr), "r"(hn), "r"(cr), "r"(ci));
            asm("{.reg .b32 t; mul.rn.bf16x2 t, %1, %4; fma.rn.bf16x2 %0, %2, %3, t;}" : "=r"(o1) : "r"(hr), "r"(hn), "r"(cr), "r"(cn));
            asm volatile("st.shared.b32 [%0], %1;" ::"r"(ad + k * 16), "r"(o0) : "memory");
            asm volatile("st.shared.b32 [%0], %1;" ::"r"(ad + di + k * 16), "r"(o1) : "memory");
          }
        }
        asm volatile("fence.proxy.async.shared::cta;" ::: "memory");
      }
      bar_sync(NB_SCAN, 96);
      const bool lead = elect();
      if (warp == 9) {
        if (lead) {
#pragma unroll 1
          for (int i = 0; i < 10; i++) {
            const int pc = (0x8654321970ull >> (4 * i)) & 15, w = pc & 1, c4 = pc >> 1;
            asm volatile("cp.async.bulk.global.shared::cta.bulk_group [%0], [%1], %2;" ::"l"(&g_hs[blockIdx.x][c4 < 4 ? w * HS_MAIN + c4 * 4 * HS_LBO : 2 * HS_MAIN + w * HS_REM]),
                         "r"(sb + OFF_DUMP + w * HS_BYTES + c4 * 4 * HS_LBO), "r"(c4 < 4 ? 4 * HS_LBO : HS_REM) : "memory");
            asm volatile("cp.async.bulk.commit_group;\ncp.async.bulk.wait_group.read 0;" ::: "memory");
            if (i == 2) mbar_arrive(bars + 8 * B_SCAN);
          }
          mbar_arrive(bars + 8 * (B_SCAN + 1));
        }
        __syncwarp();
      }
      if (warp == 9) {
        if (lead) {
          __threadfence();
          asm volatile("red.release.gpu.global.add.u32 [%0], 1;" ::"l"(&g_ready[m]) : "memory");
          g_epoch[blockIdx.x] = epoch + 1u;
          asm volatile("cp.async.bulk.wait_group 0;" ::: "memory");
          mbar_arrive(bars + 8 * B_PARK);
        }
        __syncwarp();
        bar_sync(NB_HFREE, 288);
        if (lead) {
          mbar_arrive(bars + 8 * B_HFREE);
          mbar_expect(bars + 8 * B_HSFULL, 2 * HS_MAIN);
          asm volatile("cp.async.bulk.shared::cluster.global.mbarrier::complete_tx::bytes [%0], [%1], %2, [%3];" ::"r"(sb + OFF_HS),
                       "l"(&g_hs[blockIdx.x][0]), "r"(2 * HS_MAIN), "r"(bars + 8 * B_HSFULL) : "memory");
          for (int w = 0; w < 2; w++) mbar_arrive_cta(bars + 8 * (B_RFREE + w), rank ^ 1);
        }
        __syncwarp();
      } else {
        const int w = warp - 10;
        {
          const unsigned target = 8u * (epoch + 1u);
          int spins = 0;
          unsigned v;
          do {
            if (spins) __nanosleep(500);
            asm volatile("ld.relaxed.gpu.global.u32 %0, [%1];" : "=r"(v) : "l"(&g_ready[m]) : "memory");
            if (++spins > (1 << 21)) __trap();
          } while ((int)(v - target) < 0);
          asm volatile("fence.acq_rel.gpu;" ::: "memory");
          asm volatile("fence.proxy.async.global;" ::: "memory");
        }
        const uint32_t stg = sb + OFF_STG + w * 32768;
        const int nu = 5 + rank;
#pragma unroll 1
        for (int u = 0; u < nu; u++) {
          const int t = u - rank;
          if (t == 0 || t == 2) {
            if (elect()) mbar_expect(bars + 8 * (B_RFULL + w), 16384);
            mbar_wait(bars + 8 * (B_SFULL + w), u & 1);
            mbar_wait(bars + 8 * (B_RFREE + w), t >> 1);
            if (elect())
              asm volatile("{.reg .b32 ra, rb; mapa.shared::cluster.u32 ra, %0, %3; mapa.shared::cluster.u32 rb, %2, %3;\n"
                           "cp.async.bulk.shared::cluster.shared::cta.mbarrier::complete_tx::bytes [ra], [%1], 16384, [rb];}" ::"r"(stg + 16384),
                           "r"(stg), "r"(bars + 8 * (B_RFULL + w)), "r"(rank ^ 1) : "memory");
            mbar_wait(bars + 8 * (B_RFULL + w), t >> 1);
            if (elect()) mbar_arrive_cta(bars + 8 * (B_SFREE + w), rank ^ 1);
          } else {
            mbar_wait(bars + 8 * (B_SFULL + w), u & 1);
            const bool d = u == (rank ? 0 : 4), hf = rank && u >= 4;
            const int n0 = d ? 512 : rank * 256 + (((min(t, 3) >> 1) ^ (j >> 1)) & 1) * 128 + (u == 5 ? 64 : 0);
            const uint32_t src = d && !rank ? sb + w * SLOT : stg + (u == 5 ? 16384 : 0);
            if (elect()) {
#pragma unroll 1
              for (int b = 0; b < (d || hf ? 2 : 4); b++) {
                asm volatile("cp.reduce.async.bulk.tensor.4d.global.shared::cta.add.tile.bulk_group [%0, {%1,%2,%2,%3}], [%4];" ::"l"(&prm.tOut), "r"(n0 + b * 32), "r"(0),
                             "r"(m * 16 + w * 8), "r"(src + b * 8192) : "memory");
                asm volatile("cp.async.bulk.commit_group;" ::: "memory");
                if (u < nu - 1) asm volatile("cp.async.bulk.wait_group.read 0;" ::: "memory");
              }
              if (u < 3) {
                asm volatile("cp.async.bulk.wait_group.read 0;" ::: "memory");
                mbar_arrive(bars + 8 * (B_SFREE + w));
                if (t == 1) mbar_arrive_cta(bars + 8 * (B_RFREE + w), rank ^ 1);
              }
              if (u == nu - 1) asm volatile("cp.async.bulk.wait_group.read 0;" ::: "memory");
            }
          }
          __syncwarp();
        }
      }
    }
  } else {
    asm volatile("setmaxnreg.inc.sync.aligned.u32 240;");
    const uint32_t sb = smem_base(), bars = sb + OFF_BAR;
    const int wg = warp >> 2, w4 = warp & 3;
    const int lane = threadIdx.x & 31, g = lane >> 2, q = lane & 3;
    const uint32_t hw = sb + OFF_H + wg * 65536;

    int s = 0, nst = NST + 2; uint32_t ph = 0;
    auto release = [&](int st) { if (w4 == 0) { if (elect()) mbar_arrive(bars + 8 * (B_EMPTY + st)); } };
    const uint32_t dring = (sb & 0x3FFFF) >> 4;
    uint32_t dlo; int prev = 0;
    auto stage_begin = [&]() { mbar_wait(bars + 8 * (B_FULL + s), ph); dlo = dring + s * (SLOT >> 4); wg_fence(); };
    auto advance = [&]() { if (++s == nst) { s = 0; ph ^= 1; } };
    auto stage_end = [&](bool rel) {
      wg_commit();
      if (rel) { wg_wait<1>(); release(prev); }
      prev = s;
      advance();
    };

    uint32_t xa[144];
    uint32_t xr[18], dk[9];
    uint32_t rh[2], cc[2];
#pragma unroll
    for (int i = 0; i < 9; i++) dk[i] = __ldg((const uint32_t*)(prm.dskip + j * 72 + i * 8 + q * 2));
    {
      const int r = w4 * 16 + (lane & 7) + ((lane >> 3) & 1) * 8;
      const uint32_t ro = r * 128, cx = ((lane >> 4) ^ (lane & 7)) << 4;
      float s1[2][4] = {};
      auto load = [&](int kb, uint32_t base) {
#pragma unroll
        for (int kk = 0; kk < 4; kk++) {
          const int i = (kb * 4 + kk) * 4;
          asm volatile("ldmatrix.sync.aligned.m8n8.x4.shared.b16 {%0,%1,%2,%3}, [%4];"
                       : "=r"(xa[i]), "=r"(xa[i + 1]), "=r"(xa[i + 2]), "=r"(xa[i + 3]) : "r"(base + ro + (cx ^ (kk << 5))) : "memory");
        }
      };
      float s2[4] = {}, s3[4] = {};
      auto sums = [&](int kb) {
#pragma unroll
        for (int kk = 0; kk < 4; kk += 2) {
          const int i = (kb * 4 + kk) * 4;
          uint32_t a[8];
#pragma unroll
          for (int e = 0; e < 8; e++) asm("mul.rn.bf16x2 %0, %1, %1;" : "=r"(a[e]) : "r"(xa[i + e]));
          mma16816(s3, a[4], a[5], a[6], a[7], 0x3f803f80u, 0x3f803f80u);
          mma16816(s1[0], xa[i], xa[i + 1], xa[i + 2], xa[i + 3], 0x3f803f80u, 0x3f803f80u);
          mma16816(s2, a[0], a[1], a[2], a[3], 0x3f803f80u, 0x3f803f80u);
          mma16816(s1[1], xa[i + 4], xa[i + 5], xa[i + 6], xa[i + 7], 0x3f803f80u, 0x3f803f80u);
        }
      };
#pragma unroll
      for (int i = 0; i < 9; i++) {
        const int c8 = j * 9 + i, kb = c8 >> 3;
        xr[2 * i] = (kb < 8 ? hw + kb * 8192 : sb + wg * 8192) + (w4 * 16 + g) * 128 + (((c8 & 7) ^ g) << 4) + q * 4;
        asm volatile("" : "+r"(xr[2 * i]));
      }
      mbar_wait(bars + 8 * B_X8, 0);
      load(8, sb + wg * 8192);
      auto pin = [&]() { asm volatile("{.reg .pred p; .reg .u32 c, z; mov.u32 c, %clock; mov.u32 z, %ntid.y; setp.eq.u32 p, z, 0; @p st.shared.u32 [c], c;}" ::: "memory"); };
#pragma unroll
      for (int kp = 0; kp < 4; kp++) {
        mbar_wait(bars + 8 * (B_X + wg * 4 + kp), 0);
        load(2 * kp, hw + 2 * kp * 8192);
        load(2 * kp + 1, hw + (2 * kp + 1) * 8192);
        if (kp == 3) {
#pragma unroll
          for (int i = 0; i < 9; i++) { xr[2 * i + 1] = lds32(xr[2 * i] + 1024); xr[2 * i] = lds32(xr[2 * i]); }
        }
        if (kp == 0) sums(8); else { sums(2 * kp - 2); sums(2 * kp - 1); }
      }
      asm volatile("fence.proxy.async.shared::cta;" ::: "memory");
      bar_arrive(NB_XDONE + wg, 160);
      if (wg == 1) bar_arrive(NB_STATS, 256);
      pin();
      sums(6);
      sums(7);
      pin();
#pragma unroll
      for (int e = 0; e < 2; e++) {
        const float mu = (s1[0][2 * e + 1] + s1[1][2 * e + 1]) * (1.f / kD);
        const float var = fmaxf(fmaf(-mu, mu, (s2[2 * e] + s3[2 * e]) * (1.f / kD)), 0.f);
        float sd, r;
        asm("sqrt.approx.ftz.f32 %0, %1;" : "=f"(sd) : "f"(rbf(rbf(var) + 1e-5f)));
        asm("rcp.approx.ftz.f32 %0, %1;" : "=f"(r) : "f"(rbf(sd)));
        rh[e] = pack_bf16(0.5f * r, 0.5f * r);
        cc[e] = pack_bf16(mu, mu);
      }
    }

    auto normalise = [&](int kb) {
#pragma unroll
      for (int i = 0; i < 16; i++) asm("{.reg .b32 d; sub.rn.bf16x2 d, %0, %2; mul.rn.bf16x2 %0, d, %1;}" : "+r"(xa[16 * kb + (i >> 3) + 2 * (i & 7)]) : "r"(rh[i >> 3]), "r"(cc[i >> 3]));
    };
    {
      float ab[36];
      float* op = prm.out + (size_t)(m * 128 + wg * 64 + w4 * 16 + g) * kD + j * 72 + q * 2;
      auto residual = [&](int i) {
        asm volatile("add.rn.bf16x2 %0, %0, %0;" : "+r"(dk[i]));
#pragma unroll
        for (int e = 0; e < 2; e++) {
          uint32_t t;
          asm("{.reg .b32 d; sub.rn.bf16x2 d, %1, %3; mul.rn.bf16x2 %0, d, %2;}" : "=r"(t) : "r"(xr[2 * i + e]), "r"(rh[e]), "r"(cc[e]));
          asm("fma.rn.bf16x2 %0, %0, %1, %2;" : "+r"(t) : "r"(dk[i]), "r"(xr[2 * i + e]));
          *(float2*)(op + e * 8 * kD + i * 8) = make_float2(bflo(t), bfhi(t));
        }
      };
      const uint32_t da = sb + OFF_DUMP + wg * HS_BYTES + (w4 * 16 + g) * 16 + q * 4;
      auto dump = [&](int im) {
#pragma unroll
        for (int i = 0; i < 18; i++)
          asm volatile("st.shared.b32 [%0], %1;" ::"r"(da + (i < 16 ? 8 * im + (i >> 1) : 16 + im) * HS_LBO + (i & 1) * 128), "r"(pack_bf16(ab[2 * i], ab[2 * i + 1])) : "memory");
      };
      auto bu = [&](int kb, uint32_t off) {
        wg_fence();
#pragma unroll
        for (int kk = 0; kk < 4; kk++) { const int i = (kb * 4 + kk) * 4; wgmma_n72_rs_tb0(ab, xa[i], xa[i + 1], xa[i + 2], xa[i + 3], desc((dring + (off >> 4) + kk * 2) + DLO_K, DHI_SW128), (kb | kk) != 0); }
        wg_commit();
      };
      normalise(0);
      if (wg == 0) {
#pragma unroll
        for (int kb = 1; kb < 9; kb++) normalise(kb);
        bar_sync(NB_STATS, 256);
      }
#pragma unroll
      for (int kb = 0; kb < 9; kb++) {
        if ((kb & 3) == 0) mbar_wait(bars + 8 * (B_BU + (kb >> 2)), 0);
        bu(kb, kb < 8 ? OFF_BU0 + kb * 9216 : OFF_BU1);
        if (wg == 0) residual(kb);
        else if (kb < 8) normalise(kb + 1);
      }
      wg_wait<0>();
      if (w4 == 0) { if (elect()) mbar_arrive(bars + 8 * B_RING); }
      keep(ab);
      dump(0);
#pragma unroll
      for (int kb = 0; kb < 9; kb++) {
        if (kb == 4) mbar_wait(bars + 8 * (B_BU + 3), 0);
        bu(kb, kb < 4 ? OFF_BU1 + (kb + 1) * 9216 : OFF_BU2 + (kb - 4) * 9216);
        if (wg == 1) residual(kb);
        if (kb == 5) { wg_wait<2>(); if (w4 == 0) { if (elect()) mbar_arrive(bars + 8 * (B_RING + 1)); } }
      }
      wg_wait<0>();
      keep(ab);
      dump(1);
      bar_arrive(NB_DUMP, 352);
    }

    float acc[64];
    {
      const uint32_t ha = sb + OFF_H + (threadIdx.x & 127) * 16, hblk = wg ? HBLK1 : HBLK0;
      auto glu = [&](int i) {
        return pack_bf16(fmaf(acc[32 + 2 * i], tanh_fast(acc[2 * i]), acc[32 + 2 * i]), fmaf(acc[33 + 2 * i], tanh_fast(acc[2 * i + 1]), acc[33 + 2 * i]));
      };
      for (int c = 0; c < 8; c++) {
        if (wg == 1) bar_sync(NB_SKEW, 256);
#pragma unroll
        for (int kb = 0; kb < 9; kb++) {
          if (kb == 6 && c == 3) nst = 7;
          if (kb == 5 && c == 7) nst = 6;
          stage_begin();
#pragma unroll
          for (int kk = 0; kk < 4; kk++) { const int i = (kb * 4 + kk) * 4; wgmma_n128_rs_tb1(acc, xa[i], xa[i + 1], xa[i + 2], xa[i + 3], desc((dlo + kk * 128) + DLO_MN, DHI_SW128), (kb | kk) != 0); }
          if (kb == SKEW - 1 && wg == 0) bar_arrive(NB_SKEW, 256);
          if (kb == 8 && c >= 3 && c != 6) mbar_wait(bars + 8 * (c == 3 ? B_EMPTY + 7 : c == 7 ? B_EMPTY + 6 : B_SCAN - 4 + c), c == 3);
          stage_end(kb > 0);
        }
        wg_wait<0>();
        release(prev);
        keep(acc);
        const uint32_t hc = ha + ((hblk >> (4 * c)) & 15) * 8192;
#pragma unroll
        for (int i = 0; i < 4; i++) sts128(hc + i * 2048, glu(4 * i), glu(4 * i + 1), glu(4 * i + 2), glu(4 * i + 3));
      }
      if (wg == 1) bar_sync(NB_SKEW, 256);
#pragma unroll
      for (int kb = 0; kb < 9; kb++) {
        stage_begin();
#pragma unroll
        for (int kk = 0; kk < 4; kk++) { const int i = (kb * 4 + kk) * 4; wgmma_n128_rs_tb1(acc, xa[i], xa[i + 1], xa[i + 2], xa[i + 3], desc((dlo + kk * 128) + DLO_MN, DHI_SW128), (kb | kk) != 0); }
        if (kb == SKEW - 1 && wg == 0) bar_arrive(NB_SKEW, 256);
        stage_end(kb > 0);
        if (kb > 0) {
          const uint32_t hc = ha + ((hblk >> (4 * (kb - 1))) & 15) * 8192;
#pragma unroll
          for (int i = 4 * (kb - 1); i < 4 * kb; i++) lds128_inplace(hc + (i & 3) * 2048, xa[4 * i], xa[4 * i + 1], xa[4 * i + 2], xa[4 * i + 3]);
        }
      }
      asm volatile("fence.proxy.async.shared::cta;" ::: "memory");
      bar_arrive(NB_HFREE, 288);
      wg_wait<0>();
      release(prev);
      keep(acc);
#pragma unroll
      for (int i = 0; i < 16; i++) xa[128 + i] = glu(i);
    }

    const uint32_t dhs = (((sb + OFF_HS + wg * HS_MAIN) & 0x3FFFF) >> 4) | DLO_HS, drem = DLO_HS + wg * (HS_REM >> 4);
    const int rp = (g >> 2) + 2 * (g & 3);
    const uint32_t so = w4 * 2048 + rp * 128 + (q & 1) * 8, sx = ((q >> 1) ^ rp) << 4;
    const uint32_t rcv = sb + OFF_STG + wg * 32768 + 16384 + w4 * 2048 + lane * 16;
    auto staged = [&]() {
      asm volatile("fence.proxy.async.shared::cta;" ::: "memory");
      __syncwarp();
      if (elect()) mbar_arrive(bars + 8 * (B_SFULL + wg));
    };
    auto half_tile = [&](const bool first, const int kind) {
      float a2[32];
      if (wg == 1) { if (!first) staged(); bar_sync(NB_SKEW, 256); }
      const uint32_t ph0 = ph;
      uint32_t d4;
#pragma unroll
      for (int kp = 0; kp < 5; kp++) {
        stage_begin();
#pragma unroll
        for (int kk = 0; kk < (kp < 4 ? 8 : 4); kk++) { const int i = (kp * 8 + kk) * 4; wgmma_n64_rs_tb1(a2, xa[i], xa[i + 1], xa[i + 2], xa[i + 3], desc((dlo + kk * 128) + DLO_MN, DHI_SW128), (kp | kk) != 0); }
        if (kp == 2 && wg == 0) bar_arrive(NB_SKEW, 256);
        d4 = dlo;
        stage_end(kp > 0);
        if (kp == 0 && !first && wg == 0) staged();
      }
      if (first) mbar_wait(bars + 8 * B_HSFULL, 0);
      stage_begin();
#pragma unroll
      for (int kk = 0; kk < 8; kk++) wgmma_n64_ss_tb0(a2, desc(dhs + kk * (2 * HS_LBO >> 4), DHI_NONE), desc((dlo + (kk >> 2) * 512 + (kk & 3) * 2) + DLO_K, DHI_SW128), 1);
      wgmma_n64_ss_tb0(a2, desc(d4 + 640 + drem, DHI_NONE), desc((d4 + 512) | ((1024 >> 4) << 16), DHI_NONE), 1);
      wg_commit();
      if (!first) {
        if (kind == 1) mbar_wait(bars + 8 * (B_EMPTY + wg), ph0 ^ 1);
        if (kind == 2) { mbar_wait(bars + 8 * (B_SFREE + wg), 1); mbar_wait(bars + 8 * (B_RFULL + wg), 1); }
      }
      wg_wait<0>();
      release(prev); release(s); advance();
      keep(a2);
      if (!first && kind >= 2) {
#pragma unroll
        for (int i = 0; i < 4; i++) {
          uint32_t v[4];
          lds128(rcv + (kind & 1) * 8192 + i * 512, v[0], v[1], v[2], v[3]);
#pragma unroll
          for (int e = 0; e < 4; e++) { a2[8 * i + 2 * e] += bflo(v[e]); a2[8 * i + 2 * e + 1] += bfhi(v[e]); }
        }
        __syncwarp();
      }
      const uint32_t stg = (!first && kind == 1 ? sb + wg * SLOT : sb + OFF_STG + wg * 32768 + (kind == 3 ? 16384 : 0)) + so;
#pragma unroll
      for (int i = 0; i < 8; i++) {
        const uint32_t a = stg + (i >> 2) * 8192 + (sx ^ ((i & 3) << 5));
        sts64f(a, a2[4 * i], a2[4 * i + 1]);
        sts64f(a + 1024, a2[4 * i + 2], a2[4 * i + 3]);
      }
    };
    if (rank) half_tile(true, 0);
    for (int t = 0; t < 4 - rank; t++) {
      if (wg == 1) { if (t + rank > 0) staged(); bar_sync(NB_SKEW, 256); }
#pragma unroll
      for (int kb = 0; kb < 9; kb++) {
        if ((kb == 5 && t == 0 && rank) || (kb == 1 && t == 1)) nst = NST + 1;
        if (t == 1 && ((kb == 1 && rank) || kb == 7)) nst = NST + 2;
        stage_begin();
#pragma unroll
        for (int kk = 0; kk < 4; kk++) { const int i = (kb * 4 + kk) * 4; wgmma_n128_rs_tb1(acc, xa[i], xa[i + 1], xa[i + 2], xa[i + 3], desc((dlo + kk * 128) + DLO_MN, DHI_SW128), (kb | kk) != 0); }
        if (kb == SKEW - 1 && wg == 0) bar_arrive(NB_SKEW, 256);
        stage_end(kb > 0);
        if (kb == 3 && t + rank > 0 && wg == 0) staged();
      }
      if (t == 0) mbar_wait(bars + 8 * B_HSFULL, 0);
      stage_begin();
#pragma unroll
      for (int kk = 0; kk < 4; kk++) wgmma_n128_ss_tb0(acc, desc(dhs + kk * (2 * HS_LBO >> 4), DHI_NONE), desc((dlo + kk * 2) + DLO_K, DHI_SW128), 1);
      stage_end(true);
      stage_begin();
#pragma unroll
      for (int kk = 0; kk < 4; kk++) wgmma_n128_ss_tb0(acc, desc(dhs + (4 + kk) * (2 * HS_LBO >> 4), DHI_NONE), desc((dlo + kk * 2) + DLO_K, DHI_SW128), 1);
      const int s_im = s;
      advance();
      stage_begin();
      wgmma_n128_ss_tb0(acc, desc(dlo + 256 + drem, DHI_NONE), desc(dlo | ((2048 >> 4) << 16), DHI_NONE), 1);
      stage_end(true);
      if (t + rank > 0) mbar_wait(bars + 8 * (B_SFREE + wg), (t + rank - 1) & 1);
      uint32_t pv[8];
      if (t & 1) {
        mbar_wait(bars + 8 * (B_RFULL + wg), t >> 1);
#pragma unroll
        for (int i = 0; i < 2; i++) lds128(rcv + i * 512, pv[4 * i], pv[4 * i + 1], pv[4 * i + 2], pv[4 * i + 3]);
      }
      wg_wait<0>();
      release(s_im); release(prev);
      keep(acc);
      if (t & 1) {
        const uint32_t stg = sb + OFF_STG + wg * 32768 + so;
        auto add = [&](int i, const uint32_t* v) {
#pragma unroll
          for (int e = 0; e < 4; e++) { acc[8 * i + 2 * e] += bflo(v[e]); acc[8 * i + 2 * e + 1] += bfhi(v[e]); }
        };
        auto put = [&](int i) {
          const uint32_t a = stg + (i >> 2) * 8192 + (sx ^ ((i & 3) << 5));
          sts64f(a, acc[4 * i], acc[4 * i + 1]);
          sts64f(a + 1024, acc[4 * i + 2], acc[4 * i + 3]);
        };
        uint32_t v[8];
        lds128(rcv + 1024, v[0], v[1], v[2], v[3]); lds128(rcv + 1536, v[4], v[5], v[6], v[7]);
        add(0, pv); add(1, pv + 4);
        lds128(rcv + 8192, pv[0], pv[1], pv[2], pv[3]); lds128(rcv + 8192 + 512, pv[4], pv[5], pv[6], pv[7]);
#pragma unroll
        for (int i = 0; i < 4; i++) put(i);
        add(2, v); add(3, v + 4);
        lds128(rcv + 8192 + 1024, v[0], v[1], v[2], v[3]); lds128(rcv + 8192 + 1536, v[4], v[5], v[6], v[7]);
#pragma unroll
        for (int i = 4; i < 8; i++) put(i);
        add(4, pv); add(5, pv + 4);
        __syncwarp();
#pragma unroll
        for (int i = 8; i < 12; i++) put(i);
        add(6, v); add(7, v + 4);
        __syncwarp();
#pragma unroll
        for (int i = 12; i < 16; i++) put(i);
      } else {
#pragma unroll
        for (int i = 0; i < 8; i++)
          sts128(rcv - 16384 + (i >> 2) * 8192 + (i & 3) * 512, pack_bf16(acc[8 * i], acc[8 * i + 1]), pack_bf16(acc[8 * i + 2], acc[8 * i + 3]),
                 pack_bf16(acc[8 * i + 4], acc[8 * i + 5]), pack_bf16(acc[8 * i + 6], acc[8 * i + 7]));
      }
    }
#pragma unroll 1
    for (int kind = 1 + rank; kind < 2 + 2 * rank; kind++) half_tile(false, kind);
    staged();
  }
}

typedef CUresult (*EncodeFn)(CUtensorMap*, CUtensorMapDataType, cuuint32_t, void*, const cuuint64_t*, const cuuint64_t*, const cuuint32_t*,
                             const cuuint32_t*, CUtensorMapInterleave, CUtensorMapSwizzle, CUtensorMapL2promotion, CUtensorMapFloatOOBfill);

void map2d(EncodeFn enc, CUtensorMap* tm, const void* p, uint64_t cols, uint64_t rows, uint32_t bc, uint32_t br, CUtensorMapSwizzle sw) {
  cuuint64_t gd[2] = {cols, rows}, gs[1] = {cols * 2};
  cuuint32_t bd[2] = {bc, br}, es[2] = {1, 1};
  enc(tm, CU_TENSOR_MAP_DATA_TYPE_BFLOAT16, 2, (void*)p, gd, gs, bd, es, CU_TENSOR_MAP_INTERLEAVE_NONE, sw,
      sw == CU_TENSOR_MAP_SWIZZLE_128B ? CU_TENSOR_MAP_L2_PROMOTION_L2_128B : CU_TENSOR_MAP_L2_PROMOTION_NONE, CU_TENSOR_MAP_FLOAT_OOB_FILL_NONE);
}

}

extern "C" void kernel_launch(void* const* d_in, const int* in_sizes, int n_in, void* d_out, int out_size) {
  (void)in_sizes; (void)n_in; (void)out_size;
  static EncodeFn enc = nullptr;
  if (!enc) {
    cudaDriverEntryPointQueryResult qr;
    cudaGetDriverEntryPoint("cuTensorMapEncodeTiled", (void**)&enc, cudaEnableDefault, &qr);
    cudaFuncSetAttribute(fused_kernel, cudaFuncAttributeMaxDynamicSharedMemorySize, SMEM_BYTES);
  }
  Params prm;
  const CUtensorMapSwizzle S128 = CU_TENSOR_MAP_SWIZZLE_128B;
  map2d(enc, &prm.tx, d_in[0], kD, kS, 64, 64, S128);
  map2d(enc, &prm.tBre, d_in[3], kD, 576, 64, 72, S128);
  map2d(enc, &prm.tBim, d_in[4], kD, 576, 64, 72, S128);
  map2d(enc, &prm.tCre, d_in[5], 576, kD, 64, 64, S128);
  map2d(enc, &prm.tCim, d_in[6], 576, kD, 64, 64, S128);
  map2d(enc, &prm.tCre8, d_in[5], 576, kD, 8, 64, CU_TENSOR_MAP_SWIZZLE_NONE);
  map2d(enc, &prm.tCim8, d_in[6], 576, kD, 8, 64, CU_TENSOR_MAP_SWIZZLE_NONE);
  map2d(enc, &prm.tWg, d_in[10], kF, kD, 64, 64, S128);
  map2d(enc, &prm.tWu, d_in[11], kF, kD, 64, 64, S128);
  map2d(enc, &prm.tWd, d_in[12], kD, kF, 64, 64, S128);
  {
    cuuint64_t gd[4] = {kD, 2, 4, kS / 8}, gs[3] = {4 * kD * 4, kD * 4, 8 * kD * 4};
    cuuint32_t bd[4] = {32, 2, 4, 8}, es[4] = {1, 1, 1, 1};
    enc(&prm.tOut, CU_TENSOR_MAP_DATA_TYPE_FLOAT32, 4, d_out, gd, gs, bd, es, CU_TENSOR_MAP_INTERLEAVE_NONE, S128, CU_TENSOR_MAP_L2_PROMOTION_NONE,
        CU_TENSOR_MAP_FLOAT_OOB_FILL_NONE);
  }
  prm.lre = (const __nv_bfloat16*)d_in[1];
  prm.lim = (const __nv_bfloat16*)d_in[2];
  prm.bre = (const __nv_bfloat16*)d_in[3];
  prm.bim = (const __nv_bfloat16*)d_in[4];
  prm.cre = (const __nv_bfloat16*)d_in[5];
  prm.cim = (const __nv_bfloat16*)d_in[6];
  prm.wg = (const __nv_bfloat16*)d_in[10];
  prm.wu = (const __nv_bfloat16*)d_in[11];
  prm.wd = (const __nv_bfloat16*)d_in[12];
  prm.ldt = (const __nv_bfloat16*)d_in[7];
  prm.dskip = (const __nv_bfloat16*)d_in[8];
  prm.out = (float*)d_out;

  fused_kernel<<<128, 384, SMEM_BYTES, cudaStreamPerThread>>>(prm);
}
```
